```python
import torch

def _softmax(x, axis=-1):
    return torch.softmax(x, dim=axis)

def _gelu(x):
    return torch.nn.functional.gelu(x, approximate='tanh')

def _silu(x):
    return torch.nn.functional.silu(x)

def _sigmoid(x):
    return torch.sigmoid(x)

def _layernorm(x, axis=-1, eps=1e-05):
    m = x.mean(dim=axis, keepdim=True)
    v = x.var(dim=axis, keepdim=True, unbiased=False)
    return (x - m) / torch.sqrt(v + eps)

def _scatter_add(tgt, idx, src, axis=0):
    return tgt.clone().index_add_(axis, idx, src)

def _segment_sum(src, seg, n):
    out = torch.zeros((n,) + src.shape[1:], dtype=src.dtype)
    return out.index_add_(0, seg, src)

def _pad(x, pw):
    flat = tuple((v for pair in reversed(pw) for v in pair))
    return torch.nn.functional.pad(x, flat)
kernel_name = 'interleave_layers__sliding_local_dilated__mixer_gmlp__prompt'

def setup_inputs():

    _w = lambda a: (lambda t: t.to(torch.bfloat16) if t.is_floating_point() else t)(torch.as_tensor(a))

    def _A_setup():
        B, S, D = (1, 2048, 576)
        return {'x': _w((lambda *s: torch.randn(*s, dtype=torch.bfloat16) * 0.05)(B, S, D)), 'wqkv': _w((lambda *s: torch.randn(*s, dtype=torch.bfloat16) * 0.05)(D, 3 * D)), 'wo': _w((lambda *s: torch.randn(*s, dtype=torch.bfloat16) * 0.05)(D, D))}
    _A_in = _A_setup()

    def _B_setup():
        B, S, D, F = (1, 2048, 576, 4608)
        Fh = F // 2
        return {'x': _w((lambda *s: torch.randn(*s, dtype=torch.bfloat16) * 0.05)(B, S, D)), 'w_in': _w((lambda *s: torch.randn(*s, dtype=torch.bfloat16) * 0.2)(D, 2 * Fh)), 'w_sp': _w(0.01 * (lambda *s: torch.randn(*s, dtype=torch.bfloat16) * 0.2)(S, S)), 'b_sp': _w(1.0 + 0.01 * (lambda *s: torch.randn(*s, dtype=torch.bfloat16) * 0.05)(S)), 'w_out': _w((lambda *s: torch.randn(*s, dtype=torch.bfloat16) * 0.05)(Fh, D))}
    _B_in = _B_setup()
    return {'A_x': _A_in['x'], 'A_wqkv': _A_in['wqkv'], 'A_wo': _A_in['wo'], 'B_x': _B_in['x'], 'B_w_in': _B_in['w_in'], 'B_w_sp': _B_in['w_sp'], 'B_b_sp': _B_in['b_sp'], 'B_w_out': _B_in['w_out']}

def reference(A_x, A_wqkv, A_wo, B_x, B_w_in, B_w_sp, B_b_sp, B_w_out):

    def _A_ref(x, wqkv, wo):
        B, S, D = x.shape
        H = 32
        Dh = D // H
        W, dil = (8, 2)
        qkv = (lambda x, *d: x.permute(*d))((x @ wqkv).reshape(B, S, 3, H, Dh), 2, 0, 3, 1, 4)
        q, k, v = (qkv[0], qkv[1], qkv[2])
        scale = Dh ** (-0.5)
        pos = torch.arange(S)
        off = torch.arange(W) * dil
        idx = pos[:, None] - off[None, :]
        mask = idx >= 0
        idx_c = torch.where(mask, idx, 0).reshape(-1)
        kg = k[:, :, idx_c, :].reshape(B, H, S, W, Dh)
        vg = v[:, :, idx_c, :].reshape(B, H, S, W, Dh)
        logits = torch.einsum('bhsd,bhswd->bhsw', q, kg) * scale
        logits = torch.where(mask[None, None, :, :], logits, -1000000000.0)
        attn = _softmax(logits, axis=-1)
        o = torch.einsum('bhsw,bhswd->bhsd', attn, vg)
        return (lambda x, *d: x.permute(*d))(o, 0, 2, 1, 3).reshape(B, S, D) @ wo

    def _B_ref(x, w_in, w_sp, b_sp, w_out):
        B, S, D = x.shape
        F = w_in.shape[-1]
        Fh = F // 2
        z = _gelu(torch.einsum('bsd,df->bsf', x, w_in))
        z1 = z[..., :Fh].clone()
        z2 = _layernorm(z[..., Fh:], axis=-1)
        g = torch.einsum('ts,bsf->btf', w_sp, z2) + b_sp[None, :, None]
        return torch.einsum('bsf,fd->bsd', z1 * g, w_out)
    x = A_x
    x = x + _A_ref(_layernorm(x, axis=-1), A_wqkv, A_wo)
    x = x + _B_ref(_layernorm(x, axis=-1), B_w_in, B_w_sp, B_b_sp, B_w_out)
    x = x + _A_ref(_layernorm(x, axis=-1), A_wqkv, A_wo)
    x = x + _B_ref(_layernorm(x, axis=-1), B_w_in, B_w_sp, B_b_sp, B_w_out)
    return x
```

```cpp
#include <cuda_runtime.h>
#include <cuda.h>
#include <cuda_bf16.h>
#include <stdint.h>

#define MK_TRACE 0
#define MK_DBG 0
#define P5TRACE 0
#define LAG1 1
#define C0S 32.f
#define OFM 0x10u
#define NC2 2
#define NC1 6
#define XRLX 0
#define PDEL 8
#define LD1 4
#define LD2 2
#define ZD1 8
#define ZD2 8
#define WPF 1
#define YPACE 2
#define HO2 8
#define SPL 4
#define XP0 0
#define EFM 0x33333022
#define EF(i) ((((EFM >> (4 * (i))) & 3) == 3) || (((EFM >> (4 * (i))) >> L) & 1))
#define APACE 7
#define HO3 1
#define PPK 13

namespace mk {

constexpr int SEQ = 2048, DM = 576, FH = 2304;
constexpr int NCTA = 128;
constexpr int NGRID = 132;
constexpr uint32_t ZB = 36864;
constexpr uint32_t WQ_SL = 72 * 3456;
constexpr uint32_t WO_SL = 72 * 1152;
constexpr float LN_EPS = 1e-5f;
constexpr float GA = 0.3292034911525734f, GB = 2.423681954311584f;

constexpr uint32_t ST_BYTES = 53248, ST_B = 16384, NST = 4;
constexpr uint32_t SM_STG = NST * ST_BYTES;
constexpr uint32_t SM_BAR = SM_STG + 2 * 9216, B_OFF = 896;
constexpr uint32_t SM_OFF = SM_BAR + B_OFF;
constexpr uint32_t SM_TOTAL = SM_BAR + 1024;
constexpr uint32_t SM_RT = SM_STG + 9216, SM_CV = SM_STG + 17408, SM_WT = SM_STG;
constexpr uint32_t SM_WOI = 44032, SM_CSQ = 49280, SM_XST = 50176;
enum { EV_PT = 0, EV_O = 1, EV_X1 = 2, EV_ZN = 3, EV_Z1 = 4, EV_P4 = 5, EV_XS = 6, EV_N = 7 };
constexpr uint32_t B_FULL = 0, B_FULLA = 32, B_RES = 96, B_WT = 112, B_GATE3 = 128, B_Z1 = 136, B_ZOK = 144, B_CV = 152, B_XRW = 168, B_F3 = 184, B_WF = 232, B_OF = 240,
                   B_RT = 320, B_AF3 = 352, B_RB = 544,
                   B_AD = 576, B_S5 = 608, B_AV = 616,
                   B_CSQ = 744,
                   B_LAG = 752, B_X3 = 760, B_ZS = 768, B_EVT = 784,
                   B_IMG = 912, B_WOI = 920, B_E3 = 928, B_XD = 976,
                   B_EMPTY = 992;
constexpr uint32_t SM_B3 = 9 * 16384, SM_ZP3 = SM_STG + 8192;

enum { FR_X2 = 0, FR_O = 1, FR_X1 = 3, FR_XR = 5, FR_EP = 16, FJ = 32 * 32, FJ_WQ = 0, FJ_WO = 1, FJ_ZN = 3, FJ_P4 = 5, FJ_EP = 16, F_N = FJ + 8 * 32 };

__device__ __align__(1024) uint8_t g_Z[576 * ZB];
__device__ __align__(1024) uint8_t g_WQ[8 * WQ_SL];
__device__ __align__(1024) uint8_t g_WO[8 * WO_SL];
__device__ __align__(1024) float g_CSP[2 * NCTA * 216];
__device__ __align__(1024) uint2 g_RT[SEQ];
__device__ __align__(1024) uint4 g_XST[2 * SEQ];
__device__ __align__(1024) uint4 g_ST1[SEQ * 4];
__device__ __align__(1024) uint4 g_ZST[SEQ * 4];
__device__ __align__(1024) uint4 g_HALO[32 * 8 * 6 * 32];
__device__ __align__(1024) uint32_t g_flags[F_N];

struct Params {
  CUtensorMap wsp, winb[2], wins, wout;
  CUtensorMap act[2];
  CUtensorMap res[2];
  CUtensorMap red;
  const __nv_bfloat16 *wqkv, *wo, *w_in, *w_sp, *b_sp, *w_out;
  uint8_t* xs[2];
  int role[NGRID / 2];
  uint32_t zero;
};

__device__ __forceinline__ uint32_t smem_u32(const void* p) { return (uint32_t)__cvta_generic_to_shared(p); }
__device__ __forceinline__ void mbar_init(uint32_t bar, uint32_t cnt) { asm volatile("mbarrier.init.shared::cta.b64 [%0], %1;" ::"r"(bar), "r"(cnt)); }
__device__ __forceinline__ void mbar_arrive(uint32_t bar) { asm volatile("mbarrier.arrive.shared::cta.b64 _, [%0];" ::"r"(bar) : "memory"); }
__device__ __forceinline__ void mbar_wait(uint32_t bar, uint32_t parity) {
  asm volatile(
      "{\n.reg .pred p;\n.reg .u32 c;\nmov.u32 c, 0;\nLAB_WAIT:\n"
      "mbarrier.try_wait.parity.shared::cta.b64 p, [%0], %1;\n@p bra LAB_DONE;\n"
      "add.u32 c, c, 1;\nsetp.lt.u32 p, c, 0x100000;\n@p bra LAB_WAIT;\ntrap;\nLAB_DONE:\n}" ::"r"(bar), "r"(parity)
      : "memory");
}
__device__ __forceinline__ void mbar_wait_c(uint32_t bar, uint32_t parity) {
  asm volatile("{\n.reg .pred p;\nLAB_WAIT:\nmbarrier.try_wait.parity.shared::cta.b64 p, [%0], %1;\n@!p bra LAB_WAIT;\n}" ::"r"(bar), "r"(parity) : "memory");
}
__device__ __forceinline__ void flag_wait(const uint32_t* f, uint32_t target) {
  asm volatile(
      "{\n.reg .pred p;\n.reg .u32 c, v;\nmov.u32 c, 0;\nLAB_WAIT:\n"
      "ld.relaxed.gpu.global.u32 v, [%0];\nsub.u32 v, v, %1;\nsetp.ge.s32 p, v, 0;\n@p bra LAB_DONE;\n"
      "add.u32 c, c, 1;\nsetp.lt.u32 p, c, 0x400000;\n@p bra LAB_WAIT;\ntrap;\nLAB_DONE:\nfence.acquire.gpu;\n}" ::"l"(f), "r"(target)
      : "memory");
}
__device__ __forceinline__ void fence_gpu() { asm volatile("fence.acq_rel.gpu;" ::: "memory"); }
__device__ __forceinline__ void fence_async_g() { asm volatile("fence.proxy.async.global;" ::: "memory"); }
__device__ __forceinline__ void fence_async_s() { asm volatile("fence.proxy.async.shared::cta;" ::: "memory"); }
__device__ __forceinline__ uint32_t elect_one() {
  uint32_t p; asm volatile("{\n.reg .pred P;\nelect.sync _|P, 0xffffffff;\nselp.u32 %0, 1, 0, P;\n}" : "=r"(p)); return p;
}
__device__ __forceinline__ void expect_tx_p(uint32_t el, uint32_t bar, uint32_t bytes) {
  asm volatile("{\n.reg .pred P;\nsetp.ne.u32 P, %2, 0;\n@P mbarrier.arrive.expect_tx.shared::cta.b64 _, [%0], %1;\n}" ::"r"(bar), "r"(bytes), "r"(el) : "memory");
}
__device__ __forceinline__ void bulk_load_p(uint32_t el, uint32_t dst, const void* src, uint32_t bytes, uint32_t bar) {
  asm volatile("{\n.reg .pred P;\nsetp.ne.u32 P, %4, 0;\n@P cp.async.bulk.shared::cluster.global.mbarrier::complete_tx::bytes [%0], [%1], %2, [%3];\n}" ::"r"(dst), "l"(src), "r"(bytes), "r"(bar), "r"(el) : "memory");
}
__device__ __forceinline__ uint64_t policy_evict_first() { uint64_t p; asm("createpolicy.fractional.L2::evict_first.b64 %0, 1.0;" : "=l"(p)); return p; }
__device__ __forceinline__ void bulk_load_h(uint32_t el, uint32_t dst, const void* src, uint32_t bytes, uint32_t bar, bool ef, uint64_t pol) {
  if (ef) {
    asm volatile("{\n.reg .pred P;\nsetp.ne.u32 P, %4, 0;\n@P cp.async.bulk.shared::cluster.global.mbarrier::complete_tx::bytes.L2::cache_hint [%0], [%1], %2, [%3], %5;\n}" ::"r"(dst), "l"(src), "r"(bytes), "r"(bar), "r"(el), "l"(pol) : "memory");
  } else {
    asm volatile("{\n.reg .pred P;\nsetp.ne.u32 P, %4, 0;\n@P cp.async.bulk.shared::cluster.global.mbarrier::complete_tx::bytes [%0], [%1], %2, [%3];\n}" ::"r"(dst), "l"(src), "r"(bytes), "r"(bar), "r"(el) : "memory");
  }
}
__device__ __forceinline__ void bulk_mc_h(uint32_t el, uint32_t dst, const void* src, uint32_t bytes, uint32_t bar, bool ef, uint64_t pol) {
  if (ef) {
    asm volatile("{\n.reg .pred P;\nsetp.ne.u32 P, %4, 0;\n@P cp.async.bulk.shared::cluster.global.mbarrier::complete_tx::bytes.multicast::cluster.L2::cache_hint [%0], [%1], %2, [%3], %5, %6;\n}" ::"r"(dst), "l"(src), "r"(bytes), "r"(bar), "r"(el), "h"((uint16_t)3), "l"(pol) : "memory");
  } else {
    asm volatile("{\n.reg .pred P;\nsetp.ne.u32 P, %4, 0;\n@P cp.async.bulk.shared::cluster.global.mbarrier::complete_tx::bytes.multicast::cluster [%0], [%1], %2, [%3], %5;\n}" ::"r"(dst), "l"(src), "r"(bytes), "r"(bar), "r"(el), "h"((uint16_t)3) : "memory");
  }
}
__device__ __forceinline__ void tma3d_h(uint32_t el, uint32_t dst, const CUtensorMap* m, int c0, int c1, int c2, uint32_t bar, bool ef, uint64_t pol) {
  if (ef) {
    asm volatile("{\n.reg .pred P;\nsetp.ne.u32 P, %6, 0;\n@P cp.async.bulk.tensor.3d.shared::cluster.global.mbarrier::complete_tx::bytes.L2::cache_hint [%0], [%1, {%3, %4, %5}], [%2], %7;\n}" ::"r"(dst), "l"(m), "r"(bar), "r"(c0), "r"(c1), "r"(c2), "r"(el), "l"(pol) : "memory");
  } else {
    asm volatile("{\n.reg .pred P;\nsetp.ne.u32 P, %6, 0;\n@P cp.async.bulk.tensor.3d.shared::cluster.global.mbarrier::complete_tx::bytes [%0], [%1, {%3, %4, %5}], [%2];\n}" ::"r"(dst), "l"(m), "r"(bar), "r"(c0), "r"(c1), "r"(c2), "r"(el) : "memory");
  }
}
__device__ __forceinline__ void tma2d_mc_h(uint32_t el, uint32_t dst, const CUtensorMap* m, int c0, int c1, uint32_t bar, bool ef, uint64_t pol) {
  if (ef) {
    asm volatile("{\n.reg .pred P;\nsetp.ne.u32 P, %5, 0;\n@P cp.async.bulk.tensor.2d.shared::cluster.global.mbarrier::complete_tx::bytes.multicast::cluster.L2::cache_hint [%0], [%1, {%3, %4}], [%2], %6, %7;\n}" ::"r"(dst), "l"(m), "r"(bar), "r"(c0), "r"(c1), "r"(el), "h"((uint16_t)3), "l"(pol) : "memory");
  } else {
    asm volatile("{\n.reg .pred P;\nsetp.ne.u32 P, %5, 0;\n@P cp.async.bulk.tensor.2d.shared::cluster.global.mbarrier::complete_tx::bytes.multicast::cluster [%0], [%1, {%3, %4}], [%2], %6;\n}" ::"r"(dst), "l"(m), "r"(bar), "r"(c0), "r"(c1), "r"(el), "h"((uint16_t)3) : "memory");
  }
}
__device__ __forceinline__ void tma3d_mc_h(uint32_t el, uint32_t dst, const CUtensorMap* m, int c0, int c1, int c2, uint32_t bar, bool ef, uint64_t pol) {
  if (ef) {
    asm volatile("{\n.reg .pred P;\nsetp.ne.u32 P, %6, 0;\n@P cp.async.bulk.tensor.3d.shared::cluster.global.mbarrier::complete_tx::bytes.multicast::cluster.L2::cache_hint [%0], [%1, {%3, %4, %5}], [%2], %7, %8;\n}" ::"r"(dst), "l"(m), "r"(bar), "r"(c0), "r"(c1), "r"(c2), "r"(el), "h"((uint16_t)3), "l"(pol) : "memory");
  } else {
    asm volatile("{\n.reg .pred P;\nsetp.ne.u32 P, %6, 0;\n@P cp.async.bulk.tensor.3d.shared::cluster.global.mbarrier::complete_tx::bytes.multicast::cluster [%0], [%1, {%3, %4, %5}], [%2], %7;\n}" ::"r"(dst), "l"(m), "r"(bar), "r"(c0), "r"(c1), "r"(c2), "r"(el), "h"((uint16_t)3) : "memory");
  }
}
__device__ __forceinline__ void mbar_arrive_cluster(uint32_t addr) { asm volatile("mbarrier.arrive.shared::cluster.b64 _, [%0];" ::"r"(addr) : "memory"); }
__device__ __forceinline__ uint32_t mapa(uint32_t addr, uint32_t rank) { uint32_t r; asm("mapa.shared::cluster.u32 %0, %1, %2;" : "=r"(r) : "r"(addr), "r"(rank)); return r; }
__device__ __forceinline__ void bulk_store_p(uint32_t el, void* dst, uint32_t src, uint32_t bytes) {
  asm volatile("{\n.reg .pred P;\nsetp.ne.u32 P, %3, 0;\n@P cp.async.bulk.global.shared::cta.bulk_group [%0], [%1], %2;\n}" ::"l"(dst), "r"(src), "r"(bytes), "r"(el) : "memory");
}
__device__ __forceinline__ void flag_release_p(uint32_t el, uint32_t* f) {
  asm volatile("{\n.reg .pred P;\nsetp.ne.u32 P, %1, 0;\nfence.proxy.async;\n@P red.relaxed.gpu.global.add.u32 [%0], 1;\n}" ::"l"(f), "r"(el) : "memory");
}
__device__ __forceinline__ void flag_add_p(uint32_t el, uint32_t* f) {
  asm volatile("{\n.reg .pred P;\nsetp.ne.u32 P, %1, 0;\n@P red.relaxed.gpu.global.add.u32 [%0], 1;\n}" ::"l"(f), "r"(el) : "memory");
}
__device__ __forceinline__ void prefetch_l2(const void* src, uint32_t bytes) { asm volatile("cp.async.bulk.prefetch.L2.global [%0], %1;" ::"l"(src), "r"(bytes) : "memory"); }
__device__ __forceinline__ void prefetch_map(const CUtensorMap* m) { asm volatile("prefetch.tensormap [%0];" ::"l"(m) : "memory"); }
__device__ __forceinline__ void wgmma_fence() { asm volatile("wgmma.fence.sync.aligned;" ::: "memory"); }
__device__ __forceinline__ void wgmma_commit() { asm volatile("wgmma.commit_group.sync.aligned;" ::: "memory"); }
template <int N> __device__ __forceinline__ void wgmma_wait() { asm volatile("wgmma.wait_group.sync.aligned %0;" ::"n"(N) : "memory"); }
__device__ __forceinline__ uint32_t dlo(uint32_t addr, uint32_t lbo) { return ((addr & 0x3FFFF) >> 4) + ((lbo >> 4) << 16); }
template <uint32_t SBO, uint32_t SWZ> __device__ __forceinline__ uint64_t dsc(uint32_t lo, uint32_t off) {
  uint64_t d; asm("mov.b64 %0, {%1, %2};" : "=l"(d) : "r"(lo + (off >> 4)), "n"((SBO >> 4) | (SWZ << 30))); return d;
}
template <int R> __device__ __forceinline__ void reg_alloc() { asm volatile("setmaxnreg.inc.sync.aligned.u32 %0;" ::"n"(R)); }
template <int R> __device__ __forceinline__ void reg_dealloc() { asm volatile("setmaxnreg.dec.sync.aligned.u32 %0;" ::"n"(R)); }
__device__ __forceinline__ void bar_sync(int id, int n) { asm volatile("bar.sync %0, %1;" ::"r"(id), "r"(n) : "memory"); }
__device__ __forceinline__ void bar_arrive(int id, int n) { asm volatile("bar.arrive %0, %1;" ::"r"(id), "r"(n) : "memory"); }
__device__ __forceinline__ void ldsm4(uint32_t* r, uint32_t addr) {
  asm volatile("ldmatrix.sync.aligned.m8n8.x4.shared.b16 {%0,%1,%2,%3}, [%4];" : "=r"(r[0]), "=r"(r[1]), "=r"(r[2]), "=r"(r[3]) : "r"(addr) : "memory");
}
__device__ __forceinline__ uint32_t movm(uint32_t a) { uint32_t d; asm volatile("movmatrix.sync.aligned.m8n8.trans.b16 %0, %1;" : "=r"(d) : "r"(a)); return d; }
__device__ __forceinline__ void mma16(float* c, uint32_t a0, uint32_t a1, uint32_t a2, uint32_t a3, uint32_t b0, uint32_t b1) {
  asm volatile("mma.sync.aligned.m16n8k16.row.col.f32.bf16.bf16.f32 {%0,%1,%2,%3}, {%4,%5,%6,%7}, {%8,%9}, {%0,%1,%2,%3};"
               : "+f"(c[0]), "+f"(c[1]), "+f"(c[2]), "+f"(c[3]) : "r"(a0), "r"(a1), "r"(a2), "r"(a3), "r"(b0), "r"(b1));
}
__device__ __forceinline__ void mma8(float* c, uint32_t a0, uint32_t a1, uint32_t b0) {
  asm volatile("mma.sync.aligned.m16n8k8.row.col.f32.bf16.bf16.f32 {%0,%1,%2,%3}, {%4,%5}, {%6}, {%0,%1,%2,%3};"
               : "+f"(c[0]), "+f"(c[1]), "+f"(c[2]), "+f"(c[3]) : "r"(a0), "r"(a1), "r"(b0));
}
__device__ __forceinline__ uint32_t pack2(float lo, float hi) { uint32_t r; asm("cvt.rn.bf16x2.f32 %0, %1, %2;" : "=r"(r) : "f"(hi), "f"(lo)); return r; }
__device__ __forceinline__ float blo(uint32_t v) { return __uint_as_float(v << 16); }
__device__ __forceinline__ float bhi(uint32_t v) { return __uint_as_float(v & 0xffff0000u); }
__device__ __forceinline__ float tanh_fast(float x) { float y; asm("tanh.approx.f32 %0, %1;" : "=f"(y) : "f"(x)); return y; }
__device__ __forceinline__ float rcp_fast(float x) { float y; asm("rcp.approx.ftz.f32 %0, %1;" : "=f"(y) : "f"(x)); return y; }
__device__ __forceinline__ float ex2(float x) { float y; asm("ex2.approx.ftz.f32 %0, %1;" : "=f"(y) : "f"(x)); return y; }
__device__ __forceinline__ float qsum(float v) { v += __shfl_xor_sync(~0u, v, 1); v += __shfl_xor_sync(~0u, v, 2); return v; }
__device__ __forceinline__ float qmax(float v) { v = fmaxf(v, __shfl_xor_sync(~0u, v, 1)); v = fmaxf(v, __shfl_xor_sync(~0u, v, 2)); return v; }
__device__ __forceinline__ void stg32(void* p, uint32_t v) { asm volatile("st.global.u32 [%0], %1;" ::"l"(p), "r"(v) : "memory"); }
__device__ __forceinline__ void stg128(void* p, uint32_t a, uint32_t b, uint32_t c, uint32_t d) { asm volatile("st.global.v4.u32 [%0], {%1,%2,%3,%4};" ::"l"(p), "r"(a), "r"(b), "r"(c), "r"(d) : "memory"); }
__device__ __forceinline__ uint32_t ldcg32(const void* p) { uint32_t v; asm volatile("ld.global.L1::no_allocate.u32 %0, [%1];" : "=r"(v) : "l"(p) : "memory"); return v; }
__device__ __forceinline__ void stg128_if(bool c, void* p, uint32_t a, uint32_t b, uint32_t cc, uint32_t d) {
  asm volatile("{\n.reg .pred P;\nsetp.ne.u32 P, %5, 0;\n@P st.global.v4.u32 [%0], {%1,%2,%3,%4};\n}" ::"l"(p), "r"(a), "r"(b), "r"(cc), "r"(d), "r"((uint32_t)c) : "memory");
}
__device__ __forceinline__ uint2 lds64(uint32_t a) { uint2 v; asm volatile("ld.shared.v2.u32 {%0,%1}, [%2];" : "=r"(v.x), "=r"(v.y) : "r"(a) : "memory"); return v; }
__device__ __forceinline__ uint4 ldcg128(const void* p) { uint4 v; asm volatile("ld.global.cg.v4.u32 {%0,%1,%2,%3}, [%4];" : "=r"(v.x), "=r"(v.y), "=r"(v.z), "=r"(v.w) : "l"(p) : "memory"); return v; }
__device__ __forceinline__ uint32_t ldnc16(const void* p) { uint16_t v; asm volatile("ld.global.nc.u16 %0, [%1];" : "=h"(v) : "l"(p)); return v; }
__device__ __forceinline__ uint4 ldnc128(const void* p) { uint4 v; asm volatile("ld.global.nc.v4.u32 {%0,%1,%2,%3}, [%4];" : "=r"(v.x), "=r"(v.y), "=r"(v.z), "=r"(v.w) : "l"(p)); return v; }
__device__ __forceinline__ void cp_async16(uint32_t dst, const void* src) { asm volatile("cp.async.cg.shared.global [%0], [%1], 16;" ::"r"(dst), "l"(src) : "memory"); }
__device__ __forceinline__ uint32_t hsub2(uint32_t a, uint32_t b) { uint32_t d; asm("sub.rn.bf16x2 %0, %1, %2;" : "=r"(d) : "r"(a), "r"(b)); return d; }
__device__ __forceinline__ void stg32_if(bool c, void* p, uint32_t v) {
  asm volatile("{\n.reg .pred P;\nsetp.ne.u32 P, %2, 0;\n@P st.global.u32 [%0], %1;\n}" ::"l"(p), "r"(v), "r"((uint32_t)c) : "memory");
}
__device__ __forceinline__ float wsum(float v) { for (int o = 16; o; o >>= 1) v += __shfl_xor_sync(~0u, v, o); return v; }
__device__ __forceinline__ uint32_t hmul2(uint32_t a, uint32_t b) { uint32_t d; asm("mul.rn.bf16x2 %0, %1, %2;" : "=r"(d) : "r"(a), "r"(b)); return d; }
__device__ __forceinline__ void sts32(uint32_t a, uint32_t v) { asm volatile("st.shared.u32 [%0], %1;" ::"r"(a), "r"(v) : "memory"); }
__device__ __forceinline__ uint32_t lds32(uint32_t a) { uint32_t v; asm volatile("ld.shared.u32 %0, [%1];" : "=r"(v) : "r"(a) : "memory"); return v; }
__device__ __forceinline__ void sts128(uint32_t a, uint32_t x, uint32_t y, uint32_t z, uint32_t w) { asm volatile("st.shared.v4.u32 [%0], {%1,%2,%3,%4};" ::"r"(a), "r"(x), "r"(y), "r"(z), "r"(w) : "memory"); }
__device__ __forceinline__ uint4 lds128(uint32_t a) { uint4 v; asm volatile("ld.shared.v4.u32 {%0,%1,%2,%3}, [%4];" : "=r"(v.x), "=r"(v.y), "=r"(v.z), "=r"(v.w) : "r"(a) : "memory"); return v; }
__device__ __forceinline__ void ll_st64(uint2* p, uint32_t v, uint32_t tag) {
  asm volatile("{\n.reg .b64 r;\nmov.b64 r, {%1,%2};\nst.relaxed.gpu.global.b64 [%0], r;\n}" ::"l"(p), "r"(v), "r"(tag) : "memory");
}
__device__ __forceinline__ uint2 ll_ld64(const uint2* p) {
  uint2 v; asm volatile("{\n.reg .b64 r;\nld.relaxed.gpu.global.b64 r, [%2];\nmov.b64 {%0,%1}, r;\n}" : "=r"(v.x), "=r"(v.y) : "l"(p) : "memory"); return v;
}
__device__ __forceinline__ void ll_st128(uint4* p, float a, float b, uint32_t tag, float c = 0.f) {
  asm volatile("{\n.reg .b128 r;\n.reg .b64 lo, hi;\nmov.b64 lo, {%1,%2};\nmov.b64 hi, {%3,%4};\nmov.b128 r, {lo, hi};\nst.relaxed.gpu.global.b128 [%0], r;\n}" ::"l"(p), "r"(__float_as_uint(a)), "r"(__float_as_uint(b)), "r"(tag), "r"(__float_as_uint(c)) : "memory");
}
__device__ __forceinline__ uint4 ll_ld128(const uint4* p) {
  uint4 v; asm volatile("{\n.reg .b128 r;\n.reg .b64 lo, hi;\nld.relaxed.gpu.global.b128 r, [%4];\nmov.b128 {lo, hi}, r;\nmov.b64 {%0,%1}, lo;\nmov.b64 {%2,%3}, hi;\n}" : "=r"(v.x), "=r"(v.y), "=r"(v.z), "=r"(v.w) : "l"(p) : "memory"); return v;
}
__device__ __forceinline__ void publish_p(uint32_t el, uint32_t* f) {
  asm volatile("{\n.reg .pred P;\nsetp.ne.u32 P, %1, 0;\n@P cp.async.bulk.commit_group;\n@P cp.async.bulk.wait_group 0;\n@P red.release.gpu.global.add.u32 [%0], 1;\n}" ::"l"(f), "r"(el) : "memory");
}
__device__ __forceinline__ void tma3d_red_p(uint32_t el, const CUtensorMap* m, int c0, int c1, int c2, uint32_t src) {
  asm volatile("{\n.reg .pred P;\nsetp.ne.u32 P, %5, 0;\n@P cp.reduce.async.bulk.tensor.3d.global.shared::cta.add.tile.bulk_group [%0, {%2, %3, %4}], [%1];\n@P cp.async.bulk.commit_group;\n}" ::"l"(m), "r"(src), "r"(c0), "r"(c1), "r"(c2), "r"(el) : "memory");
}
__device__ __forceinline__ void stsm4(uint32_t addr, uint32_t a, uint32_t b, uint32_t c, uint32_t d) {
  asm volatile("stmatrix.sync.aligned.m8n8.x4.shared.b16 [%0], {%1,%2,%3,%4};" ::"r"(addr), "r"(a), "r"(b), "r"(c), "r"(d) : "memory");
}
__device__ __forceinline__ void sts64(uint32_t a, uint32_t x, uint32_t y) { asm volatile("st.shared.v2.u32 [%0], {%1,%2};" ::"r"(a), "r"(x), "r"(y) : "memory"); }
__device__ __forceinline__ void ll_st128_if(bool on, uint4* p, float a, float b, uint32_t tag) {
  asm volatile("{\n.reg .pred P;\n.reg .b128 r;\n.reg .b64 lo, hi;\nsetp.ne.u32 P, %4, 0;\nmov.b64 lo, {%1,%2};\nmov.b64 hi, {%3,%3};\nmov.b128 r, {lo, hi};\n@P st.relaxed.gpu.global.b128 [%0], r;\n}" ::"l"(p), "r"(__float_as_uint(a)), "r"(__float_as_uint(b)), "r"(tag), "r"((uint32_t)on) : "memory");
}
__device__ __forceinline__ uint4 ldnc128_if(bool c, const void* p) {
  uint4 v = make_uint4(0u, 0u, 0u, 0u);
  asm volatile("{\n.reg .pred P;\nsetp.ne.u32 P, %5, 0;\n@P ld.global.nc.v4.u32 {%0,%1,%2,%3}, [%4];\n}" : "+r"(v.x), "+r"(v.y), "+r"(v.z), "+r"(v.w) : "l"(p), "r"((uint32_t)c));
  return v;
}
__device__ __forceinline__ uint32_t hfma2(uint32_t a, uint32_t b, uint32_t c) { uint32_t d; asm("fma.rn.bf16x2 %0, %1, %2, %3;" : "=r"(d) : "r"(a), "r"(b), "r"(c)); return d; }
__device__ __forceinline__ float2 lds64f(uint32_t a) { float2 v; asm volatile("ld.shared.v2.f32 {%0,%1}, [%2];" : "=f"(v.x), "=f"(v.y) : "r"(a) : "memory"); return v; }
#define TRC(cond, role, idx) do {} while (0)
#define TRV(role, idx, v) do {} while (0)
#define TRVI(c, role, idx, v) do {} while (0)

#define ACLK_INIT do {} while (0)
#define ACLK(i) do {} while (0)
#define ACLK_OUT do {} while (0)
#define QCLK(i) do {} while (0)
#define PH 1
#define RCLK(i) do {} while (0)
#define RCLK_INIT do {} while (0)
#define RCLK_OUT do {} while (0)
#define SCLK(i) do {} while (0)
#define PL 1
#define PCLK(i) do {} while (0)
#define PQ 1
#define CLK_INIT do {} while (0)
#define CLK(i) do {} while (0)
#define CLK_OUT do {} while (0)

__device__ __forceinline__ void wgmma_ss_n216(float* d, uint64_t da, uint64_t db, int scaleD) {
  asm volatile("{\n.reg .pred p;\nsetp.ne.b32 p, %110, 0;\nwgmma.mma_async.sync.aligned.m64n216k16.f32.bf16.bf16 "
    "{%0,%1,%2,%3,%4,%5,%6,%7,%8,%9,%10,%11,%12,%13,%14,%15,%16,%17,%18,%19,%20,%21,%22,%23,%24,%25,%26,%27,%28,%29,%30,%31,%32,%33,%34,%35,%36,%37,%38,%39,%40,%41,%42,%43,%44,%45,%46,%47,%48,%49,%50,%51,%52,%53,%54,%55,%56,%57,%58,%59,%60,%61,%62,%63,%64,%65,%66,%67,%68,%69,%70,%71,%72,%73,%74,%75,%76,%77,%78,%79,%80,%81,%82,%83,%84,%85,%86,%87,%88,%89,%90,%91,%92,%93,%94,%95,%96,%97,%98,%99,%100,%101,%102,%103,%104,%105,%106,%107}, "
    "%108, %109, p, 1, 1, 0, 1;\n}\n"
    : "+f"(d[0]), "+f"(d[1]), "+f"(d[2]), "+f"(d[3]), "+f"(d[4]), "+f"(d[5]), "+f"(d[6]), "+f"(d[7]), "+f"(d[8]), "+f"(d[9]), "+f"(d[10]), "+f"(d[11]), "+f"(d[12]), "+f"(d[13]), "+f"(d[14]), "+f"(d[15]), "+f"(d[16]), "+f"(d[17]), "+f"(d[18]), "+f"(d[19]), "+f"(d[20]), "+f"(d[21]), "+f"(d[22]), "+f"(d[23]), "+f"(d[24]), "+f"(d[25]), "+f"(d[26]), "+f"(d[27]), "+f"(d[28]), "+f"(d[29]), "+f"(d[30]), "+f"(d[31]), "+f"(d[32]), "+f"(d[33]), "+f"(d[34]), "+f"(d[35]), "+f"(d[36]), "+f"(d[37]), "+f"(d[38]), "+f"(d[39]), "+f"(d[40]), "+f"(d[41]), "+f"(d[42]), "+f"(d[43]), "+f"(d[44]), "+f"(d[45]), "+f"(d[46]), "+f"(d[47]), "+f"(d[48]), "+f"(d[49]), "+f"(d[50]), "+f"(d[51]), "+f"(d[52]), "+f"(d[53]), "+f"(d[54]), "+f"(d[55]), "+f"(d[56]), "+f"(d[57]), "+f"(d[58]), "+f"(d[59]), "+f"(d[60]), "+f"(d[61]), "+f"(d[62]), "+f"(d[63]), "+f"(d[64]), "+f"(d[65]), "+f"(d[66]), "+f"(d[67]), "+f"(d[68]), "+f"(d[69]), "+f"(d[70]), "+f"(d[71]), "+f"(d[72]), "+f"(d[73]), "+f"(d[74]), "+f"(d[75]), "+f"(d[76]), "+f"(d[77]), "+f"(d[78]), "+f"(d[79]), "+f"(d[80]), "+f"(d[81]), "+f"(d[82]), "+f"(d[83]), "+f"(d[84]), "+f"(d[85]), "+f"(d[86]), "+f"(d[87]), "+f"(d[88]), "+f"(d[89]), "+f"(d[90]), "+f"(d[91]), "+f"(d[92]), "+f"(d[93]), "+f"(d[94]), "+f"(d[95]), "+f"(d[96]), "+f"(d[97]), "+f"(d[98]), "+f"(d[99]), "+f"(d[100]), "+f"(d[101]), "+f"(d[102]), "+f"(d[103]), "+f"(d[104]), "+f"(d[105]), "+f"(d[106]), "+f"(d[107])
    : "l"(da), "l"(db), "r"(scaleD));
}
__device__ __forceinline__ void wgmma_ss_n72(float* d, uint64_t da, uint64_t db, int scaleD) {
  asm volatile("{\n.reg .pred p;\nsetp.ne.b32 p, %38, 0;\nwgmma.mma_async.sync.aligned.m64n72k16.f32.bf16.bf16 "
    "{%0,%1,%2,%3,%4,%5,%6,%7,%8,%9,%10,%11,%12,%13,%14,%15,%16,%17,%18,%19,%20,%21,%22,%23,%24,%25,%26,%27,%28,%29,%30,%31,%32,%33,%34,%35}, "
    "%36, %37, p, 1, 1, 0, 1;\n}\n"
    : "+f"(d[0]), "+f"(d[1]), "+f"(d[2]), "+f"(d[3]), "+f"(d[4]), "+f"(d[5]), "+f"(d[6]), "+f"(d[7]), "+f"(d[8]), "+f"(d[9]), "+f"(d[10]), "+f"(d[11]), "+f"(d[12]), "+f"(d[13]), "+f"(d[14]), "+f"(d[15]), "+f"(d[16]), "+f"(d[17]), "+f"(d[18]), "+f"(d[19]), "+f"(d[20]), "+f"(d[21]), "+f"(d[22]), "+f"(d[23]), "+f"(d[24]), "+f"(d[25]), "+f"(d[26]), "+f"(d[27]), "+f"(d[28]), "+f"(d[29]), "+f"(d[30]), "+f"(d[31]), "+f"(d[32]), "+f"(d[33]), "+f"(d[34]), "+f"(d[35])
    : "l"(da), "l"(db), "r"(scaleD));
}
__device__ __forceinline__ void wgmma_ss_n128(float* d, uint64_t da, uint64_t db, int scaleD) {
  asm volatile("{\n.reg .pred p;\nsetp.ne.b32 p, %66, 0;\nwgmma.mma_async.sync.aligned.m64n128k16.f32.bf16.bf16 "
    "{%0,%1,%2,%3,%4,%5,%6,%7,%8,%9,%10,%11,%12,%13,%14,%15,%16,%17,%18,%19,%20,%21,%22,%23,%24,%25,%26,%27,%28,%29,%30,%31,%32,%33,%34,%35,%36,%37,%38,%39,%40,%41,%42,%43,%44,%45,%46,%47,%48,%49,%50,%51,%52,%53,%54,%55,%56,%57,%58,%59,%60,%61,%62,%63}, "
    "%64, %65, p, 1, 1, 0, 1;\n}\n"
    : "+f"(d[0]), "+f"(d[1]), "+f"(d[2]), "+f"(d[3]), "+f"(d[4]), "+f"(d[5]), "+f"(d[6]), "+f"(d[7]), "+f"(d[8]), "+f"(d[9]), "+f"(d[10]), "+f"(d[11]), "+f"(d[12]), "+f"(d[13]), "+f"(d[14]), "+f"(d[15]), "+f"(d[16]), "+f"(d[17]), "+f"(d[18]), "+f"(d[19]), "+f"(d[20]), "+f"(d[21]), "+f"(d[22]), "+f"(d[23]), "+f"(d[24]), "+f"(d[25]), "+f"(d[26]), "+f"(d[27]), "+f"(d[28]), "+f"(d[29]), "+f"(d[30]), "+f"(d[31]), "+f"(d[32]), "+f"(d[33]), "+f"(d[34]), "+f"(d[35]), "+f"(d[36]), "+f"(d[37]), "+f"(d[38]), "+f"(d[39]), "+f"(d[40]), "+f"(d[41]), "+f"(d[42]), "+f"(d[43]), "+f"(d[44]), "+f"(d[45]), "+f"(d[46]), "+f"(d[47]), "+f"(d[48]), "+f"(d[49]), "+f"(d[50]), "+f"(d[51]), "+f"(d[52]), "+f"(d[53]), "+f"(d[54]), "+f"(d[55]), "+f"(d[56]), "+f"(d[57]), "+f"(d[58]), "+f"(d[59]), "+f"(d[60]), "+f"(d[61]), "+f"(d[62]), "+f"(d[63])
    : "l"(da), "l"(db), "r"(scaleD));
}
__device__ __forceinline__ void wgmma_ss_n160(float* d, uint64_t da, uint64_t db, int scaleD) {
  asm volatile("{\n.reg .pred p;\nsetp.ne.b32 p, %82, 0;\nwgmma.mma_async.sync.aligned.m64n160k16.f32.bf16.bf16 "
    "{%0,%1,%2,%3,%4,%5,%6,%7,%8,%9,%10,%11,%12,%13,%14,%15,%16,%17,%18,%19,%20,%21,%22,%23,%24,%25,%26,%27,%28,%29,%30,%31,%32,%33,%34,%35,%36,%37,%38,%39,%40,%41,%42,%43,%44,%45,%46,%47,%48,%49,%50,%51,%52,%53,%54,%55,%56,%57,%58,%59,%60,%61,%62,%63,%64,%65,%66,%67,%68,%69,%70,%71,%72,%73,%74,%75,%76,%77,%78,%79}, "
    "%80, %81, p, 1, 1, 0, 1;\n}\n"
    : "+f"(d[0]), "+f"(d[1]), "+f"(d[2]), "+f"(d[3]), "+f"(d[4]), "+f"(d[5]), "+f"(d[6]), "+f"(d[7]), "+f"(d[8]), "+f"(d[9]), "+f"(d[10]), "+f"(d[11]), "+f"(d[12]), "+f"(d[13]), "+f"(d[14]), "+f"(d[15]), "+f"(d[16]), "+f"(d[17]), "+f"(d[18]), "+f"(d[19]), "+f"(d[20]), "+f"(d[21]), "+f"(d[22]), "+f"(d[23]), "+f"(d[24]), "+f"(d[25]), "+f"(d[26]), "+f"(d[27]), "+f"(d[28]), "+f"(d[29]), "+f"(d[30]), "+f"(d[31]), "+f"(d[32]), "+f"(d[33]), "+f"(d[34]), "+f"(d[35]), "+f"(d[36]), "+f"(d[37]), "+f"(d[38]), "+f"(d[39]), "+f"(d[40]), "+f"(d[41]), "+f"(d[42]), "+f"(d[43]), "+f"(d[44]), "+f"(d[45]), "+f"(d[46]), "+f"(d[47]), "+f"(d[48]), "+f"(d[49]), "+f"(d[50]), "+f"(d[51]), "+f"(d[52]), "+f"(d[53]), "+f"(d[54]), "+f"(d[55]), "+f"(d[56]), "+f"(d[57]), "+f"(d[58]), "+f"(d[59]), "+f"(d[60]), "+f"(d[61]), "+f"(d[62]), "+f"(d[63]), "+f"(d[64]), "+f"(d[65]), "+f"(d[66]), "+f"(d[67]), "+f"(d[68]), "+f"(d[69]), "+f"(d[70]), "+f"(d[71]), "+f"(d[72]), "+f"(d[73]), "+f"(d[74]), "+f"(d[75]), "+f"(d[76]), "+f"(d[77]), "+f"(d[78]), "+f"(d[79])
    : "l"(da), "l"(db), "r"(scaleD));
}
__device__ __forceinline__ void wgmma_rs_n144(float* d, const uint32_t* a, uint64_t db, int scaleD) {
  asm volatile("{\n.reg .pred p;\nsetp.ne.b32 p, %77, 0;\nwgmma.mma_async.sync.aligned.m64n144k16.f32.bf16.bf16 "
    "{%0,%1,%2,%3,%4,%5,%6,%7,%8,%9,%10,%11,%12,%13,%14,%15,%16,%17,%18,%19,%20,%21,%22,%23,%24,%25,%26,%27,%28,%29,%30,%31,%32,%33,%34,%35,%36,%37,%38,%39,%40,%41,%42,%43,%44,%45,%46,%47,%48,%49,%50,%51,%52,%53,%54,%55,%56,%57,%58,%59,%60,%61,%62,%63,%64,%65,%66,%67,%68,%69,%70,%71}, "
    "{%72,%73,%74,%75}, %76, p, 1, 1, 1;\n}\n"
    : "+f"(d[0]), "+f"(d[1]), "+f"(d[2]), "+f"(d[3]), "+f"(d[4]), "+f"(d[5]), "+f"(d[6]), "+f"(d[7]), "+f"(d[8]), "+f"(d[9]), "+f"(d[10]), "+f"(d[11]), "+f"(d[12]), "+f"(d[13]), "+f"(d[14]), "+f"(d[15]), "+f"(d[16]), "+f"(d[17]), "+f"(d[18]), "+f"(d[19]), "+f"(d[20]), "+f"(d[21]), "+f"(d[22]), "+f"(d[23]), "+f"(d[24]), "+f"(d[25]), "+f"(d[26]), "+f"(d[27]), "+f"(d[28]), "+f"(d[29]), "+f"(d[30]), "+f"(d[31]), "+f"(d[32]), "+f"(d[33]), "+f"(d[34]), "+f"(d[35]), "+f"(d[36]), "+f"(d[37]), "+f"(d[38]), "+f"(d[39]), "+f"(d[40]), "+f"(d[41]), "+f"(d[42]), "+f"(d[43]), "+f"(d[44]), "+f"(d[45]), "+f"(d[46]), "+f"(d[47]), "+f"(d[48]), "+f"(d[49]), "+f"(d[50]), "+f"(d[51]), "+f"(d[52]), "+f"(d[53]), "+f"(d[54]), "+f"(d[55]), "+f"(d[56]), "+f"(d[57]), "+f"(d[58]), "+f"(d[59]), "+f"(d[60]), "+f"(d[61]), "+f"(d[62]), "+f"(d[63]), "+f"(d[64]), "+f"(d[65]), "+f"(d[66]), "+f"(d[67]), "+f"(d[68]), "+f"(d[69]), "+f"(d[70]), "+f"(d[71])
    : "r"(a[0]), "r"(a[1]), "r"(a[2]), "r"(a[3]), "l"(db), "r"(scaleD));
}
__device__ __forceinline__ void wgmma_rs_n64(float* d, const uint32_t* a, uint64_t db, int scaleD) {
  asm volatile("{\n.reg .pred p;\nsetp.ne.b32 p, %37, 0;\nwgmma.mma_async.sync.aligned.m64n64k16.f32.bf16.bf16 "
    "{%0,%1,%2,%3,%4,%5,%6,%7,%8,%9,%10,%11,%12,%13,%14,%15,%16,%17,%18,%19,%20,%21,%22,%23,%24,%25,%26,%27,%28,%29,%30,%31}, "
    "{%32,%33,%34,%35}, %36, p, 1, 1, 1;\n}\n"
    : "+f"(d[0]), "+f"(d[1]), "+f"(d[2]), "+f"(d[3]), "+f"(d[4]), "+f"(d[5]), "+f"(d[6]), "+f"(d[7]), "+f"(d[8]), "+f"(d[9]), "+f"(d[10]), "+f"(d[11]), "+f"(d[12]), "+f"(d[13]), "+f"(d[14]), "+f"(d[15]), "+f"(d[16]), "+f"(d[17]), "+f"(d[18]), "+f"(d[19]), "+f"(d[20]), "+f"(d[21]), "+f"(d[22]), "+f"(d[23]), "+f"(d[24]), "+f"(d[25]), "+f"(d[26]), "+f"(d[27]), "+f"(d[28]), "+f"(d[29]), "+f"(d[30]), "+f"(d[31])
    : "r"(a[0]), "r"(a[1]), "r"(a[2]), "r"(a[3]), "l"(db), "r"(scaleD));
}

template <int V> struct Int { static constexpr int value = V; };
struct Cur {
  uint32_t s, ph;
  __device__ __forceinline__ void next() { if (++s == NST) { s = 0; ph ^= 1; } }
};

__device__ __forceinline__ uint32_t o_place(uint32_t w, uint32_t e) { return (((w ? 0xd5310u : 0xa8d57u) >> (4 * e)) & 15) * 8192 + 90112; }
__device__ __forceinline__ uint8_t* z1_block(int rb, int w, int j) { return g_Z + (rb * 16 + w * 8 + j) * ZB; }
__device__ __forceinline__ uint8_t* xn_block(int hw) { return g_Z + (512 + hw * 2) * ZB; }
__device__ __forceinline__ uint8_t* z2_block(int kb, int j) { return g_Z + (256 + kb * 8 + j) * ZB; }
template <int N> __device__ __forceinline__ uint32_t spin(uint32_t z) {
#pragma unroll (N > 8 ? 1 : 8)
  for (int i = 0; i < N; i++) asm volatile("shfl.sync.bfly.b32 %0, %0, 1, 0x1f, 0xffffffff;" : "+r"(z)::"memory");
  return z;
}

__device__ __forceinline__ void rows_fetch(uint32_t el, uint32_t xr, const uint8_t* src, uint32_t bar) {
  expect_tx_p(el, bar, 9216);
#pragma unroll 1
  for (int r = 0; r < 8; r++) bulk_load_p(el, xr + r * 1152, src + r * (DM * 4), 1152, bar);
}
__device__ __forceinline__ void rows_stats(uint32_t xr, uint4* dst, uint32_t tag, int lane) {
  float s[2] = {0.f, 0.f}, q[4] = {0.f, 0.f, 0.f, 0.f};
  const uint32_t a0 = xr + (lane >> 2) * 1152 + (((lane & 3) * 2) ^ (lane >> 2)) * 16;
  uint4 n0 = lds128(a0), n1 = lds128(a0 ^ 16);
#pragma unroll 1
  for (int e = 1; e <= 9; e++) {
    const uint32_t x[8] = {n0.x, n0.y, n0.z, n0.w, n1.x, n1.y, n1.z, n1.w};
    if (e < 9) { n0 = lds128(a0 + e * 128); n1 = lds128((a0 ^ 16) + e * 128); }
#pragma unroll
    for (int u = 0; u < 8; u++) {
      const float lo = blo(x[u]), hi = bhi(x[u]);
      s[u & 1] += lo + hi; q[(u & 1) * 2] = fmaf(lo, lo, q[(u & 1) * 2]); q[(u & 1) * 2 + 1] = fmaf(hi, hi, q[(u & 1) * 2 + 1]);
    }
  }
  const float sx = s[0] + s[1], sq = (q[0] + q[1]) + (q[2] + q[3]);
  const float m = qsum(sx) * (-1.f / DM), r = rsqrtf(fmaxf(fmaf(qsum(sq), 1.f / DM, -m * m), 0.f) + LN_EPS);
  if ((lane & 3) == 0) ll_st128(dst + (lane >> 2) * 2, m, r, tag);
}

__global__ void __cluster_dims__(2, 1, 1) __launch_bounds__(384, 1) mega_kernel(const __grid_constant__ Params P) {
  extern __shared__ __align__(1024) uint8_t smem_raw[];
  const uint32_t sb = smem_u32(smem_raw);
  const uint32_t bars = sb + SM_BAR;
  const int tid = threadIdx.x;
  int lane = tid & 31;
  const int wid = __shfl_sync(~0u, tid >> 5, 0);
  const int bid = P.role[blockIdx.x >> 1] * 2 + (blockIdx.x & 1);
  if (bid >= NCTA) return;
  const int rb = bid & 15, j = bid >> 4;
  uint4 wv[5];
  {
    const int n8 = min(tid >> 3, 26), part = n8 / 9;
    const uint8_t* src = (const uint8_t*)P.wqkv + (8 * rb + (tid & 7)) * (3 * DM * 2) + (part * (DM - 72) + 72 * j + 8 * n8) * 2;
#pragma unroll
    for (int u = 0; u < 5; u++) wv[u] = ldnc128_if(tid < 216, src + (u < 4 || rb < 8 ? u : 0) * (128 * 3 * DM * 2));
  }
  if (wid >= 7 && lane == 0) {
    if (wid < 10) {
#pragma unroll
      for (uint32_t b = 0; b < B_AD / 3; b += 8) mbar_init(bars + (wid - 7) * (B_AD / 3) + b, 1);
    } else if (wid == 10) {
#pragma unroll
      for (uint32_t b = B_AD; b < B_EVT; b += 8) mbar_init(bars + b, b < B_CSQ ? 2 : b < B_LAG ? 3 : 4);
    } else {
#pragma unroll
      for (uint32_t b = B_EVT; b < 1024; b += 8) if (b < B_OFF || b >= B_IMG) mbar_init(bars + b, b < B_IMG ? 4 : b < B_EMPTY ? 8 : 16);
    }
    asm volatile("fence.mbarrier_init.release.cluster;" ::: "memory");
  }
  __syncthreads();

  if (wid >= 8) {
    reg_dealloc<40>();
    const uint32_t el = elect_one();
    const uint64_t pol = policy_evict_first();
    uint32_t* const fj = g_flags + FJ + j * 32;
    if (wid == 8) {
      if (el) { prefetch_map(&P.wsp); prefetch_map(&P.winb[j & 1]); prefetch_map(&P.wins); prefetch_map(&P.wout); prefetch_map(&P.act[1]); prefetch_map(&P.res[0]); prefetch_map(&P.res[1]); prefetch_map(&P.red); }
      const uint32_t epoch = ldcg32(fj + FJ_EP + rb);
      Cur c{0, 1};
      const uint32_t rk = bid & 1;
      uint32_t st, full;
      auto slot = [&](uint32_t bytes) {
        st = sb + c.s * ST_BYTES; full = bars + B_FULL + c.s * 8;
        mbar_wait(full, c.ph);
        expect_tx_p(el, full, bytes);
        mbar_wait(full - B_FULL + B_EMPTY, c.ph);
      };
#pragma unroll 1
      for (int L = 0; L < 2; L++) {
#pragma unroll 1
        for (int i = 0; i < 9; i++) {
          if (L == 0 && i == 0) {
            flag_wait(fj + FJ_WQ, (epoch + 1) * 16);
            fence_async_g();
            TRC(el, 2, 45);
          }
          slot(27648);
          bulk_mc_h(el, st + ST_B + rk * 13824, g_WQ + j * WQ_SL + i * 27648 + rk * 13824, 13824, full, EF(0), pol);
          c.next();
        }
        if (L == 0) {
          flag_wait(fj + FJ_WO, (epoch + 1) * 16);
          fence_async_g();
          TRC(el, 2, 46);
        }
#pragma unroll 1
        while (c.s) {
          mbar_wait(bars + B_EMPTY + c.s * 8, c.ph);
          if (el) { mbar_arrive(bars + B_FULL + c.s * 8); asm volatile("mbarrier.arrive.shared::cta.b64 _, [%0], 16;" ::"r"(bars + B_EMPTY + c.s * 8) : "memory"); }
          c.next();
        }
        expect_tx_p(el, bars + B_WF, WO_SL);
        mbar_wait(bars + B_EMPTY, c.ph);
        mbar_wait(bars + B_EMPTY + 8, c.ph);
        bulk_mc_h(el, sb + rk * (WO_SL / 2), g_WO + j * WO_SL + rk * (WO_SL / 2), WO_SL / 2, bars + B_WF, EF(1), pol);
#pragma unroll 1
        for (int r = 0; r < 10; r++) {
          const bool big = r >= 2 && r < 8;
          const int a0 = (r < 5 ? 36 : 0) + ((9 * j) >> 1) + (big ? 2 - 2 * (j & 1) : 3 * (j & 1) + rk), ks = big ? 32 : 48;
          int k = big ? (r < 5 ? r - 2 : r - 5) * 192 + rk * 16 : (r & 1) * 288;
          const CUtensorMap* m = big ? &P.winb[j & 1] : &P.wins;
          const uint32_t dst = sb + SM_B3 + rk * 6144;
#pragma unroll
          for (int p = 0; p < 6; p++, k += ks) {
            if ((p == 0 || p > 3) && r == 0) mbar_wait(bars + (p < 5 ? B_XD + p * 2 : B_S5), L);
            if (p) mbar_wait_c(bars + B_E3 + p * 8, ~r & 1); else mbar_wait(bars + B_E3, ~r & 1);
            expect_tx_p(el, bars + B_F3 + p * 8, 12288);
            tma3d_mc_h(el, dst + p * 12288, m, 0, k, a0, bars + B_F3 + p * 8, EF(2), pol);
          }
        }
        TRC(el, 2, L * 16 + 6);
        mbar_wait(bars + B_ZOK, L);
        fence_async_g();
        TRC(el, 2, L * 16 + 7);
        const uint8_t* src = z2_block(0, j) + rk * 18432;
#pragma unroll 1
        for (int r = 0; r < 8; r++) {
          const int k = (r & 3) * 512 + (r >> 2) * 64;
#pragma unroll
          for (int p = 0; p < 4; p++, src += 8 * ZB) {
            if ((p == 1 || p == 2) && r == 0) mbar_wait(bars + B_E3 - 8 + p * 24, 1);
            mbar_wait_c(bars + B_AD + p * 8, ~r & 1);
            if (p) mbar_wait_c(bars + B_EMPTY + p * 8, c.ph); else mbar_wait(bars + B_EMPTY, c.ph);
            expect_tx_p(el, bars + B_FULL + p * 8, ST_BYTES);
            bulk_mc_h(el, sb + p * ST_BYTES + ST_B + rk * 18432, src, 18432, bars + B_FULL + p * 8, EF(4), pol);
            tma3d_h(el, sb + p * ST_BYTES, &P.wsp, k + p * 128, rb * 64, 0, bars + B_FULL + p * 8, EF(3), pol);
          }
          c.ph ^= 1;
        }
        mbar_wait(bars + B_Z1, L);
        fence_async_g();
#pragma unroll 1
        for (int i = 0; i < 11; i++) {
          const int cb = i - 2 + j;
          if (i < 4) mbar_wait(bars + B_AD + c.s * 8, 1);
          slot(ZB);
          if (i < 2) bulk_load_h(el, st + ST_B, z1_block(rb, i, j), ZB, full, true, pol);
          else tma2d_mc_h(el, st + ST_B + rk * 18432, &P.wout, (cb >= 9 ? cb - 9 : cb) * 64, 288 * j + rk * 144, full, EF(5), pol);
          c.next();
        }
      }
    } else if (wid < 11) {
      uint32_t id = bid * 2 + wid - 9;
#define AGENT_IDS asm volatile("" : "+r"(lane), "+r"(id)); const uint32_t w = id & 1, hw = id & 31, rb = hw >> 1, j = id >> 5, ev = bars + B_EVT + w * EV_N * 8; \
      uint32_t* const fr = g_flags + hw * 32; uint32_t* const fj = g_flags + FJ + j * 32; (void)fr; (void)fj; (void)ev; (void)rb
      uint32_t t8 = (ldcg32(g_flags + (id & 31) * 32 + FR_EP + j) + 1) * 8;
      Cur c{0, 1};
#pragma unroll 1
      for (int L = 0; L < 2; L++) {
#pragma unroll 1
        for (int ph = 0; ph < 3; ph++) {
          if (ph + L > 0) {
            AGENT_IDS;
            uint32_t* f = fr + (ph == 0 ? FR_X2 : ph == 1 ? FR_O + L - (int)w * 32 : FR_X1 + L);
            mbar_wait(ev + ph * 8, ph ? L : 0);
            TRC(el, 3, w * 32 + L * 16 + ph * 3);
            if (ph == 2 || ((XRLX >> ph) & 1)) flag_add_p(el, f); else flag_release_p(el, f);
            TRC(el, 3, w * 32 + L * 16 + ph * 3 + 1);
            if (ph == 1) {
              expect_tx_p(el, bars + B_RES + w * 8, 9216);
              tma3d_h(el, sb + SM_STG + w * 9216, &P.res[L], j * 72, hw * 32, 0, bars + B_RES + w * 8, !L, pol);
#pragma unroll 1
              for (int e = 0; e < 5; e++) {
                const uint32_t nb = e ? 16384 : 8192, full = bars + B_OF + w * 40 + e * 8, dst = sb + o_place(w, e);
                const uint8_t* src = z1_block(rb, w, 0) + (e ? e * 16384 - 8192 : 0);
                expect_tx_p(el, full, nb);
                if (e == 0) {
                  flag_wait(f, t8 * 2);
                  fence_async_g();
                }
                if (w && (e == 0 || e == 3)) mbar_wait(bars + (e ? B_X3 : B_OF + YPACE * 8), L);
                bulk_load_h(el, dst, src, nb, full, EF(6), pol);
                TRC(el && e == 0, 3, w * 32 + L * 16 + ph * 3 + 2);
              }
              continue;
            }
            if (ph == 2) {
              const uint8_t* src = xn_block(hw);
              uint32_t full = bars + B_AF3 + w * 96, dst = sb + w * 6144;
              mbar_wait(bars + B_XD + 8, L);
#pragma unroll 1
              for (int k = 0; k < 12; k++, src += 6144, dst += 12288, full += 8) {
                expect_tx_p(el, full, 6144);
                if (k >= APACE) mbar_wait(full - APACE * 8, L);
                if (k == 0) flag_wait(f, t8);
                if (k == 11 && L == 1) flag_wait(fj + FJ_P4, t8 * 4);
                bulk_load_h(el, dst, src, 6144, full, EF(7), pol);
                TRC(el && k == 0, 3, w * 32 + L * 16 + ph * 3 + 2);
              }
              break;
            }
            const uint32_t full = bars + B_FULLA + w * 32 + c.s * 8, dst = sb + c.s * ST_BYTES + w * 8192;
            mbar_wait(bars + B_EMPTY + c.s * 8, c.ph);
            expect_tx_p(el, full, 8192);
            flag_wait(f, t8);
            fence_async_g();
            tma3d_h(el, dst, &P.act[1], 0, rb * 64, w, full, false, pol);
            c.next();
            TRC(el, 3, w * 32 + L * 16 + ph * 3 + 2);
          }
#pragma unroll 1
          for (int i = L; i < 9; i++) {
            AGENT_IDS;
            const uint32_t full = bars + B_FULLA + w * 32 + c.s * 8, dst = sb + c.s * ST_BYTES + w * 8192;
            if (L == 0 && i == 4) {
              mbar_wait(bars + B_WT + w * 8, 0);
              rows_stats(sb + SM_STG + w * 9216, g_XST + hw * 128 + 16 * j, (t8 >> 2) - 1, lane);
            }
            mbar_wait(bars + B_EMPTY + c.s * 8, c.ph);
            expect_tx_p(el, full, 8192);
            tma3d_h(el, dst, &P.act[L], i * 64, rb * 64, w, full, false, pol);
            c.next();
            if (i == 5) {
              uint8_t* d = xn_block(hw) + j * 9216 + lane * 16;
#pragma unroll 2
              for (int u = 0; u < 18; u++) stg128(d + u * 512, ~0u, ~0u, ~0u, ~0u);
            }
            if (L == 0 && i == 3) rows_fetch(el, sb + SM_STG + w * 9216, P.xs[0] + (128 * rb + 16 * j + w) * (DM * 2), bars + B_WT + w * 8);
          }
          if (c.s) { c.s = 0; c.ph ^= 1; }
          {
            AGENT_IDS;
            const uint32_t tag = (t8 >> 2) - 1 + L;
            uint4* const xs = g_XST + hw * 128;
            const uint32_t tab = sb + L * (3 * ST_BYTES) + SM_XST + w * 512 + lane * 8;
            TRC(el, 3, w * 32 + L * 16 + 13);
#pragma unroll 1
            for (int it = 0; it < (1 << 22); it++) {
              const uint4 a = ll_ld128(xs + 2 * lane), b = ll_ld128(xs + 64 + 2 * lane);
              if (__all_sync(~0u, a.z == tag && b.z == tag)) { sts64(tab, a.x, a.y); sts64(tab + 256, b.x, b.y); break; }
            }
            __syncwarp();
            if (el) mbar_arrive(bars + B_CSQ);
            TRC(el, 3, w * 32 + L * 16 + 14);
          }
        }
        if (wid == 10) {
          AGENT_IDS;
          mbar_wait(ev - (EV_N - EV_ZN) * 8, L);
          mbar_wait(ev + EV_ZN * 8, L);
          asm volatile("fence.release.gpu;" ::: "memory");
          flag_add_p(el, fj + FJ_ZN + L);
          flag_add_p(el, fr - 32 + FR_XR + L);
          flag_wait(fj + FJ_ZN + L, t8 * 2);
          flag_wait(fr - 32 + FR_XR + L, t8);
          if (el) mbar_arrive(bars + B_ZOK);
        } else if (WPF) {
          AGENT_IDS;
          mbar_wait(ev + EV_ZN * 8, L);
          if (el) asm volatile("cp.async.bulk.prefetch.tensor.3d.L2.global [%0, {%1, %2, %3}];" ::"l"(&P.wsp), "r"(j * 128), "r"(rb * 64), "r"(0) : "memory");
        }
        float cv;
        {
        AGENT_IDS;
        cv = (lane & 3) ? 0.f : -blo(ldnc16(P.b_sp + 128 * rb + 16 * j + 2 * (lane >> 2) + w));
        mbar_wait(ev + EV_Z1 * 8, L);
        const uint32_t ro = (w * 64 + 8 * j + (lane >> 2)) * 128, x0 = ((lane & 3) * 2) ^ (lane >> 2);
#pragma unroll 1
        for (int i = 0; i < 32; i++) {
          const bool tail = (i >> 1) == 12;
          const int kb = tail ? i + 6 : i < 24 ? i : i - 2;
          if (!(i & 7)) mbar_wait(bars + B_RT + i, L);
          if (i == 24) mbar_wait(bars + B_WT + w * 8, L ^ 1);
          if (!tail) mbar_wait(bars + B_FULL + c.s * 8, c.ph ^ 1);
          if (i == 3) {
            uint32_t id2 = id;
            asm volatile("" : "+r"(id2));
            expect_tx_p(el, bars + B_WT + w * 8, 3072);
#pragma unroll 1
            for (int r = 0; r < 8; r++)
              bulk_load_p(el, sb + SM_WT + w * 3200 + r * 400, (const uint8_t*)P.w_sp + (64 * (id2 & 30) + 16 * (id2 >> 5) + 2 * r + w) * (SEQ * 2) + 29 * 128, 384, bars + B_WT + w * 8);
          }
#pragma unroll
          for (int e = 0; e < 2; e++) {
            const uint4 a = lds128(!tail ? sb + c.s * ST_BYTES + ro + ((x0 ^ e) << 4) : sb + SM_WT + w * 3200 + (lane >> 2) * 400 + (i - 24) * 256 + (lane & 3) * 32 + e * 16);
            const uint4 m = lds128(sb + SM_RT + 4096 + kb * 128 + (lane & 3) * 32 + e * 16);
            cv = fmaf(blo(a.x), blo(m.x), fmaf(bhi(a.x), bhi(m.x), fmaf(blo(a.y), blo(m.y), fmaf(bhi(a.y), bhi(m.y), cv))));
            cv = fmaf(blo(a.z), blo(m.z), fmaf(bhi(a.z), bhi(m.z), fmaf(blo(a.w), blo(m.w), fmaf(bhi(a.w), bhi(m.w), cv))));
          }
          if (!tail) {
            __syncwarp();
            if (el) mbar_arrive(bars + B_AD + c.s * 8);
            c.next();
          }
        }
        }
        AGENT_IDS;
        TRC(el, 3, w * 32 + L * 16 + 11);
        asm volatile("" : "+r"(t8));
        const uint32_t tag = (t8 >> 2) - 1 + L;
        cv = qsum(cv);
        uint2* const cs = (uint2*)(g_XST + hw * 128 + 1);
        if ((lane & 3) == 0) ll_st64(cs + 32 * j + (lane >> 2) * 4, __float_as_uint(cv), tag);
#pragma unroll 1
        for (int it = 0; it < (1 << 22); it++) {
          const uint2 a = ll_ld64(cs + 4 * lane), b = ll_ld64(cs + 128 + 4 * lane);
          if (__all_sync(~0u, a.y == tag && b.y == tag)) { sts32(sb + SM_CV + w * 256 + lane * 4, a.x); sts32(sb + SM_CV + w * 256 + 128 + lane * 4, b.x); break; }
        }
        __syncwarp();
        if (el) mbar_arrive(bars + B_CV + w * 8);
        TRC(el, 3, w * 32 + L * 16 + 12);
#pragma unroll 1
        for (int kb = 30; kb < 32; kb++) {
          mbar_wait(bars + B_FULL + c.s * 8, c.ph ^ 1);
          if (el) mbar_arrive(bars + B_AD + c.s * 8);
          c.next();
        }
        c.ph ^= ((c.s + 11) >> 2) & 1; c.s = (c.s + 11) & 3;
        if (L == 0) {
          mbar_wait(ev + EV_P4 * 8, 0);
          flag_add_p(el, fj + FJ_P4);
        }
      }
    } else {
      const uint32_t epoch = ldcg32(fj + FJ_EP + rb);
      mbar_wait(bars + B_IMG, 0);
      TRC(el, 2, 41);
      flag_release_p(el, fj + FJ_WQ);
      TRC(el, 2, 42);
#pragma unroll 1
      for (int L = 0; L < 2; L++) {
        float* const csf = g_CSP + (NCTA + bid) * 216;
        if (L == 0) {
          flag_wait(fj + FJ_WQ, (epoch + 1) * 16);
          fence_async_g();
          expect_tx_p(el, bars + B_XRW, 13824);
          bulk_load_p(el, sb + ST_BYTES + SM_WOI, g_CSP + j * 16 * 216, 6912, bars + B_XRW);
          bulk_load_p(el, sb + 2 * ST_BYTES + SM_WOI, g_CSP + (j * 16 + 8) * 216, 6912, bars + B_XRW);
          mbar_wait(bars + B_XRW, 0);
#pragma unroll 1
          for (int f = lane; f < 54; f += 32) {
            float s[4] = {0.f, 0.f, 0.f, 0.f};
#pragma unroll 4
            for (int r = 0; r < 16; r++) {
              const uint4 v = lds128(sb + ST_BYTES + SM_WOI + (r >> 3) * ST_BYTES + (r & 7) * 864 + f * 16);
              s[0] += __uint_as_float(v.x); s[1] += __uint_as_float(v.y); s[2] += __uint_as_float(v.z); s[3] += __uint_as_float(v.w);
            }
            sts128(sb + SM_CSQ + f * 16, __float_as_uint(s[0]), __float_as_uint(s[1]), __float_as_uint(s[2]), __float_as_uint(s[3]));
            stg128(csf + f * 4, __float_as_uint(s[0]), __float_as_uint(s[1]), __float_as_uint(s[2]), __float_as_uint(s[3]));
          }
          __syncwarp();
          if (el) mbar_arrive(bars + B_CSQ);
        } else {
#pragma unroll 1
          for (int u = 0; u < 4; u++) {
            const int w = u & 1;
            if (u < 2) {
              flag_wait(g_flags + (rb * 2 + w) * 32 + FR_X2, (epoch + 1) * 8);
              fence_async_g();
              TRC(el, 2, 48 + u);
              rows_fetch(el, sb + SM_STG + w * 9216, P.xs[1] + (128 * rb + 16 * j + w) * (DM * 2), bars + B_XRW + w * 8);
            } else {
              mbar_wait(bars + B_XRW + w * 8, w ^ 1);
              TRC(el, 2, 48 + u);
              rows_stats(sb + SM_STG + w * 9216, g_XST + (rb * 2 + w) * 128 + 16 * j, epoch * 2 + 2, lane);
              TRC(el, 2, 50 + u);
            }
          }
          expect_tx_p(el, bars + B_CSQ, 864);
          bulk_load_p(el, sb + 3 * ST_BYTES + SM_CSQ, csf, 864, bars + B_CSQ);
        }
        if (L == 0) {
          TRC(el, 2, 43);
          mbar_wait(bars + B_WOI, 0);
          bulk_store_p(el, g_WO + j * WO_SL + rb * (41 * 128), sb + SM_WOI, (rb < 15 ? 41 : 33) * 128);
          publish_p(el, fj + FJ_WO);
          TRC(el, 2, 44);
          if (el) prefetch_l2((const uint8_t*)P.w_in + bid * 41472, 41472);
          uint4 y[4];
#pragma unroll
          for (int u = 0; u < 4; u++) y[u] = ldnc128((u < 2 ? (const uint8_t*)P.w_in + (100 + 300 * u) * (2 * FH * 2) + (FH + 1024 * u) * 2 : (const uint8_t*)P.w_sp + (1000 * u - 1500) * (SEQ * 2) + u * 1024) + lane * 16);
          float sq[2] = {0.f, 0.f};
#pragma unroll
          for (int u = 0; u < 4; u++) {
            const uint32_t x[4] = {y[u].x, y[u].y, y[u].z, y[u].w};
#pragma unroll
            for (int e = 0; e < 4; e++) sq[u >> 1] = fmaf(blo(x[e]), blo(x[e]), fmaf(bhi(x[e]), bhi(x[e]), sq[u >> 1]));
          }
          const float o0 = sqrtf(wsum(sq[0]) * (2.f * GA * GA * DM / 512.f)), o1 = sqrtf(wsum(sq[1]) * (C0S * C0S * SEQ / 512.f));
          const uint32_t off = (__float_as_uint(o0) & 0x7f800000u) >> 16 | 0x8000u | OFM;
          if (el) sts128(sb + SM_OFF, off * 0x10001u, min(__float_as_uint(o1) & 0x7f800000u, 0x7e000000u) | 0x00400000u, __float_as_uint(GB), 0u);
        }
#pragma unroll 1
        for (int w = 0; w < 2; w++) {
          mbar_wait(bars + B_EVT + (w * EV_N + EV_XS) * 8, L);
          if (!w) mbar_wait(bars + B_AF3 + XP0 * 8, L);
          if (el) asm volatile("cp.async.bulk.tensor.3d.global.shared::cta.tile.bulk_group [%0, {%2, %3, %4}], [%1];\ncp.async.bulk.commit_group;\ncp.async.bulk.wait_group.read 0;" ::"l"(&P.res[1]), "r"(sb + SM_STG + w * 9216), "r"(j * 72), "r"(rb * 64 + w * 32), "r"(0) : "memory");
          __syncwarp();
          if (lane < 2 && !w) mbar_arrive_cluster(mapa(bars + B_S5, lane));
        }
        if (el) { asm volatile("cp.async.bulk.wait_group 0;" ::: "memory"); mbar_arrive(bars + B_GATE3); }
        const uint32_t tag = epoch * 2 + L + 1;
        asm volatile("" : "+r"(lane));
#pragma unroll 1
        for (int b = 0; b < 8; b++) {
          if (!(b & 3)) {
            const int mb = b >> 2;
            mbar_wait(bars + B_ZS + mb * 8, L);
            lane += spin<ZD1>(P.zero);
            TRC(el && !mb, 2, L * 16 + 8);
            uint4 v;
#pragma unroll 1
            for (int it = 0; it < (1 << 22); it++) {
              v = ll_ld128(g_ZST + ((rb * 2 + mb) * 8 + (lane >> 2)) * 32 + 4 * j + (lane & 3));
              const uint32_t tg = 2 + L;
              if (__all_sync(~0u, !(((v.x ^ tg) | (v.y ^ tg) | (v.z ^ tg) | (v.w ^ tg)) & 3))) break;
            }
            const bool o = lane & 16;
            float ss = __uint_as_float(o ? v.y : v.x) + __shfl_xor_sync(~0u, __uint_as_float(o ? v.x : v.y), 16), sq = __uint_as_float(o ? v.w : v.z) + __shfl_xor_sync(~0u, __uint_as_float(o ? v.z : v.w), 16);
            ss += __shfl_xor_sync(~0u, ss, 4); sq += __shfl_xor_sync(~0u, sq, 4); ss += __shfl_xor_sync(~0u, ss, 8); sq += __shfl_xor_sync(~0u, sq, 8);
            const float mean = ss * (1.f / FH), rs = blo(pack2(rsqrtf(fmaxf(fmaf(sq, 1.f / FH, -mean * mean), 0.f) + 4.f * GA * GA * LN_EPS), 0.f));
            if (!(lane & 12)) ll_st64(g_RT + (mb * 16 + rb) * 64 + 8 * j + 2 * (lane & 3) + (lane >> 4), pack2(rs, rs * (mean - blo(lds32(sb + SM_OFF)))), tag);
            TRC(el && !mb, 2, L * 16 + 10);
            lane += spin<ZD2>(P.zero);
          }
          uint4 v[4];
#pragma unroll 1
          for (int it = 0; it < (1 << 22); it++) {
            bool ok = true;
#pragma unroll
            for (int u = 0; u < 4; u++) { v[u] = ll_ld128((const uint4*)g_RT + b * 128 + u * 32 + lane); ok = ok && v[u].y == tag && v[u].w == tag; }
            if (__all_sync(~0u, ok)) break;
          }
#pragma unroll
          for (int u = 0; u < 4; u++) {
            const uint32_t rt = sb + SM_RT + b * 512 + u * 128, ro = (lane >> 3) * 32 + (lane & 3) * 8 + ((lane >> 2) & 1) * 2;
            sts32(rt + 4096 + lane * 4, __byte_perm(v[u].x, v[u].z, 0x7632));
            asm volatile("st.shared.u16 [%0], %1;\nst.shared.u16 [%0 + 4], %2;" ::"r"(rt + ro), "h"((uint16_t)v[u].x), "h"((uint16_t)v[u].z) : "memory");
          }
          __syncwarp();
          if (el && (b & 1)) mbar_arrive(bars + B_RT + (b - 1) * 4);
          TRC(el && b < 2, 2, L * 16 + 11 + b);
        }
        TRC(el, 2, L * 16 + 9);
        mbar_wait(bars + B_EVT + EV_Z1 * 8, L);
        mbar_wait(bars + B_EVT + (EV_N + EV_Z1) * 8, L);
        fence_gpu();
        if (el) mbar_arrive(bars + B_Z1);
      }
    }
  } else {
    reg_alloc<232>();
    const int w = wid >> 2, q = wid & 3;
    int g = lane >> 2, t = lane & 3;
    const uint32_t ev = bars + B_EVT + w * EV_N * 8;
    const bool tr = (tid & 127) == 0;
    (void)tr;
    Cur c{0, 0};
    const uint32_t ebar = mapa(bars + B_EMPTY, (bid & 1) ^ (lane & 1));
    auto release = [&](uint32_t s) { if (lane < 2) mbar_arrive_cluster(ebar + s * 8); };
    const uint32_t stg = sb + SM_STG + w * 9216;
    uint32_t ia = 0;
    auto wait_ab = [&]() { mbar_wait_c(bars + B_FULL + c.s * 8, c.ph); mbar_wait_c(bars + B_FULLA + w * 32 + c.s * 8, (ia >> c.s) & 1); ia ^= 1u << c.s; };
    uint32_t lagph = 0, rph = 0;
    auto yield = [&](int left, int lag) { if (w == 1 && left == lag) mbar_wait_c(bars + B_LAG, lagph); };
    auto yield_done = [&]() { if (w == 0 && lane == 0) mbar_arrive(bars + B_LAG); };
    auto signal = [&](int e) { __syncwarp(); if (lane == 0) mbar_arrive(ev + e * 8); };
    TRC(tr, w, 0);

    {
      uint8_t* dst = g_WQ + j * WQ_SL + rb * 3456 + tid * 16;
#pragma unroll
      for (int u = 0; u < 5; u++) {
        stg128_if((u < 4 || rb < 8) && tid < 216, dst + u * (16 * 3456), wv[u].x, wv[u].y, wv[u].z, wv[u].w);
        if (u == 0) TRC(tr, w, 60);
      }
      if (P.zero == 0) {
        float s[8];
#pragma unroll
        for (int e = 0; e < 8; e++) s[e] = 0.f;
#pragma unroll
        for (int u = 0; u < 5; u++) {
          const bool on = u < 4 || rb < 8;
          const uint32_t x[4] = {wv[u].x, wv[u].y, wv[u].z, wv[u].w};
#pragma unroll
          for (int e = 0; e < 4; e++) { s[2 * e] += on ? blo(x[e]) : 0.f; s[2 * e + 1] += on ? bhi(x[e]) : 0.f; }
        }
#pragma unroll
        for (int m = 4; m; m >>= 1) {
#pragma unroll
          for (int e = 0; e < m; e++) s[e] = ((tid & m) ? s[e + m] : s[e]) + __shfl_xor_sync(~0u, (tid & m) ? s[e] : s[e + m], m);
        }
        stg32_if(tid < 216, g_CSP + bid * 216 + tid, __float_as_uint(s[0]));
      }
      __syncwarp();
      if (lane == 0) mbar_arrive(bars + B_IMG);
    }
    auto fetch_wo = [&]() {
#pragma unroll 1
      for (int u = tid; u < 328; u += 256) {
        const int m = min(41 * rb + (u >> 3), 647), k8 = m / 9;
        cp_async16(sb + SM_WOI + u * 16, (const uint8_t*)P.wo + (8 * k8 + (u & 7)) * (DM * 2) + (72 * j + 8 * (m - k8 * 9)) * 2);
      }
    };
    const uint32_t epoch = ldcg32(g_flags + (rb * 2 + w) * 32 + FR_EP + j);
    TRC(tr, w, 1);

#pragma unroll 1
    for (int L = 0; L < 2; L++) {
      const int tb = 2 + L * 24;
      asm volatile("" : "+r"(lane), "+r"(g), "+r"(t));
      (void)tb;
      const uint32_t tag = epoch * 2 + L + 1;
      uint32_t aoff = (w * 64 + q * 16 + (lane & 15)) * 128 + (((lane >> 4) ^ (lane & 7)) << 4);
      {
        uint32_t Pk[27][2];
        float sc0, sc1;
        const uint32_t att = stg + 2 * q * 128 + lane * 4;
        uint4* hp = g_HALO + ((((rb - (q == 0)) * 2 + w) * 8 + j) * 6) * 32 + lane;
        uint8_t* od = z1_block(rb, q >> 1, 0) + (9 * j) * 1024 + (4 * (q & 1) + w) * 128 + lane * 4;
        ACLK_INIT;
        {
          float acc[108];
#pragma unroll
          for (int i = 0; i < 108; i++) acc[i] = 0.f;
          uint32_t prev = 0;
#pragma unroll 1
          for (int kb = 0; kb < 9; kb++) {
            wait_ab();
            yield(9 - kb, LAG1);
            TRC(tr && kb == 0, w, tb + 0);
            PCLK(kb * 4);
            const uint32_t st = sb + c.s * ST_BYTES, da = dlo(st + w * 8192, 16), db = dlo(st + ST_B, 3456);
            wgmma_fence();
#pragma unroll
            for (int kk = 0; kk < 4; kk++) {
              wgmma_ss_n216(acc, dsc<1024, 1>(da, kk * 32), dsc<128, 0>(db, kk * 6912), 1);
              if (kk == 0) { wgmma_commit(); wgmma_wait<1>(); if (kb > 0) release(prev); }
            }
            wgmma_commit();
            if (kb == 8) yield_done();
            PCLK(kb * 4 + 1);
            if (kb == 0 && L == 0) fetch_wo();
            if (kb == 3 && L == 0) {
              asm volatile("cp.async.wait_all;" ::: "memory");
              fence_async_s();
              __syncwarp();
              if (lane == 0) mbar_arrive(bars + B_WOI);
            }
            PCLK(kb * 4 + 2);
            PCLK(kb * 4 + 3);
            prev = c.s; c.next();
          }
          const uint32_t cs = sb + prev * ST_BYTES + SM_CSQ + t * 8;
          mbar_wait_c(bars + B_CSQ, L);
          const float2 n0 = lds64f(sb + prev * ST_BYTES + SM_XST + w * 512 + (16 * q + g) * 8), n1 = lds64f(sb + prev * ST_BYTES + SM_XST + w * 512 + (16 * q + g + 8) * 8);
          const float m0 = n0.x, r0 = n0.y, m1 = n1.x, r1 = n1.y;
          float2 cv[27];
#pragma unroll
          for (int G = 0; G < 27; G++) cv[G] = lds64f(cs + G * 32);
          PCLK(36);
          wgmma_wait<0>();
          PCLK(37);
          release(prev);
          lagph ^= 1;
          TRC(tr, w, tb + 1);
          ACLK(0);
#pragma unroll
          for (int G = 9; G < 27; G++) Pk[G][1] = pack2(fmaf(m1, cv[G].x, acc[4 * G + 2]) * r1, fmaf(m1, cv[G].y, acc[4 * G + 3]) * r1);
          if (q < 3) {
#pragma unroll
            for (int i = 0; i < 18; i++) sts32(att + 256 + (i >> 1) * 1024 + (i & 1) * 128, Pk[9 + i][1]);
          } else if (rb < 15) {
#pragma unroll
            for (int i = 0; i < 6; i++) ll_st128(hp + i * 32, __uint_as_float(Pk[9 + 3 * i][1]), __uint_as_float(Pk[10 + 3 * i][1]), tag, __uint_as_float(Pk[11 + 3 * i][1]));
          }
#pragma unroll
          for (int G = 0; G < 27; G++) {
            if (G < 9) {
              Pk[G][0] = pack2(fmaf(m0, cv[G].x, acc[4 * G]), fmaf(m0, cv[G].y, acc[4 * G + 1]));
              Pk[G][1] = pack2(fmaf(m1, cv[G].x, acc[4 * G + 2]), fmaf(m1, cv[G].y, acc[4 * G + 3]));
            } else {
              Pk[G][0] = pack2(fmaf(m0, cv[G].x, acc[4 * G]) * r0, fmaf(m0, cv[G].y, acc[4 * G + 1]) * r0);
            }
          }
          sc0 = r0 * (0.23570226039551584f * 1.4426950408889634f); sc1 = r1 * (0.23570226039551584f * 1.4426950408889634f);
        }
        ACLK(1);
        constexpr int GA_[4] = {0, 2, 4, 7}, GB_[4] = {1, 3, 5, 8}, GC_[4] = {2, 4, 6, 6};
        float S1[4][4], S2[4][4];
        uint32_t qa[4][2], qc[4][2];
#pragma unroll
        for (int h = 0; h < 4; h++) {
#pragma unroll
          for (int r = 0; r < 2; r++) {
            qa[h][r] = (h == 0 || h == 3 || t >= h) ? Pk[GA_[h]][r] : 0u;
            qc[h][r] = (h == 3 ? t == 3 : t <= h) ? Pk[GC_[h]][r] : 0u;
          }
#pragma unroll
          for (int i = 0; i < 4; i++) S1[h][i] = S2[h][i] = 0.f;
          mma16(S1[h], qa[h][0], qa[h][1], Pk[GB_[h]][0], Pk[GB_[h]][1], Pk[9 + GA_[h]][0], Pk[9 + GB_[h]][0]);
          mma16(S2[h], qa[h][0], qa[h][1], Pk[GB_[h]][0], Pk[GB_[h]][1], Pk[9 + GA_[h]][1], Pk[9 + GB_[h]][1]);
        }
#pragma unroll
        for (int h = 0; h < 4; h++) {
          mma8(S1[h], qc[h][0], qc[h][1], Pk[9 + GC_[h]][0]);
          mma8(S2[h], qc[h][0], qc[h][1], Pk[9 + GC_[h]][1]);
        }
        uint32_t V1[9], V2[9];
#pragma unroll
        for (int i = 0; i < 9; i++) { V1[i] = movm(Pk[18 + i][0]); V2[i] = movm(Pk[18 + i][1]); }
        const bool remote = q == 0 && rb > 0;
        uint4 hv[6];
#pragma unroll
        for (int i = 0; i < 6; i++) hv[i] = make_uint4(0u, 0u, tag, 0u);
        if (remote) {
#pragma unroll
          for (int i = 0; i < 6; i++) hv[i] = ll_ld128(hp + i * 32);
        }
        const bool up0 = 2 * t > g, up1 = 2 * t + 1 > g;
        const uint32_t mup = (up0 ? 0xffffu : 0u) | (up1 ? 0xffff0000u : 0u);
        auto finish = [&](const float (&x0)[4], const float (&x1)[4], const uint32_t (&Va)[9], const uint32_t (&Vb)[9], int hi) {
          uint32_t p[4];
          float rs[4];
#pragma unroll
          for (int h = 0; h < 4; h++) {
            const float m = qmax(fmaxf(x0[h], x1[h]));
            p[h] = pack2(ex2(x0[h] - m), ex2(x1[h] - m));
            rs[h] = rcp_fast(qsum(blo(p[h]) + bhi(p[h])));
          }
#pragma unroll
          for (int i = 0; i < 9; i++) {
            const int h = 4 * i / 9;
            const bool split = i == 2 || i == 4 || i == 6, nx = split && 2 * t >= i;
            float O[4] = {0.f, 0.f, 0.f, 0.f}, N[4] = {0.f, 0.f, 0.f, 0.f};
            mma16(O, p[h] & mup, 0u, p[h] & ~mup, 0u, Va[i], Vb[i]);
            if (split) mma16(N, p[h + 1] & mup, 0u, p[h + 1] & ~mup, 0u, Va[i], Vb[i]);
            const float r = nx ? rs[h + (split ? 1 : 0)] : rs[h];
            stg32(od + i * 1024 + hi * 256, pack2((nx ? N[0] : O[0]) * r, (nx ? N[1] : O[1]) * r));
          }
        };
        {
          float x0[4], x1[4];
#pragma unroll
          for (int h = 0; h < 4; h++) { x0[h] = (up0 ? S1[h][2] : S2[h][2]) * sc1; x1[h] = (up1 ? S1[h][3] : S2[h][3]) * sc1; }
          finish(x0, x1, V1, V2, 1);
        }
        ACLK(2);
        bar_sync(1 + w, 128);
        uint32_t H[18];
        if (q > 0) {
#pragma unroll
          for (int i = 0; i < 18; i++) H[i] = lds32(att + (i >> 1) * 1024 + (i & 1) * 128);
        } else {
#pragma unroll 1
          for (int it = 0; it < (1 << 20); it++) {
            bool ok = true;
#pragma unroll
            for (int i = 0; i < 6; i++) ok = ok && hv[i].z == tag;
            if (__all_sync(~0u, ok)) break;
#pragma unroll
            for (int i = 0; i < 6; i++) hv[i] = ll_ld128(hp + i * 32);
          }
#pragma unroll
          for (int i = 0; i < 6; i++) { H[3 * i] = hv[i].x; H[3 * i + 1] = hv[i].y; H[3 * i + 2] = hv[i].w; }
        }
        float S0[4][4];
#pragma unroll
        for (int h = 0; h < 4; h++) {
#pragma unroll
          for (int i = 0; i < 4; i++) S0[h][i] = 0.f;
          mma16(S0[h], qa[h][0], 0u, Pk[GB_[h]][0], 0u, H[GA_[h]], H[GB_[h]]);
        }
#pragma unroll
        for (int h = 0; h < 4; h++) mma8(S0[h], qc[h][0], 0u, H[GC_[h]]);
        uint32_t V0[9];
#pragma unroll
        for (int i = 0; i < 9; i++) V0[i] = movm(H[9 + i]);
        ACLK(3);
        {
          const bool nohalo = (rb | q) == 0;
          float x0[4], x1[4];
#pragma unroll
          for (int h = 0; h < 4; h++) {
            x0[h] = up0 && nohalo ? -INFINITY : (up0 ? S0[h][0] : S1[h][0]) * sc0;
            x1[h] = up1 && nohalo ? -INFINITY : (up1 ? S0[h][1] : S1[h][1]) * sc0;
          }
          finish(x0, x1, V0, V1, 0);
        }
        ACLK(4);
        signal(EV_O);
        ACLK_OUT;
        TRC(tr, w, tb + 2);
      }
      if (c.s) { c.s = 0; c.ph ^= 1; }
      {
        float acc[36];
        const int hw = rb * 2 + w;
        const uint32_t xt = stg + (8 * q + g) * 144 + t * 4;
        uint32_t xm = stg + (8 * q + (lane & 7)) * 144 + (lane & 8) * 576 + (lane & 16);
        uint8_t* xn = xn_block(hw) + j * 9216 + q * 256 + lane * 4;
        uint32_t* sp = (uint32_t*)(g_ST1 + (hw * 8 + j) * 32 + 8 * q) + lane;
        const uint4* sg = g_ST1 + (hw * 8 + t) * 32 + 8 * q + g;
        asm volatile("" : "+r"(xm), "+l"(xn), "+l"(sp), "+l"(sg));
        mbar_wait_c(bars + B_RES + w * 8, L);
        TRC(tr, w, tb + 21);
#pragma unroll
        for (int i = 0; i < 18; i++) { const uint32_t x = lds32(xt + (i >> 1) * 16 + (i & 1) * 4608); acc[2 * i] = blo(x); acc[2 * i + 1] = bhi(x); asm volatile("" : "+f"(acc[2 * i]), "+f"(acc[2 * i + 1])); }
        mbar_wait_c(bars + B_WF, L);
        const uint32_t db = dlo(sb, 1152), of = bars + B_OF + w * 40;
        uint32_t da[5];
#pragma unroll
        for (int e = 0; e < 5; e++) da[e] = __shfl_sync(~0u, dlo(sb + o_place(w, e), 1024), 0);
        if (w) bar_sync(7, 256);
#pragma unroll
        for (int kb = 0; kb < 9; kb++) {
          const int e = (kb + 1) >> 1;
          if (kb == 0 || (kb & 1)) { mbar_wait_c(of + e * 8, L); wgmma_fence(); }
          TRC(tr && kb == 0, w, tb + 3);
          if (kb == HO2 && !w) bar_arrive(7, 256);
#pragma unroll
          for (int kk = 0; kk < 4; kk++) wgmma_ss_n72(acc, dsc<128, 0>(da[e], (kb && !(kb & 1)) * 8192 + kk * 2048), dsc<128, 0>(db, kb * 9216 + kk * 2304), 1);
          if (!(kb & 1) || kb == 5) wgmma_commit();
          if (kb == 5) { wgmma_wait<1>(); if (lane + w == 0) mbar_arrive(bars + B_X3); }
        }
        RCLK_INIT;
        wgmma_wait<0>();
        RCLK(0);
        if (lane < 2) mbar_arrive_cluster(ebar + B_XD - B_EMPTY + w * 8);
        TRC(tr && P5TRACE != 5, w, tb + 4);
        {
          float s0 = 0.f, s1 = 0.f, q0 = 0.f, q1 = 0.f;
#pragma unroll
          for (int i = 0; i < 36; i++) {
            if (i & 2) { s1 += acc[i]; q1 = fmaf(acc[i], acc[i], q1); } else { s0 += acc[i]; q0 = fmaf(acc[i], acc[i], q0); }
          }
          const bool o1 = t & 1, o2 = t & 2;
          const float ss = (o1 ? s1 : s0) + __shfl_xor_sync(~0u, o1 ? s0 : s1, 1), sq = (o1 ? q1 : q0) + __shfl_xor_sync(~0u, o1 ? q0 : q1, 1);
          const float v = (o2 ? sq : ss) + __shfl_xor_sync(~0u, o2 ? ss : sq, 2);
          asm volatile("st.relaxed.gpu.global.u32 [%0], %1;" ::"l"(sp), "r"((__float_as_uint(v) & ~3u) | (2 + L)) : "memory");
        }
        RCLK(1);
        RCLK(2);
        sg += spin<PDEL>(P.zero);
        uint4 pa, pb;
#pragma unroll 1
        for (int it = 0; it < (1 << 20); it++) {
          pa = ll_ld128(sg); pb = ll_ld128(sg + 128);
          const uint32_t tg = 2 + L;
          if (__all_sync(~0u, !(((pa.x ^ tg) | (pa.y ^ tg) | (pa.z ^ tg) | (pa.w ^ tg) | (pb.x ^ tg) | (pb.y ^ tg) | (pb.z ^ tg) | (pb.w ^ tg)) & 3))) break;
        }
        RCLK(3);
        float mean0 = qsum(__uint_as_float(pa.x) + __uint_as_float(pb.x)) * (-1.f / DM), mean1 = qsum(__uint_as_float(pa.y) + __uint_as_float(pb.y)) * (-1.f / DM);
        const float rs0 = GA * rsqrtf(fmaxf(fmaf(qsum(__uint_as_float(pa.z) + __uint_as_float(pb.z)), 1.f / DM, -mean0 * mean0), 0.f) + LN_EPS);
        const float rs1 = GA * rsqrtf(fmaxf(fmaf(qsum(__uint_as_float(pa.w) + __uint_as_float(pb.w)), 1.f / DM, -mean1 * mean1), 0.f) + LN_EPS);
        mean0 *= rs0; mean1 *= rs1;
#pragma unroll
        for (int i = 0; i < 18; i++) {
          const float a = (i & 1) ? rs1 : rs0, b = (i & 1) ? mean1 : mean0;
          stg32(xn + (i >> 1) * 1024 + (i & 1) * 128, pack2(fmaf(acc[2 * i], a, b), fmaf(acc[2 * i + 1], a, b)));
        }
        signal(EV_X1);
        RCLK(4);
        if (w) {
          uint32_t rp = 0;
#pragma unroll 1
          for (int u = q; u < 24; u += 4) {
            const uint32_t mb = u < 2 * SPL ? u >= SPL : u & 1, k = u < 2 * SPL ? u - mb * SPL : u >> 1, o = k * 12288 + mb * 6144;
            const uint32_t a = sb + o + lane * 32 + (lane >> 2) * 4;
            mbar_wait_c(bars + B_AF3 + mb * 96 + k * 8, L);
#pragma unroll 1
            for (int it = 0; it < (1 << 16); it++) {
              uint32_t x = lds32(a);
#pragma unroll
              for (int e = 1; e < 6; e++) x = max(x, lds32(a + e * 1024));
              if (!__any_sync(~0u, x == ~0u)) break;
              fence_async_s();
              __syncwarp();
              expect_tx_p(lane == 0, bars + B_RB + q * 8, 6144);
              bulk_load_p(lane == 0, sb + o, xn_block(rb * 2 + mb) + k * 6144, 6144, bars + B_RB + q * 8);
              mbar_wait_c(bars + B_RB + q * 8, rph);
              rph ^= 1; rp++;
            }
            if (lane <= (u < 2 * SPL)) mbar_arrive(bars + B_AV + (u < SPL ? 12 + k : k) * 8);
          }
          TRVI(lane == 0, 5, 56 + L * 4 + q, rp);
        }
#pragma unroll
        for (int u = 0; u < 4; u++)
          stsm4(xm + u * 32, pack2(acc[8 * u], acc[8 * u + 1]), pack2(acc[8 * u + 2], acc[8 * u + 3]), pack2(acc[8 * u + 4], acc[8 * u + 5]), pack2(acc[8 * u + 6], acc[8 * u + 7]));
        asm volatile("stmatrix.sync.aligned.m8n8.x2.shared.b16 [%0], {%1,%2};" ::"r"(xm + 128), "r"(pack2(acc[32], acc[33])), "r"(pack2(acc[34], acc[35])) : "memory");
        fence_async_s();
        signal(EV_XS);
        RCLK(5);
        TRC(tr, w, tb + 5);
        RCLK(6);
        RCLK_OUT;
      }
      {
      float acc[160];
#pragma unroll
      for (int i = 0; i < 160; i++) acc[i] = 0.f;
      float s[2] = {0.f, 0.f}, qq[2] = {0.f, 0.f}, zo = 0.f;
      const uint32_t zp = sb + SM_ZP3 + (tid & 127) * 4;
      auto zstat = [&](int mb, bool on) {
        const bool o1 = t & 1, o2 = t & 2;
        const float ss = ((o1 ? s[1] : s[0]) + __shfl_xor_sync(~0u, o1 ? s[0] : s[1], 1)) * 0x1p60f, sq = (o1 ? qq[1] : qq[0]) + __shfl_xor_sync(~0u, o1 ? qq[0] : qq[1], 1);
        const uint32_t v = (__float_as_uint((o2 ? sq : ss) + zo + __shfl_xor_sync(~0u, o2 ? ss : sq, 2)) & ~3u) | (2 + L);
        asm volatile("{\n.reg .pred p, q, r;\nsetp.eq.u32 p, %4, 1;\nsetp.eq.u32 q, %4, 2;\nsetp.eq.and.u32 r, %5, 0, q;\n@p st.shared.u32 [%0], %2;\n@p bar.arrive 13, 256;\n"
                     "@q st.relaxed.gpu.global.u32 [%1], %2;\n@r mbarrier.arrive.shared::cta.b64 _, [%3];\n}" ::"r"(zp + mb * 512), "l"((uint32_t*)(g_ZST + ((rb * 2 + mb) * 8 + j) * 32) + (tid & 127)),
                     "r"(v), "r"(bars + B_ZS + mb * 8), "r"(on ? 1 + w : 0), "r"(lane) : "memory");
        s[0] = s[1] = qq[0] = qq[1] = 0.f;
      };
      const uint32_t ebar3 = ebar + (B_E3 - B_EMPTY);
#pragma unroll 1
      for (int half = 0; half < 2; half++) {
        const bool big = half != w;
        auto rel3 = [&](int p) { if (lane < 2) mbar_arrive_cluster(ebar3 + p * 8); };
        if (half + w > 0) bar_sync(6 + w, 256);
        auto pass = [&](auto nk) {
          constexpr int NK = nk.value;
          uint32_t d0 = dlo(sb, 1024), ph = half & ~w, af = bars + B_AV;
          const uint32_t db = dlo(sb + SM_B3, NK == 3 ? 6144 : 2048);
          const bool lead = NK == 3 && !half;
          if (lead) {
#pragma unroll
            for (int u = 0; u < 2 * SPL; u++) {
              const int mb = u / SPL, p = u % SPL;
              if (!mb) mbar_wait_c(bars + B_F3 + p * 8, 0);
              mbar_wait_c(af + (mb ? p : 12 + p) * 8, L);
              TRC(tr && u == 0, w, tb + 6);
              if (p == 0) SCLK(mb * 4);
              wgmma_fence();
#pragma unroll
              for (int kk = 0; kk < 3; kk++) {
                wgmma_ss_n128(acc + mb * 80, dsc<128, 0>(d0, p * 12288 + kk * 2048 + mb * 6144), dsc<1024, 1>(db, p * 12288 + kk * 2048), p + kk > 0);
                if (kk == 0 && u > SPL) { wgmma_commit(); wgmma_wait<1>(); rel3(p - 1); }
              }
              wgmma_commit();
            }
          }
#pragma unroll 1
          for (int it = 0; it < 6 / NK; it++) {
#pragma unroll
            for (int p = 0; p < 6; p++) {
              if (p < SPL && lead && it == 0) continue;
              mbar_wait_c(bars + B_F3 + p * 8, ph);
              if (NK == 3) mbar_wait_c(af + p * 8, L);
              TRC(tr && p == 0 && it == 0, w, tb + 6 + half * 4);
              if (NK == 2 ? !(p & 1) : p % 3 == 0) SCLK(half * 11 + (NK == 2 ? it * 3 + p / 2 : it * 2 + p / 3));
              wgmma_fence();
#pragma unroll
              for (int u = 0; u < 2 * NK; u++) {
                const int kk = u >> 1, mb = u & 1, e = p * NK + kk;
                const uint64_t da = dsc<128, 0>(d0, (e / 3) * 12288 + (e % 3) * 2048 + mb * 6144);
                if (NK == 3) wgmma_ss_n128(acc + mb * 80, da, dsc<1024, 1>(db, p * 12288 + kk * 2048), e > 0 || it > 0);
                else wgmma_ss_n160(acc + mb * 80, da, dsc<1024, 1>(db, p * 12288 + kk * 6144), e > 0 || it > 0);
                if (u == 0) { wgmma_commit(); wgmma_wait<1>(); if (p > 0 || it > 0) rel3((p + 5) % 6); }
                if (u == HO3 && p == 5 && it == 6 / NK - 1) bar_arrive(7 - w, 256);
              }
              wgmma_commit();
            }
            d0 += NK * 1536; af += 48;
            ph ^= 1;
          }
        };
        if (big) pass(Int<2>{}); else pass(Int<3>{});
        if (w) { bar_sync(13, 256); zo = __uint_as_float(lds32(zp + half * 512)); }
        if (half) zstat(1, true);
        mbar_wait_c(bars + B_GATE3, L);
        const uint32_t off2 = lds32(sb + SM_OFF);
        const int go = (j & 1) ? (big ? 0 : 20) : (big ? 16 : 0);
        const float* gbp = (const float*)(smem_raw + SM_OFF + 8);
        asm volatile("" : "+l"(gbp));
        uint8_t* zd = half ? z1_block(rb, 0, j) + go * 1024 + (q & 1) * 2048 + (q >> 1) * 512 + lane * 16 : z2_block(rb, j) + q * 9216 + go * 128 + ((g & 3) * 2 + (g >> 2)) * 16 + t * 4;
        wgmma_wait<0>();
        SCLK(half * 11 + 9);
        rel3(5);
        TRC(tr, w, tb + 7 + half * 4);
        auto gelu = [&](auto z2) {
          constexpr int NC = z2.value ? NC2 : NC1;
          float gate[NC], gb = GB, gn = GB;
          uint32_t qa[2][3] = {{0, 0, 0}, {0, 0, 0}};
#pragma unroll
          for (int e = 0; e < NC; e++) gate[e] = GB;
#pragma unroll
          for (int G = 0; G < 20; G++) {
            if (G == 16 && !big) break;
            if (G % (z2.value ? LD2 : LD1) == 0) { gb = gn; if (G < 20 - (z2.value ? LD2 : LD1)) asm volatile("ld.f32 %0, [%1];" : "=f"(gn) : "l"(gbp) : "memory"); }
#pragma unroll
            for (int r = 0; r < 2; r++) {
              float z[2];
              float& gt = gate[(G * 2 + r) % NC];
#pragma unroll
              for (int e = 0; e < 2; e++) {
                const float v = acc[4 * G + 2 * r + e];
                z[e] = fmaf(v, tanh_fast(v * fmaf(v, v, gt)), v);
                if (z2.value) { s[r] = fmaf(z[e], 0x1p-60f, s[r]); qq[r] = fmaf(z[e], z[e], qq[r]); }
              }
              const uint32_t pk = pack2(z[0], z[1]);
              if (z2.value) {
                stg32(zd + G * 128 + r * 4608, hsub2(pk, off2));
                gt = fmaf(qq[r], s[r], gb);
              } else {
                gt = fmaf(__uint_as_float(pk), 0x1p-60f, gb);
                if ((G & 3) == 3) stg128(zd + (G >> 2) * 4096 + r * (8 * ZB), qa[r][0], qa[r][1], qa[r][2], pk);
                else qa[r][G & 3] = pk;
              }
            }
          }
        };
#pragma unroll 1
        for (int mb = 0;; mb++) {
          if (half) gelu(Int<0>{}); else gelu(Int<1>{});
          if (mb) break;
          zstat(0, !half);
#pragma unroll
          for (int i = 0; i < 80; i++) acc[i] = acc[80 + i];
          zd += half ? 1024 : 128 * ZB;
        }
        signal(half ? EV_Z1 : EV_ZN);
        SCLK(half * 11 + 10);
        TRC(tr, w, tb + 8 + half * 4);
      }
      }
      uint32_t hA[18][4];
      {
        float acc[144];
        const float c0 = __uint_as_float(lds32(sb + SM_OFF + 4));
#pragma unroll
        for (int i = 0; i < 144; i++) {
          asm volatile("fma.rn.f32 %0, %1, %2, %3;" : "=f"(acc[i]) : "f"(__uint_as_float(P.zero)), "f"((float)(i + 2)), "f"(c0));
        }
        uint32_t prev = 0;
        auto stage = [&](int kb) {
          mbar_wait_c(bars + B_FULL + c.s * 8, c.ph);
          TRC(tr && kb == 0, w, tb + 13);
          SCLK(22 + kb);
          const uint32_t st = sb + c.s * ST_BYTES, db = dlo(st + ST_B, 4608), rt = sb + SM_RT + kb * 128 + t * 8;
          uint32_t a[4][4];
#pragma unroll
          for (int kk = 0; kk < 4; kk++) {
            uint32_t r[4];
            ldsm4(r, st + (aoff ^ (kk << 5)));
            const uint2 sc = lds64(rt + kk * 32);
            a[kk][0] = hmul2(__byte_perm(r[0], r[2], 0x5410), sc.x); a[kk][2] = hmul2(__byte_perm(r[0], r[2], 0x7632), sc.y);
            a[kk][1] = hmul2(__byte_perm(r[1], r[3], 0x5410), sc.x); a[kk][3] = hmul2(__byte_perm(r[1], r[3], 0x7632), sc.y);
          }
          if (kb + w == 0) bar_sync(6, 256);
          wgmma_fence();
#pragma unroll
          for (int i = 0; i < 8; i++) {
            const int kk = i & 3, hf = i >> 2;
            wgmma_rs_n144(acc + hf * 72, a[kk], dsc<128, 0>(db, kk * 9216 + hf * 2304), 1);
            if (i == 0) { wgmma_commit(); wgmma_wait<1>(); if (kb) release(prev); }
            if (i == 3) wgmma_commit();
          }
          wgmma_commit();
          prev = c.s; c.next();
        };
#pragma unroll 1
        for (int kb = 0; kb < 32; kb += 2) {
          if (!(kb & 7)) mbar_wait_c(bars + B_RT + kb, L);
          stage(kb);
          stage(kb + 1);
        }
        mbar_wait_c(bars + B_CV + w * 8, L);
        const float gk = 0.5f / GA;
        const float c1 = __uint_as_float(lds32(sb + SM_OFF + 4));
        const float gb0 = -gk * (c1 + __uint_as_float(lds32(sb + SM_CV + w * 256 + (16 * q + g) * 4))), gb1 = -gk * (c1 + __uint_as_float(lds32(sb + SM_CV + w * 256 + (16 * q + g + 8) * 4)));
        if (w == 1) { mbar_wait_c(bars + B_FULL + c.s * 8, c.ph); release(c.s); c.next(); }
        mbar_wait_c(bars + B_FULL + c.s * 8, c.ph);
        const uint32_t zs = sb + c.s * ST_BYTES + ST_B + (tid & 127) * 16;
        uint4 zl, zh;
#pragma unroll
        for (int u = 0; u < 18; u++) {
          if (u == 0) wgmma_wait<1>();
          if (u == 9) {
            wgmma_wait<0>();
            release(prev);
            if (L == 0) signal(EV_P4);
            TRC(tr, w, tb + 14);
            SCLK(54);
          }
          if (!(u & 1)) { zl = lds128(zs + u * 2048); zh = lds128(zs + u * 2048 + 2048); }
          const uint4 z = (u & 1) ? make_uint4(zl.z, zh.z, zl.w, zh.w) : make_uint4(zl.x, zh.x, zl.y, zh.y);
          hA[u][0] = hmul2(z.x, pack2(fmaf(acc[8 * u], gk, gb0), fmaf(acc[8 * u + 1], gk, gb0)));
          hA[u][1] = hmul2(z.y, pack2(fmaf(acc[8 * u + 2], gk, gb1), fmaf(acc[8 * u + 3], gk, gb1)));
          hA[u][2] = hmul2(z.z, pack2(fmaf(acc[8 * u + 4], gk, gb0), fmaf(acc[8 * u + 5], gk, gb0)));
          hA[u][3] = hmul2(z.w, pack2(fmaf(acc[8 * u + 6], gk, gb1), fmaf(acc[8 * u + 7], gk, gb1)));
        }
        __syncwarp();
        release(c.s);
        c.next();
        if (w == 0) { mbar_wait_c(bars + B_FULL + c.s * 8, c.ph); release(c.s); c.next(); }
        TRC(tr, w, tb + 15);
      }
      {
        CLK_INIT;
        if (w == 1) bar_arrive(6, 256);
        uint32_t pk[16];
#pragma unroll
        for (int i = 0; i < 16; i++) pk[i] = 0u;
        auto dump = [&](int p) {
          const uint32_t d = sb + (p & 3) * ST_BYTES, cb = p + j >= 9 ? p + j - 9 : p + j;
          if (lane == 0) asm volatile("cp.async.bulk.wait_group.read 3;" ::: "memory");
          __syncwarp();
#pragma unroll
          for (int u = 0; u < 4; u++) stsm4(d + (aoff ^ (u << 5)), pk[4 * u], pk[4 * u + 1], pk[4 * u + 2], pk[4 * u + 3]);
          fence_async_s();
          __syncwarp();
          tma3d_red_p(lane == 0, &P.red, cb * 64, rb * 64 + q * 16, w, d + w * 8192 + q * 2048);
        };
#pragma unroll 1
        for (int p = 0; p < 9; p++) {
          float acc[32];
          CLK(0);
          mbar_wait_c(bars + B_FULL + c.s * 8, c.ph);
          const uint32_t db = dlo(sb + c.s * ST_BYTES + ST_B, 0);
          CLK(1);
          bar_sync(6 + w, 256);
          CLK(2);
          wgmma_fence();
#pragma unroll
          for (int kk = 0; kk < 18; kk++) {
            wgmma_rs_n64(acc, hA[kk], dsc<1024, 1>(db, kk * 2048), kk != 0);
            if (kk == PPK && (w == 0 || p < 8)) bar_arrive(7 - w, 256);
          }
          wgmma_commit();
          CLK(3);
          if (p > 0) dump(p - 1);
          CLK(5);
          wgmma_wait<0>();
          CLK(4);
          if (L == 0 || p < 5) release(c.s);
          c.next();
#pragma unroll
          for (int i = 0; i < 16; i++) pk[i] = pack2(acc[2 * i], acc[2 * i + 1]);
          if (p == 8) { TRC(tr, w, tb + 16); dump(8); TRC(tr, w, tb + 17); }
        }
        if (lane == 0) asm volatile("cp.async.bulk.wait_group 0;" ::: "memory");
        if (L == 0) signal(EV_PT);
        CLK_OUT;
        TRC(tr, w, tb + 18);
      }
    }
    if ((tid & 127) == 0) g_flags[(rb * 2 + w) * 32 + FR_EP + j] = epoch + 1;
    if (tid == 0) g_flags[FJ + j * 32 + FJ_EP + rb] = epoch + 1;
  }
}

typedef CUresult (*EncodeFn)(CUtensorMap*, CUtensorMapDataType, cuuint32_t, void*, const cuuint64_t*, const cuuint64_t*, const cuuint32_t*,
                             const cuuint32_t*, CUtensorMapInterleave, CUtensorMapSwizzle, CUtensorMapL2promotion, CUtensorMapFloatOOBfill);

static void make_map(EncodeFn fn, CUtensorMap* m, const void* ptr, int rank, uint64_t d0, uint64_t d1, uint64_t d2, uint64_t s1, uint64_t s2,
                     uint32_t b0, uint32_t b1, uint32_t b2, CUtensorMapSwizzle swz) {
  cuuint64_t dims[3] = {d0, d1, d2}, strides[2] = {s1, s2};
  cuuint32_t box[3] = {b0, b1, b2}, es[3] = {1, 1, 1};
  fn(m, CU_TENSOR_MAP_DATA_TYPE_BFLOAT16, rank, const_cast<void*>(ptr), dims, strides, box, es, CU_TENSOR_MAP_INTERLEAVE_NONE, swz,
     CU_TENSOR_MAP_L2_PROMOTION_L2_128B, CU_TENSOR_MAP_FLOAT_OOB_FILL_NONE);
}

}

extern "C" void kernel_launch(void* const* d_in, const int* in_sizes, int n_in, void* d_out, int out_size) {
  using namespace mk;
  (void)in_sizes; (void)n_in; (void)out_size;
  static EncodeFn fn = nullptr;
  if (!fn) {
    cudaDriverEntryPointQueryResult qr;
    cudaGetDriverEntryPoint("cuTensorMapEncodeTiled", (void**)&fn, cudaEnableDefault, &qr);
    cudaFuncSetAttribute(mega_kernel, cudaFuncAttributeMaxDynamicSharedMemorySize, SM_TOTAL);
  }
  Params p;
  p.wqkv = (const __nv_bfloat16*)d_in[1];
  p.wo = (const __nv_bfloat16*)d_in[2];
  p.w_in = (const __nv_bfloat16*)d_in[4];
  p.w_sp = (const __nv_bfloat16*)d_in[5];
  p.b_sp = (const __nv_bfloat16*)d_in[6];
  p.w_out = (const __nv_bfloat16*)d_in[7];
  p.zero = 0;
  p.xs[0] = (uint8_t*)d_in[0];
  p.xs[1] = (uint8_t*)d_out;
  for (int cl = 0; cl < NGRID / 2; cl++) {
    const int tp = cl < 4 ? cl + 62 : cl - 4;
    p.role[cl] = tp < 32 ? tp : tp < 60 ? (4 + (tp - 32) / 7) * 8 + (tp - 32) % 7 + 1 : tp < 62 ? tp + 4 : (tp - 58) * 8;
  }
  make_map(fn, &p.wsp, p.w_sp, 3, 2048, 1024, 2, 8192, 4096, 64, 64, 2, CU_TENSOR_MAP_SWIZZLE_128B);
  for (int i = 0; i < 2; i++) {
    make_map(fn, &p.act[i], p.xs[i], 3, DM, 1024, 2, 2304, 1152, 64, 64, 1, CU_TENSOR_MAP_SWIZZLE_128B);
    make_map(fn, &p.res[i], p.xs[i], 3, DM, 1024, 2, 2304, 1152, 72, 32, 2, CU_TENSOR_MAP_SWIZZLE_NONE);
  }
  make_map(fn, &p.red, d_out, 3, DM, 1024, 2, 2304, 1152, 64, 16, 1, CU_TENSOR_MAP_SWIZZLE_128B);
  for (int i = 0; i < 2; i++) make_map(fn, &p.winb[i], p.w_in + 32 * i, 3, 64, 576, 72 - i, 9216, 128, 64, 16, 3, CU_TENSOR_MAP_SWIZZLE_128B);
  make_map(fn, &p.wins, p.w_in, 3, 64, 576, 72, 9216, 128, 64, 48, 1, CU_TENSOR_MAP_SWIZZLE_128B);
  make_map(fn, &p.wout, p.w_out, 2, 576, 2304, 1, 1152, 0, 64, 144, 1, CU_TENSOR_MAP_SWIZZLE_128B);
  mega_kernel<<<NGRID, 384, SM_TOTAL, cudaStreamPerThread>>>(p);
}
```

```cpp
#include <cuda_runtime.h>
#include <cuda.h>
#include <cuda_bf16.h>
#include <stdint.h>

#define MK_TRACE 0
#define MK_DBG 0
#define P5TRACE 0
#define LAG1 1
#define C0S 32.f
#define OFM 0x10u
#define NC2 2
#define NC1 6
#define XRLX 0
#define PDEL 8
#define LD1 4
#define LD2 2
#define ZD1 8
#define ZD2 8
#define WPF 1
#define YPACE 2
#define HO2 8
#define SPL 4
#define XP0 0
#define EFM 0x33333022
#define EF(i) ((((EFM >> (4 * (i))) & 3) == 3) || (((EFM >> (4 * (i))) >> L) & 1))
#define AEP 2
#define PZI 4
#define RESL 1
#define P2L 1
#define KS 1
#define RFI 3
#define XK1 1
#define XK2 2
#define APACE 7
#define HO3 1
#define PPK 13

namespace mk {

constexpr int SEQ = 2048, DM = 576, FH = 2304;
constexpr int NCTA = 128;
constexpr int NGRID = 132;
constexpr uint32_t ZB = 36864;
constexpr uint32_t WQ_SL = 72 * 3456;
constexpr uint32_t WO_SL = 72 * 1152;
constexpr float LN_EPS = 1e-5f;
constexpr float GA = 0.3292034911525734f, GB = 2.423681954311584f;

constexpr uint32_t ST_BYTES = 53248, ST_B = 16384, NST = 4;
constexpr uint32_t SM_STG = NST * ST_BYTES;
constexpr uint32_t SM_BAR = SM_STG + 2 * 9216, B_OFF = 896;
constexpr uint32_t SM_OFF = SM_BAR + B_OFF;
constexpr uint32_t SM_TOTAL = SM_BAR + 1024;
constexpr uint32_t SM_RT = SM_STG + 9216, SM_CV = SM_STG + 17408, SM_WT = SM_STG;
constexpr uint32_t SM_WOI = 44032, SM_CSQ = 49280, SM_XST = 50176;
enum { EV_PT = 0, EV_O = 1, EV_X1 = 2, EV_ZN = 3, EV_Z1 = 4, EV_XS = 5, EV_N = 6 };
constexpr uint32_t B_FULL = 0, B_FULLA = 32, B_RES = 96, B_WT = 112, B_GATE3 = 128, B_Z1 = 136, B_ZOK = 144, B_CV = 152, B_XRW = 168, B_F3 = 184, B_WF = 232, B_OF = 240,
                   B_RT = 320, B_AF3 = 352, B_RB = 544,
                   B_AD = 576, B_S5 = 608, B_AV = 616,
                   B_CSQ = 760,
                   B_LAG = 768, B_X3 = 776, B_ZS = 784, B_EVT = 800,
                   B_IMG = 912, B_WOI = 920, B_E3 = 928, B_XD = 976,
                   B_EMPTY = 992;
constexpr uint32_t SM_B3 = 9 * 16384, SM_ZP3 = SM_STG + 8192;

enum { FR_X2 = 0, FR_O = 1, FR_X1 = 3, FR_XR = 5, FR_OL = 7, FR_PZ = 9, FR_EP = 16, FJ = 32 * 32, FJ_WQ = 0, FJ_WO = 1, FJ_ZN = 3, FJ_P4 = 5, FJ_EP = 16, F_N = FJ + 8 * 32 };

struct Scratch {
  alignas(1024) uint32_t flags[F_N];
  alignas(1024) float CSP[2 * NCTA * 216];
  alignas(1024) uint2 RT[SEQ];
  alignas(1024) uint4 XST[2 * SEQ];
  alignas(1024) uint4 ST1[SEQ * 4];
  alignas(1024) uint4 ZST[SEQ * 4];
  alignas(1024) uint4 HALO[32 * 8 * 6 * 32];
  alignas(1024) uint8_t WO[8 * WO_SL];
  alignas(1024) uint8_t WQ[8 * WQ_SL];
  alignas(1024) uint8_t Z[576 * ZB];
};
__device__ Scratch g_scratch;

struct Ptrs {
  const __nv_bfloat16* wqkv;
  uint8_t* WQ;
  uint32_t* flags;
  float* CSP;
  const uint8_t* x;
  uint32_t zero;
  uint4 *XST, *HALO, *ST1, *ZST;
  uint2* RT;
  uint8_t *Z, *WO, *out;
  const __nv_bfloat16 *wo, *w_in, *w_sp, *b_sp;
};
struct Params {
  CUtensorMap wsp, winb[2], wins, wout;
  CUtensorMap act[2];
  CUtensorMap res[2];
  CUtensorMap row[2];
  CUtensorMap red;
};

__device__ __forceinline__ uint32_t smem_u32(const void* p) { return (uint32_t)__cvta_generic_to_shared(p); }
__device__ __forceinline__ void mbar_init(uint32_t bar, uint32_t cnt) { asm volatile("mbarrier.init.shared::cta.b64 [%0], %1;" ::"r"(bar), "r"(cnt)); }
__device__ __forceinline__ void mbar_arrive(uint32_t bar) { asm volatile("mbarrier.arrive.shared::cta.b64 _, [%0];" ::"r"(bar) : "memory"); }
__device__ __forceinline__ void mbar_wait(uint32_t bar, uint32_t parity) {
  asm volatile(
      "{\n.reg .pred p;\n.reg .u32 c;\nmov.u32 c, 0;\nLAB_WAIT:\n"
      "mbarrier.try_wait.parity.shared::cta.b64 p, [%0], %1;\n@p bra LAB_DONE;\n"
      "add.u32 c, c, 1;\nsetp.lt.u32 p, c, 0x100000;\n@p bra LAB_WAIT;\ntrap;\nLAB_DONE:\n}" ::"r"(bar), "r"(parity)
      : "memory");
}
__device__ __forceinline__ void mbar_wait_c(uint32_t bar, uint32_t parity) {
  asm volatile("{\n.reg .pred p;\nLAB_WAIT:\nmbarrier.try_wait.parity.shared::cta.b64 p, [%0], %1;\n@!p bra LAB_WAIT;\n}" ::"r"(bar), "r"(parity) : "memory");
}
__device__ __forceinline__ void flag_wait(const uint32_t* f, uint32_t target) {
  asm volatile(
      "{\n.reg .pred p;\n.reg .u32 c, v;\nmov.u32 c, 0;\nLAB_WAIT:\n"
      "ld.relaxed.gpu.global.u32 v, [%0];\nsub.u32 v, v, %1;\nsetp.ge.s32 p, v, 0;\n@p bra LAB_DONE;\n"
      "add.u32 c, c, 1;\nsetp.lt.u32 p, c, 0x400000;\n@p bra LAB_WAIT;\ntrap;\nLAB_DONE:\nfence.acquire.gpu;\n}" ::"l"(f), "r"(target)
      : "memory");
}
__device__ __forceinline__ void fence_gpu() { asm volatile("fence.acq_rel.gpu;" ::: "memory"); }
__device__ __forceinline__ void fence_async_g() { asm volatile("fence.proxy.async.global;" ::: "memory"); }
__device__ __forceinline__ void fence_async_s() { asm volatile("fence.proxy.async.shared::cta;" ::: "memory"); }
__device__ __forceinline__ uint32_t elect_one() {
  uint32_t p; asm volatile("{\n.reg .pred P;\nelect.sync _|P, 0xffffffff;\nselp.u32 %0, 1, 0, P;\n}" : "=r"(p)); return p;
}
__device__ __forceinline__ void expect_tx_p(uint32_t el, uint32_t bar, uint32_t bytes) {
  asm volatile("{\n.reg .pred P;\nsetp.ne.u32 P, %2, 0;\n@P mbarrier.arrive.expect_tx.shared::cta.b64 _, [%0], %1;\n}" ::"r"(bar), "r"(bytes), "r"(el) : "memory");
}
__device__ __forceinline__ void bulk_load_p(uint32_t el, uint32_t dst, const void* src, uint32_t bytes, uint32_t bar) {
  asm volatile("{\n.reg .pred P;\nsetp.ne.u32 P, %4, 0;\n@P cp.async.bulk.shared::cluster.global.mbarrier::complete_tx::bytes [%0], [%1], %2, [%3];\n}" ::"r"(dst), "l"(src), "r"(bytes), "r"(bar), "r"(el) : "memory");
}
__device__ __forceinline__ uint64_t policy_evict_first() { uint64_t p; asm("createpolicy.fractional.L2::evict_first.b64 %0, 1.0;" : "=l"(p)); return p; }
__device__ __forceinline__ void bulk_load_h(uint32_t el, uint32_t dst, const void* src, uint32_t bytes, uint32_t bar, bool ef, uint64_t pol) {
  if (ef) {
    asm volatile("{\n.reg .pred P;\nsetp.ne.u32 P, %4, 0;\n@P cp.async.bulk.shared::cluster.global.mbarrier::complete_tx::bytes.L2::cache_hint [%0], [%1], %2, [%3], %5;\n}" ::"r"(dst), "l"(src), "r"(bytes), "r"(bar), "r"(el), "l"(pol) : "memory");
  } else {
    asm volatile("{\n.reg .pred P;\nsetp.ne.u32 P, %4, 0;\n@P cp.async.bulk.shared::cluster.global.mbarrier::complete_tx::bytes [%0], [%1], %2, [%3];\n}" ::"r"(dst), "l"(src), "r"(bytes), "r"(bar), "r"(el) : "memory");
  }
}
__device__ __forceinline__ void bulk_mc_h(uint32_t el, uint32_t dst, const void* src, uint32_t bytes, uint32_t bar, bool ef, uint64_t pol) {
  if (ef) {
    asm volatile("{\n.reg .pred P;\nsetp.ne.u32 P, %4, 0;\n@P cp.async.bulk.shared::cluster.global.mbarrier::complete_tx::bytes.multicast::cluster.L2::cache_hint [%0], [%1], %2, [%3], %5, %6;\n}" ::"r"(dst), "l"(src), "r"(bytes), "r"(bar), "r"(el), "h"((uint16_t)3), "l"(pol) : "memory");
  } else {
    asm volatile("{\n.reg .pred P;\nsetp.ne.u32 P, %4, 0;\n@P cp.async.bulk.shared::cluster.global.mbarrier::complete_tx::bytes.multicast::cluster [%0], [%1], %2, [%3], %5;\n}" ::"r"(dst), "l"(src), "r"(bytes), "r"(bar), "r"(el), "h"((uint16_t)3) : "memory");
  }
}
__device__ __forceinline__ void tma3d_h(uint32_t el, uint32_t dst, const CUtensorMap* m, int c0, int c1, int c2, uint32_t bar, bool ef, uint64_t pol) {
  if (ef) {
    asm volatile("{\n.reg .pred P;\nsetp.ne.u32 P, %6, 0;\n@P cp.async.bulk.tensor.3d.shared::cluster.global.mbarrier::complete_tx::bytes.L2::cache_hint [%0], [%1, {%3, %4, %5}], [%2], %7;\n}" ::"r"(dst), "l"(m), "r"(bar), "r"(c0), "r"(c1), "r"(c2), "r"(el), "l"(pol) : "memory");
  } else {
    asm volatile("{\n.reg .pred P;\nsetp.ne.u32 P, %6, 0;\n@P cp.async.bulk.tensor.3d.shared::cluster.global.mbarrier::complete_tx::bytes [%0], [%1, {%3, %4, %5}], [%2];\n}" ::"r"(dst), "l"(m), "r"(bar), "r"(c0), "r"(c1), "r"(c2), "r"(el) : "memory");
  }
}
__device__ __forceinline__ void tma2d_mc_h(uint32_t el, uint32_t dst, const CUtensorMap* m, int c0, int c1, uint32_t bar, bool ef, uint64_t pol) {
  if (ef) {
    asm volatile("{\n.reg .pred P;\nsetp.ne.u32 P, %5, 0;\n@P cp.async.bulk.tensor.2d.shared::cluster.global.mbarrier::complete_tx::bytes.multicast::cluster.L2::cache_hint [%0], [%1, {%3, %4}], [%2], %6, %7;\n}" ::"r"(dst), "l"(m), "r"(bar), "r"(c0), "r"(c1), "r"(el), "h"((uint16_t)3), "l"(pol) : "memory");
  } else {
    asm volatile("{\n.reg .pred P;\nsetp.ne.u32 P, %5, 0;\n@P cp.async.bulk.tensor.2d.shared::cluster.global.mbarrier::complete_tx::bytes.multicast::cluster [%0], [%1, {%3, %4}], [%2], %6;\n}" ::"r"(dst), "l"(m), "r"(bar), "r"(c0), "r"(c1), "r"(el), "h"((uint16_t)3) : "memory");
  }
}
__device__ __forceinline__ void tma3d_mc_h(uint32_t el, uint32_t dst, const CUtensorMap* m, int c0, int c1, int c2, uint32_t bar, bool ef, uint64_t pol) {
  if (ef) {
    asm volatile("{\n.reg .pred P;\nsetp.ne.u32 P, %6, 0;\n@P cp.async.bulk.tensor.3d.shared::cluster.global.mbarrier::complete_tx::bytes.multicast::cluster.L2::cache_hint [%0], [%1, {%3, %4, %5}], [%2], %7, %8;\n}" ::"r"(dst), "l"(m), "r"(bar), "r"(c0), "r"(c1), "r"(c2), "r"(el), "h"((uint16_t)3), "l"(pol) : "memory");
  } else {
    asm volatile("{\n.reg .pred P;\nsetp.ne.u32 P, %6, 0;\n@P cp.async.bulk.tensor.3d.shared::cluster.global.mbarrier::complete_tx::bytes.multicast::cluster [%0], [%1, {%3, %4, %5}], [%2], %7;\n}" ::"r"(dst), "l"(m), "r"(bar), "r"(c0), "r"(c1), "r"(c2), "r"(el), "h"((uint16_t)3) : "memory");
  }
}
__device__ __forceinline__ void mbar_arrive_cluster(uint32_t addr) { asm volatile("mbarrier.arrive.shared::cluster.b64 _, [%0];" ::"r"(addr) : "memory"); }
__device__ __forceinline__ uint32_t mapa(uint32_t addr, uint32_t rank) { uint32_t r; asm("mapa.shared::cluster.u32 %0, %1, %2;" : "=r"(r) : "r"(addr), "r"(rank)); return r; }
__device__ __forceinline__ void bulk_store_p(uint32_t el, void* dst, uint32_t src, uint32_t bytes) {
  asm volatile("{\n.reg .pred P;\nsetp.ne.u32 P, %3, 0;\n@P cp.async.bulk.global.shared::cta.bulk_group [%0], [%1], %2;\n}" ::"l"(dst), "r"(src), "r"(bytes), "r"(el) : "memory");
}
__device__ __forceinline__ void flag_release_p(uint32_t el, uint32_t* f) {
  asm volatile("{\n.reg .pred P;\nsetp.ne.u32 P, %1, 0;\nfence.proxy.async;\n@P red.relaxed.gpu.global.add.u32 [%0], 1;\n}" ::"l"(f), "r"(el) : "memory");
}
__device__ __forceinline__ void flag_add_p(uint32_t el, uint32_t* f) {
  asm volatile("{\n.reg .pred P;\nsetp.ne.u32 P, %1, 0;\n@P red.relaxed.gpu.global.add.u32 [%0], 1;\n}" ::"l"(f), "r"(el) : "memory");
}
__device__ __forceinline__ void prefetch_l2(const void* src, uint32_t bytes) { asm volatile("cp.async.bulk.prefetch.L2.global [%0], %1;" ::"l"(src), "r"(bytes) : "memory"); }
__device__ __forceinline__ void prefetch_map(const CUtensorMap* m) { asm volatile("prefetch.tensormap [%0];" ::"l"(m) : "memory"); }
__device__ __forceinline__ void wgmma_fence() { asm volatile("wgmma.fence.sync.aligned;" ::: "memory"); }
__device__ __forceinline__ void wgmma_commit() { asm volatile("wgmma.commit_group.sync.aligned;" ::: "memory"); }
template <int N> __device__ __forceinline__ void wgmma_wait() { asm volatile("wgmma.wait_group.sync.aligned %0;" ::"n"(N) : "memory"); }
__device__ __forceinline__ uint32_t dlo(uint32_t addr, uint32_t lbo) { return ((addr & 0x3FFFF) >> 4) + ((lbo >> 4) << 16); }
template <uint32_t SBO, uint32_t SWZ> __device__ __forceinline__ uint64_t dsc(uint32_t lo, uint32_t off) {
  uint64_t d; asm("mov.b64 %0, {%1, %2};" : "=l"(d) : "r"(lo + (off >> 4)), "n"((SBO >> 4) | (SWZ << 30))); return d;
}
template <int R> __device__ __forceinline__ void reg_alloc() { asm volatile("setmaxnreg.inc.sync.aligned.u32 %0;" ::"n"(R)); }
template <int R> __device__ __forceinline__ void reg_dealloc() { asm volatile("setmaxnreg.dec.sync.aligned.u32 %0;" ::"n"(R)); }
__device__ __forceinline__ void bar_sync(int id, int n) { asm volatile("bar.sync %0, %1;" ::"r"(id), "r"(n) : "memory"); }
__device__ __forceinline__ void bar_arrive(int id, int n) { asm volatile("bar.arrive %0, %1;" ::"r"(id), "r"(n) : "memory"); }
__device__ __forceinline__ void ldsm4(uint32_t* r, uint32_t addr) {
  asm volatile("ldmatrix.sync.aligned.m8n8.x4.shared.b16 {%0,%1,%2,%3}, [%4];" : "=r"(r[0]), "=r"(r[1]), "=r"(r[2]), "=r"(r[3]) : "r"(addr) : "memory");
}
__device__ __forceinline__ uint32_t movm(uint32_t a) { uint32_t d; asm volatile("movmatrix.sync.aligned.m8n8.trans.b16 %0, %1;" : "=r"(d) : "r"(a)); return d; }
__device__ __forceinline__ void mma16(float* c, uint32_t a0, uint32_t a1, uint32_t a2, uint32_t a3, uint32_t b0, uint32_t b1) {
  asm volatile("mma.sync.aligned.m16n8k16.row.col.f32.bf16.bf16.f32 {%0,%1,%2,%3}, {%4,%5,%6,%7}, {%8,%9}, {%0,%1,%2,%3};"
               : "+f"(c[0]), "+f"(c[1]), "+f"(c[2]), "+f"(c[3]) : "r"(a0), "r"(a1), "r"(a2), "r"(a3), "r"(b0), "r"(b1));
}
__device__ __forceinline__ void mma8(float* c, uint32_t a0, uint32_t a1, uint32_t b0) {
  asm volatile("mma.sync.aligned.m16n8k8.row.col.f32.bf16.bf16.f32 {%0,%1,%2,%3}, {%4,%5}, {%6}, {%0,%1,%2,%3};"
               : "+f"(c[0]), "+f"(c[1]), "+f"(c[2]), "+f"(c[3]) : "r"(a0), "r"(a1), "r"(b0));
}
__device__ __forceinline__ uint32_t pack2(float lo, float hi) { uint32_t r; asm("cvt.rn.bf16x2.f32 %0, %1, %2;" : "=r"(r) : "f"(hi), "f"(lo)); return r; }
__device__ __forceinline__ float blo(uint32_t v) { return __uint_as_float(v << 16); }
__device__ __forceinline__ float bhi(uint32_t v) { return __uint_as_float(v & 0xffff0000u); }
__device__ __forceinline__ float tanh_fast(float x) { float y; asm("tanh.approx.f32 %0, %1;" : "=f"(y) : "f"(x)); return y; }
__device__ __forceinline__ float rcp_fast(float x) { float y; asm("rcp.approx.ftz.f32 %0, %1;" : "=f"(y) : "f"(x)); return y; }
__device__ __forceinline__ float ex2(float x) { float y; asm("ex2.approx.ftz.f32 %0, %1;" : "=f"(y) : "f"(x)); return y; }
__device__ __forceinline__ float qsum(float v) { v += __shfl_xor_sync(~0u, v, 1); v += __shfl_xor_sync(~0u, v, 2); return v; }
__device__ __forceinline__ float qmax(float v) { v = fmaxf(v, __shfl_xor_sync(~0u, v, 1)); v = fmaxf(v, __shfl_xor_sync(~0u, v, 2)); return v; }
__device__ __forceinline__ void stg32(void* p, uint32_t v) { asm volatile("st.global.u32 [%0], %1;" ::"l"(p), "r"(v) : "memory"); }
__device__ __forceinline__ void stg128(void* p, uint32_t a, uint32_t b, uint32_t c, uint32_t d) { asm volatile("st.global.v4.u32 [%0], {%1,%2,%3,%4};" ::"l"(p), "r"(a), "r"(b), "r"(c), "r"(d) : "memory"); }
__device__ __forceinline__ uint32_t ldcg32(const void* p) { uint32_t v; asm volatile("ld.global.L1::no_allocate.u32 %0, [%1];" : "=r"(v) : "l"(p) : "memory"); return v; }
__device__ __forceinline__ void stg128_if(bool c, void* p, uint32_t a, uint32_t b, uint32_t cc, uint32_t d) {
  asm volatile("{\n.reg .pred P;\nsetp.ne.u32 P, %5, 0;\n@P st.global.v4.u32 [%0], {%1,%2,%3,%4};\n}" ::"l"(p), "r"(a), "r"(b), "r"(cc), "r"(d), "r"((uint32_t)c) : "memory");
}
__device__ __forceinline__ uint2 lds64(uint32_t a) { uint2 v; asm volatile("ld.shared.v2.u32 {%0,%1}, [%2];" : "=r"(v.x), "=r"(v.y) : "r"(a) : "memory"); return v; }
__device__ __forceinline__ uint4 ldcg128(const void* p) { uint4 v; asm volatile("ld.global.cg.v4.u32 {%0,%1,%2,%3}, [%4];" : "=r"(v.x), "=r"(v.y), "=r"(v.z), "=r"(v.w) : "l"(p) : "memory"); return v; }
__device__ __forceinline__ uint32_t ldnc16(const void* p) { uint16_t v; asm volatile("ld.global.nc.u16 %0, [%1];" : "=h"(v) : "l"(p)); return v; }
__device__ __forceinline__ uint4 ldnc128(const void* p) { uint4 v; asm volatile("ld.global.nc.v4.u32 {%0,%1,%2,%3}, [%4];" : "=r"(v.x), "=r"(v.y), "=r"(v.z), "=r"(v.w) : "l"(p)); return v; }
__device__ __forceinline__ void cp_async16(uint32_t dst, const void* src) { asm volatile("cp.async.cg.shared.global [%0], [%1], 16;" ::"r"(dst), "l"(src) : "memory"); }
__device__ __forceinline__ uint32_t hsub2(uint32_t a, uint32_t b) { uint32_t d; asm("sub.rn.bf16x2 %0, %1, %2;" : "=r"(d) : "r"(a), "r"(b)); return d; }
__device__ __forceinline__ void stg32_if(bool c, void* p, uint32_t v) {
  asm volatile("{\n.reg .pred P;\nsetp.ne.u32 P, %2, 0;\n@P st.global.u32 [%0], %1;\n}" ::"l"(p), "r"(v), "r"((uint32_t)c) : "memory");
}
__device__ __forceinline__ float wsum(float v) { for (int o = 16; o; o >>= 1) v += __shfl_xor_sync(~0u, v, o); return v; }
__device__ __forceinline__ uint32_t hmul2(uint32_t a, uint32_t b) { uint32_t d; asm("mul.rn.bf16x2 %0, %1, %2;" : "=r"(d) : "r"(a), "r"(b)); return d; }
__device__ __forceinline__ void sts32(uint32_t a, uint32_t v) { asm volatile("st.shared.u32 [%0], %1;" ::"r"(a), "r"(v) : "memory"); }
__device__ __forceinline__ uint32_t lds32(uint32_t a) { uint32_t v; asm volatile("ld.shared.u32 %0, [%1];" : "=r"(v) : "r"(a) : "memory"); return v; }
__device__ __forceinline__ void sts128(uint32_t a, uint32_t x, uint32_t y, uint32_t z, uint32_t w) { asm volatile("st.shared.v4.u32 [%0], {%1,%2,%3,%4};" ::"r"(a), "r"(x), "r"(y), "r"(z), "r"(w) : "memory"); }
__device__ __forceinline__ uint4 lds128(uint32_t a) { uint4 v; asm volatile("ld.shared.v4.u32 {%0,%1,%2,%3}, [%4];" : "=r"(v.x), "=r"(v.y), "=r"(v.z), "=r"(v.w) : "r"(a) : "memory"); return v; }
__device__ __forceinline__ void ll_st64(uint2* p, uint32_t v, uint32_t tag) {
  asm volatile("{\n.reg .b64 r;\nmov.b64 r, {%1,%2};\nst.relaxed.gpu.global.b64 [%0], r;\n}" ::"l"(p), "r"(v), "r"(tag) : "memory");
}
__device__ __forceinline__ uint2 ll_ld64(const uint2* p) {
  uint2 v; asm volatile("{\n.reg .b64 r;\nld.relaxed.gpu.global.b64 r, [%2];\nmov.b64 {%0,%1}, r;\n}" : "=r"(v.x), "=r"(v.y) : "l"(p) : "memory"); return v;
}
__device__ __forceinline__ void ll_st128(uint4* p, float a, float b, uint32_t tag, float c = 0.f) {
  asm volatile("{\n.reg .b128 r;\n.reg .b64 lo, hi;\nmov.b64 lo, {%1,%2};\nmov.b64 hi, {%3,%4};\nmov.b128 r, {lo, hi};\nst.relaxed.gpu.global.b128 [%0], r;\n}" ::"l"(p), "r"(__float_as_uint(a)), "r"(__float_as_uint(b)), "r"(tag), "r"(__float_as_uint(c)) : "memory");
}
__device__ __forceinline__ uint4 ll_ld128g(const void* p) {
  uint4 v; asm volatile("{\n.reg .b128 r;\n.reg .b64 lo, hi;\nld.relaxed.gpu.b128 r, [%4];\nmov.b128 {lo, hi}, r;\nmov.b64 {%0,%1}, lo;\nmov.b64 {%2,%3}, hi;\n}" : "=r"(v.x), "=r"(v.y), "=r"(v.z), "=r"(v.w) : "l"(p) : "memory"); return v;
}
__device__ __forceinline__ uint4 ll_ld128(const uint4* p) {
  uint4 v; asm volatile("{\n.reg .b128 r;\n.reg .b64 lo, hi;\nld.relaxed.gpu.global.b128 r, [%4];\nmov.b128 {lo, hi}, r;\nmov.b64 {%0,%1}, lo;\nmov.b64 {%2,%3}, hi;\n}" : "=r"(v.x), "=r"(v.y), "=r"(v.z), "=r"(v.w) : "l"(p) : "memory"); return v;
}
__device__ __forceinline__ void publish_p(uint32_t el, uint32_t* f) {
  asm volatile("{\n.reg .pred P;\nsetp.ne.u32 P, %1, 0;\n@P cp.async.bulk.commit_group;\n@P cp.async.bulk.wait_group 0;\n@P red.release.gpu.global.add.u32 [%0], 1;\n}" ::"l"(f), "r"(el) : "memory");
}
__device__ __forceinline__ void tma3d_red_p(uint32_t el, const CUtensorMap* m, int c0, int c1, int c2, uint32_t src) {
  asm volatile("{\n.reg .pred P;\nsetp.ne.u32 P, %5, 0;\n@P cp.reduce.async.bulk.tensor.3d.global.shared::cta.add.tile.bulk_group [%0, {%2, %3, %4}], [%1];\n@P cp.async.bulk.commit_group;\n}" ::"l"(m), "r"(src), "r"(c0), "r"(c1), "r"(c2), "r"(el) : "memory");
}
__device__ __forceinline__ void stsm4(uint32_t addr, uint32_t a, uint32_t b, uint32_t c, uint32_t d) {
  asm volatile("stmatrix.sync.aligned.m8n8.x4.shared.b16 [%0], {%1,%2,%3,%4};" ::"r"(addr), "r"(a), "r"(b), "r"(c), "r"(d) : "memory");
}
__device__ __forceinline__ void sts64(uint32_t a, uint32_t x, uint32_t y) { asm volatile("st.shared.v2.u32 [%0], {%1,%2};" ::"r"(a), "r"(x), "r"(y) : "memory"); }
__device__ __forceinline__ void ll_st128_if(bool on, uint4* p, float a, float b, uint32_t tag) {
  asm volatile("{\n.reg .pred P;\n.reg .b128 r;\n.reg .b64 lo, hi;\nsetp.ne.u32 P, %4, 0;\nmov.b64 lo, {%1,%2};\nmov.b64 hi, {%3,%3};\nmov.b128 r, {lo, hi};\n@P st.relaxed.gpu.global.b128 [%0], r;\n}" ::"l"(p), "r"(__float_as_uint(a)), "r"(__float_as_uint(b)), "r"(tag), "r"((uint32_t)on) : "memory");
}
__device__ __forceinline__ uint4 ldnc128_if(bool c, const void* p) {
  uint4 v = make_uint4(0u, 0u, 0u, 0u);
  asm volatile("{\n.reg .pred P;\nsetp.ne.u32 P, %5, 0;\n@P ld.global.nc.v4.u32 {%0,%1,%2,%3}, [%4];\n}" : "+r"(v.x), "+r"(v.y), "+r"(v.z), "+r"(v.w) : "l"(p), "r"((uint32_t)c));
  return v;
}
__device__ __forceinline__ uint32_t hfma2(uint32_t a, uint32_t b, uint32_t c) { uint32_t d; asm("fma.rn.bf16x2 %0, %1, %2, %3;" : "=r"(d) : "r"(a), "r"(b), "r"(c)); return d; }
__device__ __forceinline__ float2 lds64f(uint32_t a) { float2 v; asm volatile("ld.shared.v2.f32 {%0,%1}, [%2];" : "=f"(v.x), "=f"(v.y) : "r"(a) : "memory"); return v; }
#define TRC(cond, role, idx) do {} while (0)
#define TRV(role, idx, v) do {} while (0)
#define TRVI(c, role, idx, v) do {} while (0)

#define ACLK_INIT do {} while (0)
#define ACLK(i) do {} while (0)
#define ACLK_OUT do {} while (0)
#define QCLK(i) do {} while (0)
#define PH 1
#define RCLK(i) do {} while (0)
#define RCLK_INIT do {} while (0)
#define RCLK_OUT do {} while (0)
#define SCLK(i) do {} while (0)
#define PL 1
#define PCLK(i) do {} while (0)
#define PQ 1
#define CLK_INIT do {} while (0)
#define CLK(i) do {} while (0)
#define CLK_OUT do {} while (0)

__device__ __forceinline__ void wgmma_ss_n216(float* d, uint64_t da, uint64_t db, int scaleD) {
  asm volatile("{\n.reg .pred p;\nsetp.ne.b32 p, %110, 0;\nwgmma.mma_async.sync.aligned.m64n216k16.f32.bf16.bf16 "
    "{%0,%1,%2,%3,%4,%5,%6,%7,%8,%9,%10,%11,%12,%13,%14,%15,%16,%17,%18,%19,%20,%21,%22,%23,%24,%25,%26,%27,%28,%29,%30,%31,%32,%33,%34,%35,%36,%37,%38,%39,%40,%41,%42,%43,%44,%45,%46,%47,%48,%49,%50,%51,%52,%53,%54,%55,%56,%57,%58,%59,%60,%61,%62,%63,%64,%65,%66,%67,%68,%69,%70,%71,%72,%73,%74,%75,%76,%77,%78,%79,%80,%81,%82,%83,%84,%85,%86,%87,%88,%89,%90,%91,%92,%93,%94,%95,%96,%97,%98,%99,%100,%101,%102,%103,%104,%105,%106,%107}, "
    "%108, %109, p, 1, 1, 0, 1;\n}\n"
    : "+f"(d[0]), "+f"(d[1]), "+f"(d[2]), "+f"(d[3]), "+f"(d[4]), "+f"(d[5]), "+f"(d[6]), "+f"(d[7]), "+f"(d[8]), "+f"(d[9]), "+f"(d[10]), "+f"(d[11]), "+f"(d[12]), "+f"(d[13]), "+f"(d[14]), "+f"(d[15]), "+f"(d[16]), "+f"(d[17]), "+f"(d[18]), "+f"(d[19]), "+f"(d[20]), "+f"(d[21]), "+f"(d[22]), "+f"(d[23]), "+f"(d[24]), "+f"(d[25]), "+f"(d[26]), "+f"(d[27]), "+f"(d[28]), "+f"(d[29]), "+f"(d[30]), "+f"(d[31]), "+f"(d[32]), "+f"(d[33]), "+f"(d[34]), "+f"(d[35]), "+f"(d[36]), "+f"(d[37]), "+f"(d[38]), "+f"(d[39]), "+f"(d[40]), "+f"(d[41]), "+f"(d[42]), "+f"(d[43]), "+f"(d[44]), "+f"(d[45]), "+f"(d[46]), "+f"(d[47]), "+f"(d[48]), "+f"(d[49]), "+f"(d[50]), "+f"(d[51]), "+f"(d[52]), "+f"(d[53]), "+f"(d[54]), "+f"(d[55]), "+f"(d[56]), "+f"(d[57]), "+f"(d[58]), "+f"(d[59]), "+f"(d[60]), "+f"(d[61]), "+f"(d[62]), "+f"(d[63]), "+f"(d[64]), "+f"(d[65]), "+f"(d[66]), "+f"(d[67]), "+f"(d[68]), "+f"(d[69]), "+f"(d[70]), "+f"(d[71]), "+f"(d[72]), "+f"(d[73]), "+f"(d[74]), "+f"(d[75]), "+f"(d[76]), "+f"(d[77]), "+f"(d[78]), "+f"(d[79]), "+f"(d[80]), "+f"(d[81]), "+f"(d[82]), "+f"(d[83]), "+f"(d[84]), "+f"(d[85]), "+f"(d[86]), "+f"(d[87]), "+f"(d[88]), "+f"(d[89]), "+f"(d[90]), "+f"(d[91]), "+f"(d[92]), "+f"(d[93]), "+f"(d[94]), "+f"(d[95]), "+f"(d[96]), "+f"(d[97]), "+f"(d[98]), "+f"(d[99]), "+f"(d[100]), "+f"(d[101]), "+f"(d[102]), "+f"(d[103]), "+f"(d[104]), "+f"(d[105]), "+f"(d[106]), "+f"(d[107])
    : "l"(da), "l"(db), "r"(scaleD));
}
__device__ __forceinline__ void wgmma_ss_n72(float* d, uint64_t da, uint64_t db, int scaleD) {
  asm volatile("{\n.reg .pred p;\nsetp.ne.b32 p, %38, 0;\nwgmma.mma_async.sync.aligned.m64n72k16.f32.bf16.bf16 "
    "{%0,%1,%2,%3,%4,%5,%6,%7,%8,%9,%10,%11,%12,%13,%14,%15,%16,%17,%18,%19,%20,%21,%22,%23,%24,%25,%26,%27,%28,%29,%30,%31,%32,%33,%34,%35}, "
    "%36, %37, p, 1, 1, 0, 1;\n}\n"
    : "+f"(d[0]), "+f"(d[1]), "+f"(d[2]), "+f"(d[3]), "+f"(d[4]), "+f"(d[5]), "+f"(d[6]), "+f"(d[7]), "+f"(d[8]), "+f"(d[9]), "+f"(d[10]), "+f"(d[11]), "+f"(d[12]), "+f"(d[13]), "+f"(d[14]), "+f"(d[15]), "+f"(d[16]), "+f"(d[17]), "+f"(d[18]), "+f"(d[19]), "+f"(d[20]), "+f"(d[21]), "+f"(d[22]), "+f"(d[23]), "+f"(d[24]), "+f"(d[25]), "+f"(d[26]), "+f"(d[27]), "+f"(d[28]), "+f"(d[29]), "+f"(d[30]), "+f"(d[31]), "+f"(d[32]), "+f"(d[33]), "+f"(d[34]), "+f"(d[35])
    : "l"(da), "l"(db), "r"(scaleD));
}
__device__ __forceinline__ void wgmma_ss_n128(float* d, uint64_t da, uint64_t db, int scaleD) {
  asm volatile("{\n.reg .pred p;\nsetp.ne.b32 p, %66, 0;\nwgmma.mma_async.sync.aligned.m64n128k16.f32.bf16.bf16 "
    "{%0,%1,%2,%3,%4,%5,%6,%7,%8,%9,%10,%11,%12,%13,%14,%15,%16,%17,%18,%19,%20,%21,%22,%23,%24,%25,%26,%27,%28,%29,%30,%31,%32,%33,%34,%35,%36,%37,%38,%39,%40,%41,%42,%43,%44,%45,%46,%47,%48,%49,%50,%51,%52,%53,%54,%55,%56,%57,%58,%59,%60,%61,%62,%63}, "
    "%64, %65, p, 1, 1, 0, 1;\n}\n"
    : "+f"(d[0]), "+f"(d[1]), "+f"(d[2]), "+f"(d[3]), "+f"(d[4]), "+f"(d[5]), "+f"(d[6]), "+f"(d[7]), "+f"(d[8]), "+f"(d[9]), "+f"(d[10]), "+f"(d[11]), "+f"(d[12]), "+f"(d[13]), "+f"(d[14]), "+f"(d[15]), "+f"(d[16]), "+f"(d[17]), "+f"(d[18]), "+f"(d[19]), "+f"(d[20]), "+f"(d[21]), "+f"(d[22]), "+f"(d[23]), "+f"(d[24]), "+f"(d[25]), "+f"(d[26]), "+f"(d[27]), "+f"(d[28]), "+f"(d[29]), "+f"(d[30]), "+f"(d[31]), "+f"(d[32]), "+f"(d[33]), "+f"(d[34]), "+f"(d[35]), "+f"(d[36]), "+f"(d[37]), "+f"(d[38]), "+f"(d[39]), "+f"(d[40]), "+f"(d[41]), "+f"(d[42]), "+f"(d[43]), "+f"(d[44]), "+f"(d[45]), "+f"(d[46]), "+f"(d[47]), "+f"(d[48]), "+f"(d[49]), "+f"(d[50]), "+f"(d[51]), "+f"(d[52]), "+f"(d[53]), "+f"(d[54]), "+f"(d[55]), "+f"(d[56]), "+f"(d[57]), "+f"(d[58]), "+f"(d[59]), "+f"(d[60]), "+f"(d[61]), "+f"(d[62]), "+f"(d[63])
    : "l"(da), "l"(db), "r"(scaleD));
}
__device__ __forceinline__ void wgmma_ss_n160(float* d, uint64_t da, uint64_t db, int scaleD) {
  asm volatile("{\n.reg .pred p;\nsetp.ne.b32 p, %82, 0;\nwgmma.mma_async.sync.aligned.m64n160k16.f32.bf16.bf16 "
    "{%0,%1,%2,%3,%4,%5,%6,%7,%8,%9,%10,%11,%12,%13,%14,%15,%16,%17,%18,%19,%20,%21,%22,%23,%24,%25,%26,%27,%28,%29,%30,%31,%32,%33,%34,%35,%36,%37,%38,%39,%40,%41,%42,%43,%44,%45,%46,%47,%48,%49,%50,%51,%52,%53,%54,%55,%56,%57,%58,%59,%60,%61,%62,%63,%64,%65,%66,%67,%68,%69,%70,%71,%72,%73,%74,%75,%76,%77,%78,%79}, "
    "%80, %81, p, 1, 1, 0, 1;\n}\n"
    : "+f"(d[0]), "+f"(d[1]), "+f"(d[2]), "+f"(d[3]), "+f"(d[4]), "+f"(d[5]), "+f"(d[6]), "+f"(d[7]), "+f"(d[8]), "+f"(d[9]), "+f"(d[10]), "+f"(d[11]), "+f"(d[12]), "+f"(d[13]), "+f"(d[14]), "+f"(d[15]), "+f"(d[16]), "+f"(d[17]), "+f"(d[18]), "+f"(d[19]), "+f"(d[20]), "+f"(d[21]), "+f"(d[22]), "+f"(d[23]), "+f"(d[24]), "+f"(d[25]), "+f"(d[26]), "+f"(d[27]), "+f"(d[28]), "+f"(d[29]), "+f"(d[30]), "+f"(d[31]), "+f"(d[32]), "+f"(d[33]), "+f"(d[34]), "+f"(d[35]), "+f"(d[36]), "+f"(d[37]), "+f"(d[38]), "+f"(d[39]), "+f"(d[40]), "+f"(d[41]), "+f"(d[42]), "+f"(d[43]), "+f"(d[44]), "+f"(d[45]), "+f"(d[46]), "+f"(d[47]), "+f"(d[48]), "+f"(d[49]), "+f"(d[50]), "+f"(d[51]), "+f"(d[52]), "+f"(d[53]), "+f"(d[54]), "+f"(d[55]), "+f"(d[56]), "+f"(d[57]), "+f"(d[58]), "+f"(d[59]), "+f"(d[60]), "+f"(d[61]), "+f"(d[62]), "+f"(d[63]), "+f"(d[64]), "+f"(d[65]), "+f"(d[66]), "+f"(d[67]), "+f"(d[68]), "+f"(d[69]), "+f"(d[70]), "+f"(d[71]), "+f"(d[72]), "+f"(d[73]), "+f"(d[74]), "+f"(d[75]), "+f"(d[76]), "+f"(d[77]), "+f"(d[78]), "+f"(d[79])
    : "l"(da), "l"(db), "r"(scaleD));
}
__device__ __forceinline__ void wgmma_rs_n144(float* d, const uint32_t* a, uint64_t db, int scaleD) {
  asm volatile("{\n.reg .pred p;\nsetp.ne.b32 p, %77, 0;\nwgmma.mma_async.sync.aligned.m64n144k16.f32.bf16.bf16 "
    "{%0,%1,%2,%3,%4,%5,%6,%7,%8,%9,%10,%11,%12,%13,%14,%15,%16,%17,%18,%19,%20,%21,%22,%23,%24,%25,%26,%27,%28,%29,%30,%31,%32,%33,%34,%35,%36,%37,%38,%39,%40,%41,%42,%43,%44,%45,%46,%47,%48,%49,%50,%51,%52,%53,%54,%55,%56,%57,%58,%59,%60,%61,%62,%63,%64,%65,%66,%67,%68,%69,%70,%71}, "
    "{%72,%73,%74,%75}, %76, p, 1, 1, 1;\n}\n"
    : "+f"(d[0]), "+f"(d[1]), "+f"(d[2]), "+f"(d[3]), "+f"(d[4]), "+f"(d[5]), "+f"(d[6]), "+f"(d[7]), "+f"(d[8]), "+f"(d[9]), "+f"(d[10]), "+f"(d[11]), "+f"(d[12]), "+f"(d[13]), "+f"(d[14]), "+f"(d[15]), "+f"(d[16]), "+f"(d[17]), "+f"(d[18]), "+f"(d[19]), "+f"(d[20]), "+f"(d[21]), "+f"(d[22]), "+f"(d[23]), "+f"(d[24]), "+f"(d[25]), "+f"(d[26]), "+f"(d[27]), "+f"(d[28]), "+f"(d[29]), "+f"(d[30]), "+f"(d[31]), "+f"(d[32]), "+f"(d[33]), "+f"(d[34]), "+f"(d[35]), "+f"(d[36]), "+f"(d[37]), "+f"(d[38]), "+f"(d[39]), "+f"(d[40]), "+f"(d[41]), "+f"(d[42]), "+f"(d[43]), "+f"(d[44]), "+f"(d[45]), "+f"(d[46]), "+f"(d[47]), "+f"(d[48]), "+f"(d[49]), "+f"(d[50]), "+f"(d[51]), "+f"(d[52]), "+f"(d[53]), "+f"(d[54]), "+f"(d[55]), "+f"(d[56]), "+f"(d[57]), "+f"(d[58]), "+f"(d[59]), "+f"(d[60]), "+f"(d[61]), "+f"(d[62]), "+f"(d[63]), "+f"(d[64]), "+f"(d[65]), "+f"(d[66]), "+f"(d[67]), "+f"(d[68]), "+f"(d[69]), "+f"(d[70]), "+f"(d[71])
    : "r"(a[0]), "r"(a[1]), "r"(a[2]), "r"(a[3]), "l"(db), "r"(scaleD));
}
__device__ __forceinline__ void wgmma_rs_n64(float* d, const uint32_t* a, uint64_t db, int scaleD) {
  asm volatile("{\n.reg .pred p;\nsetp.ne.b32 p, %37, 0;\nwgmma.mma_async.sync.aligned.m64n64k16.f32.bf16.bf16 "
    "{%0,%1,%2,%3,%4,%5,%6,%7,%8,%9,%10,%11,%12,%13,%14,%15,%16,%17,%18,%19,%20,%21,%22,%23,%24,%25,%26,%27,%28,%29,%30,%31}, "
    "{%32,%33,%34,%35}, %36, p, 1, 1, 1;\n}\n"
    : "+f"(d[0]), "+f"(d[1]), "+f"(d[2]), "+f"(d[3]), "+f"(d[4]), "+f"(d[5]), "+f"(d[6]), "+f"(d[7]), "+f"(d[8]), "+f"(d[9]), "+f"(d[10]), "+f"(d[11]), "+f"(d[12]), "+f"(d[13]), "+f"(d[14]), "+f"(d[15]), "+f"(d[16]), "+f"(d[17]), "+f"(d[18]), "+f"(d[19]), "+f"(d[20]), "+f"(d[21]), "+f"(d[22]), "+f"(d[23]), "+f"(d[24]), "+f"(d[25]), "+f"(d[26]), "+f"(d[27]), "+f"(d[28]), "+f"(d[29]), "+f"(d[30]), "+f"(d[31])
    : "r"(a[0]), "r"(a[1]), "r"(a[2]), "r"(a[3]), "l"(db), "r"(scaleD));
}

template <int V> struct Int { static constexpr int value = V; };
struct Cur {
  uint32_t s, ph;
  __device__ __forceinline__ void next() { if (++s == NST) { s = 0; ph ^= 1; } }
};

__device__ __forceinline__ uint32_t o_place(uint32_t w, uint32_t e) { return (((w ? 0xd5310u : 0xa8d57u) >> (4 * e)) & 15) * 8192 + 90112; }
#define z1_block(rb, w, j) (Q.Z + ((rb) * 16 + (w) * 8 + (j)) * ZB)
#define xn_block(hw) (Q.Z + (512 + (hw) * 2) * ZB)
#define z2_block(kb, j) (Q.Z + (256 + (kb) * 8 + (j)) * ZB)
template <int N> __device__ __forceinline__ uint32_t spin(uint32_t z) {
#pragma unroll (N > 8 ? 1 : 8)
  for (int i = 0; i < N; i++) asm volatile("shfl.sync.bfly.b32 %0, %0, 1, 0x1f, 0xffffffff;" : "+r"(z)::"memory");
  return z;
}

__global__ void __cluster_dims__(2, 1, 1) __launch_bounds__(384, 1) mega_kernel(const Ptrs Q, const __grid_constant__ Params P) {
  extern __shared__ __align__(1024) uint8_t smem_raw[];
  const uint32_t sb = smem_u32(smem_raw);
  const uint32_t bars = sb + SM_BAR;
  const int tid = threadIdx.x;
  int lane = tid & 31;
  const int wid = __shfl_sync(~0u, tid >> 5, 0);
  const int cl = blockIdx.x >> 1;
  const int bid = (cl < 4 ? cl * 8 + 32 : cl - 4 + (max(cl - 29, 0) * 37 >> 8)) * 2 + (blockIdx.x & 1);
  const int rb = bid & 15, j = bid >> 4;
  uint4 wv[5];
  {
    const int n8 = min(tid >> 3, 26), part = n8 / 9;
    const uint8_t* src = (const uint8_t*)Q.wqkv + (8 * rb + (tid & 7)) * (3 * DM * 2) + (part * (DM - 72) + 72 * j + 8 * n8) * 2;
#pragma unroll
    for (int u = 0; u < 5; u++) wv[u] = ldnc128_if(tid < 216 && cl < 64 && (u < 4 || rb < 8), src + u * (128 * 3 * DM * 2));
  }
  if (cl >= 64) return;
  if (wid >= 7 && lane == 0) {
    if (wid < 10) {
#pragma unroll
      for (uint32_t b = 0; b < B_AD / 3; b += 8) mbar_init(bars + (wid - 7) * (B_AD / 3) + b, 1);
    } else if (wid == 10) {
#pragma unroll
      for (uint32_t b = B_AD; b < B_EVT; b += 8) mbar_init(bars + b, b < B_CSQ ? 2 : b < B_LAG ? 3 : 4);
    } else {
#pragma unroll
      for (uint32_t b = B_EVT; b < 1024; b += 8) if (b < B_OFF || b >= B_IMG) mbar_init(bars + b, b < B_IMG ? 4 : b < B_EMPTY ? 8 : 16);
    }
    asm volatile("fence.mbarrier_init.release.cluster;" ::: "memory");
  }
  __syncthreads();

  if (wid >= 8) {
    reg_dealloc<40>();
    const uint32_t el = elect_one();
    const uint64_t pol = policy_evict_first();
    uint32_t* const fj = Q.flags + FJ + j * 32;
    if (wid == 8) {
      if (el) { prefetch_map(&P.wsp); prefetch_map(&P.winb[j & 1]); prefetch_map(&P.wins); prefetch_map(&P.wout); prefetch_map(&P.act[1]); prefetch_map(&P.res[0]); prefetch_map(&P.res[1]); prefetch_map(&P.row[1]); prefetch_map(&P.red); }
      const uint32_t epoch = ldcg32(fj + FJ_EP + rb);
      Cur c{0, 1};
      const uint32_t rk = bid & 1;
      uint32_t st, full;
      auto slot = [&](uint32_t bytes) {
        st = sb + c.s * ST_BYTES; full = bars + B_FULL + c.s * 8;
        mbar_wait(full, c.ph);
        expect_tx_p(el, full, bytes);
        mbar_wait(full - B_FULL + B_EMPTY, c.ph);
      };
#pragma unroll 1
      for (int L = 0; L < 2; L++) {
#pragma unroll 1
        for (int i = 0; i < 9; i++) {
          if (L == 0 && i == 0) {
            flag_wait(fj + FJ_WQ, (epoch + 1) * 16);
            fence_async_g();
            TRC(el, 2, 45);
          }
          slot(27648);
          bulk_mc_h(el, st + ST_B + rk * 13824, Q.WQ + j * WQ_SL + i * 27648 + rk * 13824, 13824, full, EF(0), pol);
          c.next();
        }
        if (L == 0) {
          flag_wait(fj + FJ_WO, (epoch + 1) * 16);
          fence_async_g();
          TRC(el, 2, 46);
        }
#pragma unroll 1
        while (c.s) {
          mbar_wait(bars + B_EMPTY + c.s * 8, c.ph);
          if (el) { mbar_arrive(bars + B_FULL + c.s * 8); asm volatile("mbarrier.arrive.shared::cta.b64 _, [%0], 16;" ::"r"(bars + B_EMPTY + c.s * 8) : "memory"); }
          c.next();
        }
        expect_tx_p(el, bars + B_WF, WO_SL);
        mbar_wait(bars + B_EMPTY, c.ph);
        mbar_wait(bars + B_EMPTY + 8, c.ph);
        bulk_mc_h(el, sb + rk * (WO_SL / 2), Q.WO + j * WO_SL + rk * (WO_SL / 2), WO_SL / 2, bars + B_WF, EF(1), pol);
#pragma unroll 1
        for (int r = 0; r < 10; r++) {
          const bool big = r >= 2 && r < 8;
          const int a0 = (r < 5 ? 36 : 0) + ((9 * j) >> 1) + (big ? 2 - 2 * (j & 1) : 3 * (j & 1) + rk), ks = big ? 32 : 48;
          int k = big ? (r < 5 ? r - 2 : r - 5) * 192 + rk * 16 : (r & 1) * 288;
          const CUtensorMap* m = big ? &P.winb[j & 1] : &P.wins;
          const uint32_t dst = sb + SM_B3 + rk * 6144;
#pragma unroll
          for (int p = 0; p < 6; p++, k += ks) {
            if ((p == 0 || p > 3) && r == 0) mbar_wait(bars + (p < 5 ? B_XD + p * 2 : B_S5), L);
            if (p) mbar_wait_c(bars + B_E3 + p * 8, ~r & 1); else mbar_wait(bars + B_E3, ~r & 1);
            expect_tx_p(el, bars + B_F3 + p * 8, 12288);
            tma3d_mc_h(el, dst + p * 12288, m, 0, k, a0, bars + B_F3 + p * 8, EF(2), pol);
          }
        }
        TRC(el, 2, L * 16 + 6);
        mbar_wait(bars + B_ZOK, L);
        fence_async_g();
        TRC(el, 2, L * 16 + 7);
        const uint8_t* src = z2_block(0, j) + rk * 18432;
#pragma unroll 1
        for (int r = 0; r < 8; r++) {
          const int k = (r & 3) * 512 + (r >> 2) * 64;
#pragma unroll
          for (int p = 0; p < 4; p++, src += 8 * ZB) {
            if ((p == 1 || p == 2) && r == 0) mbar_wait(bars + B_E3 - 8 + p * 24, 1);
            mbar_wait_c(bars + B_AD + p * 8, ~r & 1);
            if (p) mbar_wait_c(bars + B_EMPTY + p * 8, c.ph); else mbar_wait(bars + B_EMPTY, c.ph);
            expect_tx_p(el, bars + B_FULL + p * 8, ST_BYTES);
            bulk_mc_h(el, sb + p * ST_BYTES + ST_B + rk * 18432, src, 18432, bars + B_FULL + p * 8, EF(4), pol);
            tma3d_h(el, sb + p * ST_BYTES, &P.wsp, k + p * 128, rb * 64, 0, bars + B_FULL + p * 8, EF(3), pol);
          }
          c.ph ^= 1;
        }
        mbar_wait(bars + B_Z1, L);
        fence_async_g();
#pragma unroll 1
        for (int i = 0; i < 11; i++) {
          const int cb = i - 2 + j;
          if (i < 4) mbar_wait(bars + B_AD + c.s * 8, 1);
          slot(ZB);
          if (i < 2) bulk_load_h(el, st + ST_B, z1_block(rb, i, j), ZB, full, true, pol);
          else tma2d_mc_h(el, st + ST_B + rk * 18432, &P.wout, (cb >= 9 ? cb - 9 : cb) * 64, 288 * j + rk * 144, full, EF(5), pol);
          c.next();
        }
      }
    } else if (wid < 11) {
      uint32_t id = bid * 2 + wid - 9;
#define AGENT_IDS asm volatile("" : "+r"(lane), "+r"(id)); const uint32_t w = id & 1, hw = id & 31, rb = hw >> 1, j = id >> 5, ev = bars + B_EVT + w * EV_N * 8; \
      uint32_t* const fr = Q.flags + hw * 32; uint32_t* const fj = Q.flags + FJ + j * 32; (void)fr; (void)fj; (void)ev; (void)rb
      uint32_t t8 = 0;
      Cur c{0, 1};
#pragma unroll 1
      for (int L = 0; L < 2; L++) {
#pragma unroll 1
        for (int ph = 0; ph < 3; ph++) {
          if (ph + L > 0) {
            AGENT_IDS;
            uint32_t* f = fr + (ph == 0 ? FR_X2 : ph == 1 ? FR_O + L - (int)w * 32 : FR_X1 + L);
            mbar_wait_c(ev + ph * 8, L);
            TRC(el, 3, w * 32 + L * 16 + ph * 3);
            if (ph || XRLX) flag_add_p(el, f); else flag_release_p(el, f);
            TRC(el, 3, w * 32 + L * 16 + ph * 3 + 1);
            if (ph == 1) {
#pragma unroll 1
              for (int e = 0; e < 5; e++) {
                const uint32_t nb = e ? 16384 : 8192, full = bars + B_OF + w * 40 + e * 8, dst = sb + o_place(w, e);
                const uint8_t* src = z1_block(rb, w, 0) + (e ? e * 16384 - 8192 : 0);
                expect_tx_p(el, full, nb);
                if (e == 0) {
                  flag_wait(f + w * (FR_OL - FR_O), t8 * (2 - w));
                  if (w) fence_async_g();
                }
                if (w && (e == 0 || e == 3)) mbar_wait_c(bars + (e ? B_X3 : B_OF + YPACE * 8), L);
                bulk_load_h(el, dst, src, nb, full, EF(6), pol);
                TRC(el && e == 0, 3, w * 32 + L * 16 + ph * 3 + 2);
              }
              continue;
            }
            if (ph == 2) {
              const uint8_t* src = xn_block(hw);
              uint32_t full = bars + B_AF3 + w * 96, dst = sb + w * 6144;
              mbar_wait_c(bars + B_XD + 8, L);
#pragma unroll 1
              for (int k = 0; k < 12; k++, src += 6144, dst += 12288, full += 8) {
                expect_tx_p(el, full, 6144);
                if (k >= APACE) mbar_wait_c(full - APACE * 8, L);
                if (k == 0) flag_wait(f, t8);
                if (k == 11 && L == 1) flag_wait(fj + FJ_P4, t8 * 4);
                bulk_load_h(el, dst, src, 6144, full, EF(7), pol);
                TRC(el && k == 0, 3, w * 32 + L * 16 + ph * 3 + 2);
              }
              break;
            }
            const uint32_t full = bars + B_FULLA + w * 32 + c.s * 8, dst = sb + c.s * ST_BYTES + w * 8192;
            mbar_wait_c(bars + B_EMPTY + c.s * 8, c.ph);
            expect_tx_p(el, full, 8192);
            flag_wait(f, t8);
            fence_async_g();
            tma3d_h(el, dst, &P.act[1], 0, rb * 64, w, full, false, pol);
            c.next();
            TRC(el, 3, w * 32 + L * 16 + ph * 3 + 2);
          }
#pragma unroll 1
          for (int i = L; i < 9; i++) {
            AGENT_IDS;
            const uint32_t full = bars + B_FULLA + w * 32 + c.s * 8, dst = sb + c.s * ST_BYTES + w * 8192;
            if (L == 0 && i == AEP) t8 = (ldcg32(fr + FR_EP + j) + 1) * 8;
            mbar_wait_c(bars + B_EMPTY + c.s * 8, c.ph);
            expect_tx_p(el, full, 8192);
            tma3d_h(el, dst, &P.act[L], i * 64, rb * 64, w, full, false, pol);
            c.next();
            if (i == PZI || i == PZI + 1) {
              uint8_t* d = (i == PZI ? xn_block(hw) : z1_block(rb, 0, 0) + w * 4608) + j * 9216 + lane * 16;
#pragma unroll 1
              for (int u = i == PZI ? 0 : 3; u < 6; u++, d += 1536) { stg128(d, ~0u, ~0u, ~0u, ~0u); stg128(d + 512, ~0u, ~0u, ~0u, ~0u); stg128(d + 1024, ~0u, ~0u, ~0u, ~0u); }
            }
            if (i == RFI) {
              expect_tx_p(el, bars + B_WT + w * 8, 9216);
              tma3d_h(el, sb + SM_STG + w * 9216, &P.row[L], 0, 3 * w, rb * 64 + 8 * j, bars + B_WT + w * 8, false, pol);
            }
            if (i == 4 && L > w) {
              expect_tx_p(el, bars + B_CSQ, 864);
              bulk_load_p(el, sb + 3 * ST_BYTES + SM_CSQ, Q.CSP + (NCTA + (id >> 1)) * 216, 864, bars + B_CSQ);
            }
          }
          if (c.s) { c.s = 0; c.ph ^= 1; }
          {
            AGENT_IDS;
            const uint32_t tag = (t8 >> 2) - 1 + L;
            uint4* const xs = Q.XST + hw * 128;
            const uint32_t tab = sb + L * (3 * ST_BYTES) + SM_XST + w * 768 + lane * 8;
            TRC(el, 3, w * 32 + L * 16 + 13);
#pragma unroll 1
            for (int it = 0; it < (1 << 22); it++) {
              const uint4 a = ll_ld128(xs + 2 * lane), b = ll_ld128(xs + 64 + 2 * lane), h = ll_ld128(xs - (rb ? 192 : 0) + 2 * (lane | 24));
              if (__all_sync(~0u, a.z == tag && b.z == tag && h.z == tag)) { sts64(tab, h.x, h.y); sts64(tab + 256, a.x, a.y); sts64(tab + 512, b.x, b.y); break; }
            }
            __syncwarp();
            if (el) mbar_arrive(bars + B_CSQ);
            TRC(el, 3, w * 32 + L * 16 + 14);
            uint32_t* f = Q.flags + rb * 64 + FR_PZ + L;
            if (RESL) flag_release_p(el, f);
            expect_tx_p(el, bars + B_RES + w * 8, 9216);
            tma3d_h(el, sb + SM_STG + w * 9216, &P.res[L], j * 72, hw * 32, 0, bars + B_RES + w * 8, !L, pol);
            if (!RESL) flag_release_p(el, f);
            flag_wait(f, t8 * 2);
            fence_async_g();
            TRC(el, 3, w * 32 + L * 16 + 15);
          }
        }
        if (wid == 10) {
          AGENT_IDS;
          mbar_wait_c(ev - (EV_N - EV_ZN) * 8, L);
          mbar_wait_c(ev + EV_ZN * 8, L);
          asm volatile("fence.release.gpu;" ::: "memory");
          flag_add_p(el, fj + FJ_ZN + L);
          flag_add_p(el, fr - 32 + FR_XR + L);
          flag_wait(fj + FJ_ZN + L, t8 * 2);
          flag_wait(fr - 32 + FR_XR + L, t8);
          if (el) mbar_arrive(bars + B_ZOK);
        } else if (WPF) {
          AGENT_IDS;
          mbar_wait_c(ev + EV_ZN * 8, L);
          if (el) asm volatile("cp.async.bulk.prefetch.tensor.3d.L2.global [%0, {%1, %2, %3}];" ::"l"(&P.wsp), "r"(j * 128), "r"(rb * 64), "r"(0) : "memory");
        }
        float cv;
        {
        AGENT_IDS;
        cv = (lane & 3) ? 0.f : -blo(ldnc16(Q.b_sp + 128 * rb + 16 * j + 2 * (lane >> 2) + w));
        mbar_wait_c(ev + EV_Z1 * 8, L);
        const uint32_t ro = (w * 64 + 8 * j + (lane >> 2)) * 128, x0 = ((lane & 3) * 2) ^ (lane >> 2);
#pragma unroll 1
        for (int i = 0; i < 32; i++) {
          const bool tail = (i >> 1) == 12;
          const int kb = tail ? i + 6 : i < 24 ? i : i - 2;
          if (!(i & 7)) mbar_wait_c(bars + B_RT + i, L);
          if (i == 24) mbar_wait_c(bars + B_WT + w * 8, 1);
          if (!tail) mbar_wait(bars + B_FULL + c.s * 8, c.ph ^ 1);
          if (i == 3) {
            uint32_t id2 = id;
            asm volatile("" : "+r"(id2));
            expect_tx_p(el, bars + B_WT + w * 8, 3072);
#pragma unroll 1
            for (int r = 0; r < 8; r++)
              bulk_load_p(el, sb + SM_WT + w * 3200 + r * 400, (const uint8_t*)Q.w_sp + (64 * (id2 & 30) + 16 * (id2 >> 5) + 2 * r + w) * (SEQ * 2) + 29 * 128, 384, bars + B_WT + w * 8);
          }
#pragma unroll
          for (int e = 0; e < 2; e++) {
            const uint4 a = lds128(!tail ? sb + c.s * ST_BYTES + ro + ((x0 ^ e) << 4) : sb + SM_WT + w * 3200 + (lane >> 2) * 400 + (i - 24) * 256 + (lane & 3) * 32 + e * 16);
            const uint4 m = lds128(sb + SM_RT + 4096 + kb * 128 + (lane & 3) * 32 + e * 16);
            cv = fmaf(blo(a.x), blo(m.x), fmaf(bhi(a.x), bhi(m.x), fmaf(blo(a.y), blo(m.y), fmaf(bhi(a.y), bhi(m.y), cv))));
            cv = fmaf(blo(a.z), blo(m.z), fmaf(bhi(a.z), bhi(m.z), fmaf(blo(a.w), blo(m.w), fmaf(bhi(a.w), bhi(m.w), cv))));
          }
          if (!tail) {
            __syncwarp();
            if (el) mbar_arrive(bars + B_AD + c.s * 8);
            c.next();
          }
        }
        }
        AGENT_IDS;
        TRC(el, 3, w * 32 + L * 16 + 11);
        asm volatile("" : "+r"(t8));
        const uint32_t tag = (t8 >> 2) - 1 + L;
        cv = qsum(cv);
        uint2* const cs = (uint2*)(Q.XST + hw * 128 + 1);
        if ((lane & 3) == 0) ll_st64(cs + 32 * j + (lane >> 2) * 4, __float_as_uint(cv), tag);
#pragma unroll 1
        for (int it = 0; it < (1 << 22); it++) {
          const uint2 a = ll_ld64(cs + 4 * lane), b = ll_ld64(cs + 128 + 4 * lane);
          if (__all_sync(~0u, a.y == tag && b.y == tag)) { sts32(sb + SM_CV + w * 256 + lane * 4, a.x); sts32(sb + SM_CV + w * 256 + 128 + lane * 4, b.x); break; }
        }
        __syncwarp();
        if (el) mbar_arrive(bars + B_CV + w * 8);
        TRC(el, 3, w * 32 + L * 16 + 12);
#pragma unroll 1
        for (int kb = 30; kb < 32; kb++) {
          mbar_wait_c(bars + B_FULL + c.s * 8, c.ph ^ 1);
          if (el) mbar_arrive(bars + B_AD + c.s * 8);
          c.next();
        }
        c.ph ^= ((c.s + 11) >> 2) & 1; c.s = (c.s + 11) & 3;
        if (L == 0) {
          mbar_wait_c(ev + EV_PT * 8, 0);
          flag_add_p(el, fj + FJ_P4);
        }
      }
    } else {
      const uint32_t epoch = ldcg32(fj + FJ_EP + rb);
      mbar_wait(bars + B_IMG, 0);
      TRC(el, 2, 41);
      flag_release_p(el, fj + FJ_WQ);
      TRC(el, 2, 42);
#pragma unroll 1
      for (int L = 0; L < 2; L++) {
        float* const csf = Q.CSP + (NCTA + bid) * 216;
        if (L == 0) {
          flag_wait(fj + FJ_WQ, (epoch + 1) * 16);
          fence_async_g();
          expect_tx_p(el, bars + B_XRW, 13824);
          bulk_load_p(el, sb + ST_BYTES + SM_WOI, Q.CSP + j * 16 * 216, 6912, bars + B_XRW);
          bulk_load_p(el, sb + 2 * ST_BYTES + SM_WOI, Q.CSP + (j * 16 + 8) * 216, 6912, bars + B_XRW);
          mbar_wait(bars + B_XRW, 0);
#pragma unroll 1
          for (int f = lane; f < 54; f += 32) {
            float s[4] = {0.f, 0.f, 0.f, 0.f};
#pragma unroll 2
            for (int r = 0; r < 16; r++) {
              const uint4 v = lds128(sb + ST_BYTES + SM_WOI + (r >> 3) * ST_BYTES + (r & 7) * 864 + f * 16);
              s[0] += __uint_as_float(v.x); s[1] += __uint_as_float(v.y); s[2] += __uint_as_float(v.z); s[3] += __uint_as_float(v.w);
            }
            sts128(sb + SM_CSQ + f * 16, __float_as_uint(s[0]), __float_as_uint(s[1]), __float_as_uint(s[2]), __float_as_uint(s[3]));
            stg128(csf + f * 4, __float_as_uint(s[0]), __float_as_uint(s[1]), __float_as_uint(s[2]), __float_as_uint(s[3]));
          }
          __syncwarp();
          if (el) mbar_arrive(bars + B_CSQ);
          TRC(el, 2, 43);
          mbar_wait(bars + B_WOI, 0);
          bulk_store_p(el, Q.WO + j * WO_SL + rb * (41 * 128), sb + SM_WOI, (rb < 15 ? 41 : 33) * 128);
          publish_p(el, fj + FJ_WO);
          TRC(el, 2, 44);
          if (el) prefetch_l2((const uint8_t*)Q.w_in + bid * 41472, 41472);
          float o0 = 0.f, o1 = 0.f;
#pragma unroll 1
          for (int u = 0; u < 2; u++) {
            const uint8_t* src = (u ? (const uint8_t*)Q.w_sp + 500 * (SEQ * 2) + 2048 : (const uint8_t*)Q.w_in + 100 * (2 * FH * 2) + FH * 2) + lane * 16;
            const uint4 a = ldnc128(src), b = ldnc128(src + 300 * (2 * FH * 2) + 2048);
            const uint32_t x[8] = {a.x, a.y, a.z, a.w, b.x, b.y, b.z, b.w};
            float sq = 0.f;
#pragma unroll
            for (int e = 0; e < 8; e++) sq = fmaf(blo(x[e]), blo(x[e]), fmaf(bhi(x[e]), bhi(x[e]), sq));
            o0 = o1;
            asm("sqrt.approx.f32 %0, %1;" : "=f"(o1) : "f"(wsum(sq) * (u ? C0S * C0S * SEQ / 512.f : 2.f * GA * GA * DM / 512.f)));
          }
          const uint32_t off = (__float_as_uint(o0) & 0x7f800000u) >> 16 | 0x8000u | OFM;
          if (el) sts128(sb + SM_OFF, off * 0x10001u, min(__float_as_uint(o1) & 0x7f800000u, 0x7e000000u) | 0x00400000u, __float_as_uint(GB), 0u);
        }
        mbar_wait(bars + B_EVT + EV_O * 8, L);
        mbar_wait(bars + B_EVT + (EV_N + EV_O) * 8, L);
        flag_release_p(el, Q.flags + rb * 64 + FR_OL + L);
#pragma unroll 1
        for (int w = 0; w < 2; w++) {
          mbar_wait(bars + B_EVT + (w * EV_N + EV_XS) * 8, L);
          if (!w) mbar_wait(bars + B_AF3 + XP0 * 8, L);
          if (el) asm volatile("cp.async.bulk.tensor.3d.global.shared::cta.tile.bulk_group [%0, {%2, %3, %4}], [%1];\ncp.async.bulk.commit_group;\ncp.async.bulk.wait_group.read 0;" ::"l"(&P.res[1]), "r"(sb + SM_STG + w * 9216), "r"(j * 72), "r"(rb * 64 + w * 32), "r"(0) : "memory");
          __syncwarp();
          if (lane < 2 && !w) mbar_arrive_cluster(mapa(bars + B_S5, lane));
        }
        if (el) { asm volatile("cp.async.bulk.wait_group 0;" ::: "memory"); mbar_arrive(bars + B_GATE3); }
        const uint32_t tag = epoch * 2 + L + 1;
        asm volatile("" : "+r"(lane));
#pragma unroll 1
        for (int b = 0; b < 8; b++) {
          if (!(b & 3)) {
            const int mb = b >> 2;
            mbar_wait(bars + B_ZS + mb * 8, L);
            lane += spin<ZD1>(Q.zero);
            TRC(el && !mb, 2, L * 16 + 8);
            uint4 v;
#pragma unroll 1
            for (int it = 0; it < (1 << 22); it++) {
              v = ll_ld128(Q.ZST + ((rb * 2 + mb) * 8 + (lane >> 2)) * 32 + 4 * j + (lane & 3));
              const uint32_t tg = 2 + L;
              if (__all_sync(~0u, !(((v.x ^ tg) | (v.y ^ tg) | (v.z ^ tg) | (v.w ^ tg)) & 3))) break;
            }
            const bool o = lane & 16;
            float ss = __uint_as_float(o ? v.y : v.x) + __shfl_xor_sync(~0u, __uint_as_float(o ? v.x : v.y), 16), sq = __uint_as_float(o ? v.w : v.z) + __shfl_xor_sync(~0u, __uint_as_float(o ? v.z : v.w), 16);
            ss += __shfl_xor_sync(~0u, ss, 4); sq += __shfl_xor_sync(~0u, sq, 4); ss += __shfl_xor_sync(~0u, ss, 8); sq += __shfl_xor_sync(~0u, sq, 8);
            const float mean = ss * (1.f / FH), rs = blo(pack2(rsqrtf(fmaxf(fmaf(sq, 1.f / FH, -mean * mean), 0.f) + 4.f * GA * GA * LN_EPS), 0.f));
            if (!(lane & 12)) ll_st64(Q.RT + (mb * 16 + rb) * 64 + 8 * j + 2 * (lane & 3) + (lane >> 4), pack2(rs, rs * (mean - blo(lds32(sb + SM_OFF)))), tag);
            TRC(el && !mb, 2, L * 16 + 10);
            lane += spin<ZD2>(Q.zero);
          }
          uint4 v[4];
#pragma unroll 1
          for (int it = 0; it < (1 << 22); it++) {
            bool ok = true;
#pragma unroll
            for (int u = 0; u < 4; u++) { v[u] = ll_ld128((const uint4*)Q.RT + b * 128 + u * 32 + lane); ok = ok && v[u].y == tag && v[u].w == tag; }
            if (__all_sync(~0u, ok)) break;
          }
#pragma unroll
          for (int u = 0; u < 4; u++) {
            const uint32_t rt = sb + SM_RT + b * 512 + u * 128, ro = (lane >> 3) * 32 + (lane & 3) * 8 + ((lane >> 2) & 1) * 2;
            sts32(rt + 4096 + lane * 4, __byte_perm(v[u].x, v[u].z, 0x7632));
            asm volatile("st.shared.u16 [%0], %1;\nst.shared.u16 [%0 + 4], %2;" ::"r"(rt + ro), "h"((uint16_t)v[u].x), "h"((uint16_t)v[u].z) : "memory");
          }
          __syncwarp();
          if (el && (b & 1)) mbar_arrive(bars + B_RT + (b - 1) * 4);
          TRC(el && b < 2, 2, L * 16 + 11 + b);
        }
        TRC(el, 2, L * 16 + 9);
        mbar_wait(bars + B_EVT + EV_Z1 * 8, L);
        mbar_wait(bars + B_EVT + (EV_N + EV_Z1) * 8, L);
        fence_gpu();
        if (el) mbar_arrive(bars + B_Z1);
      }
    }
  } else {
    const int w = wid >> 2, q = wid & 3;
    int g = lane >> 2, t = lane & 3;
    const uint32_t ev = bars + B_EVT + w * EV_N * 8;
    const bool tr = (tid & 127) == 0;
    (void)tr;
    Cur c{0, 0};
    const uint32_t ebar = mapa(bars + B_EMPTY, (bid & 1) ^ (lane & 1));
    auto release = [&](uint32_t s) { if (lane < 2) mbar_arrive_cluster(ebar + s * 8); };
    const uint32_t stg = sb + SM_STG + w * 9216;
    uint32_t ia = 0;
    auto wait_ab = [&]() { mbar_wait_c(bars + B_FULL + c.s * 8, c.ph); mbar_wait_c(bars + B_FULLA + w * 32 + c.s * 8, (ia >> c.s) & 1); ia ^= 1u << c.s; };
    uint32_t lagph = 0;
    auto yield = [&](int left, int lag) { if (w == 1 && left == lag) mbar_wait_c(bars + B_LAG, lagph); };
    auto yield_done = [&]() { if (w == 0 && lane == 0) mbar_arrive(bars + B_LAG); };
    uint32_t rp = 0;
    auto check = [&](auto n, uint32_t dst, const uint8_t* src) {
      const uint32_t a = dst + lane * 32 + (lane >> 2) * 4;
#pragma unroll 1
      for (int it = 0; it < (1 << 16); it++) {
        uint32_t x = lds32(a);
#pragma unroll
        for (int e = 1; e < n.value; e++) x = max(x, lds32(a + e * 1024));
        if (!__any_sync(~0u, x == ~0u)) break;
        fence_async_s();
        __syncwarp();
        expect_tx_p(lane == 0, bars + B_RB + q * 8, n.value * 1024);
        bulk_load_p(lane == 0, dst, src, n.value * 1024, bars + B_RB + q * 8);
        mbar_wait_c(bars + B_RB + q * 8, rp & 1);
        rp++;
      }
    };
    auto signal = [&](int e) { __syncwarp(); if (lane == 0) mbar_arrive(ev + e * 8); };
    TRC(tr, w, 0);

    {
      uint8_t* dst = Q.WQ + j * WQ_SL + rb * 3456 + tid * 16;
#pragma unroll
      for (int u = 0; u < 5; u++) {
        stg128_if((u < 4 || rb < 8) && tid < 216, dst + u * (16 * 3456), wv[u].x, wv[u].y, wv[u].z, wv[u].w);
        if (u == 0) TRC(tr, w, 60);
      }
      if (Q.zero == 0) {
        float s[8];
#pragma unroll
        for (int u = 0; u < 5; u++) {
          const uint32_t x[4] = {wv[u].x, wv[u].y, wv[u].z, wv[u].w};
#pragma unroll
          for (int e = 0; e < 4; e++) { s[2 * e] = u ? s[2 * e] + blo(x[e]) : blo(x[e]); s[2 * e + 1] = u ? s[2 * e + 1] + bhi(x[e]) : bhi(x[e]); }
        }
#pragma unroll
        for (int m = 4; m; m >>= 1) {
#pragma unroll
          for (int e = 0; e < m; e++) s[e] = ((tid & m) ? s[e + m] : s[e]) + __shfl_xor_sync(~0u, (tid & m) ? s[e] : s[e + m], m);
        }
        stg32_if(tid < 216, Q.CSP + bid * 216 + tid, __float_as_uint(s[0]));
      }
      __syncwarp();
      if (lane == 0) mbar_arrive(bars + B_IMG);
    }
    reg_alloc<232>();
    auto fetch_wo = [&]() {
#pragma unroll 1
      for (int u = tid; u < 328; u += 256) {
        const int m = min(41 * rb + (u >> 3), 647), k8 = m / 9;
        cp_async16(sb + SM_WOI + u * 16, (const uint8_t*)Q.wo + (8 * k8 + (u & 7)) * (DM * 2) + (72 * j + 8 * (m - k8 * 9)) * 2);
      }
    };
    const uint32_t epoch = ldcg32(Q.flags + (rb * 2 + w) * 32 + FR_EP + j);
    TRC(tr, w, 1);

#pragma unroll 1
    for (int L = 0; L < 2; L++) {
      const int tb = 2 + L * 24;
      asm volatile("" : "+r"(lane), "+r"(g), "+r"(t));
      (void)tb;
      const uint32_t tag = epoch * 2 + L + 1;
      uint32_t aoff = (w * 64 + q * 16 + (lane & 15)) * 128 + (((lane >> 4) ^ (lane & 7)) << 4);
      {
        uint32_t Pk[27][2];
        float rk[2][2], sc[2][2];
        const bool up0 = 2 * t > g, up1 = 2 * t + 1 > g;
        constexpr int HA_[6] = {0, 2, 4, 7, 12, 15}, HC_[6] = {6, 9, 10, 11, 14, 17};
        const bool remote = q == 0 && rb > 0;
        uint4* hp = Q.HALO + ((((rb - (q == 0)) * 2 + w) * 8 + j) * 6) * 32 + lane;
        const uint32_t att = 2 * ST_BYTES + w * 8192 + lane * 16;
        const uint8_t* hs = remote ? (const uint8_t*)hp : smem_raw + att + (q == 3 ? ST_BYTES : q == 2 ? 3072 : 0);
        uint8_t* od = z1_block(rb, q >> 1, 0) + (9 * j) * 1024 + (4 * (q & 1) + w) * 128 + lane * 4;
        ACLK_INIT;
        {
          float acc[108];
#pragma unroll
          for (int i = 0; i < 108; i++) acc[i] = 0.f;
          float sx[2] = {0.f, 0.f}, sq[2] = {0.f, 0.f};
          uint32_t prev = 0;
#pragma unroll 1
          for (int kb = 0; kb < 9; kb++) {
            wait_ab();
            yield(9 - kb, LAG1);
            TRC(tr && kb == 0, w, tb + 0);
            PCLK(kb * 4);
            const uint32_t st = sb + c.s * ST_BYTES, da = dlo(st + w * 8192, 16), db = dlo(st + ST_B, 3456);
            wgmma_fence();
#pragma unroll
            for (int kk = 0; kk < 4; kk++) {
              wgmma_ss_n216(acc, dsc<1024, 1>(da, kk * 32), dsc<128, 0>(db, kk * 6912), 1);
              if (kk == 0) { wgmma_commit(); wgmma_wait<1>(); if (kb > 0) release(prev); }
              if (kk == 3) wgmma_commit();
              if (kk == XK1) {
            if (kb >= KS && kb < KS + 3) {
              mbar_wait_c(bars + B_WT + w * 8, 0);
#pragma unroll
              for (int u = 0; u < 3; u++) {
                const uint2 x = lds64(stg + (2 * q + (lane >> 4)) * 1152 + (lane & 15) * 8 + (kb - KS) * 384 + u * 128);
                sx[0] += blo(x.x) + bhi(x.x); sx[1] += blo(x.y) + bhi(x.y);
                sq[0] = fmaf(blo(x.x), blo(x.x), fmaf(bhi(x.x), bhi(x.x), sq[0])); sq[1] = fmaf(blo(x.y), blo(x.y), fmaf(bhi(x.y), bhi(x.y), sq[1]));
              }
            }
            if (kb == KS + 3) {
              const bool o = lane & 1;
              float v = (o ? sq[0] + sq[1] : sx[0] + sx[1]) + __shfl_xor_sync(~0u, o ? sx[0] + sx[1] : sq[0] + sq[1], 1);
              v += __shfl_xor_sync(~0u, v, 2); v += __shfl_xor_sync(~0u, v, 4); v += __shfl_xor_sync(~0u, v, 8);
              const float m = v * (-1.f / DM), r = rsqrtf(fmaxf(fmaf(__shfl_xor_sync(~0u, v, 1), 1.f / DM, -m * m), 0.f) + LN_EPS);
              ll_st128_if(!(lane & 15), Q.XST + (rb * 2 + w) * 128 + 16 * j + 4 * q + (lane >> 3), m, r, tag);
            }
              }
              if (kk == XK2 && L == 0) {
            if (kb == 0) fetch_wo();
            if (kb == 3) {
              asm volatile("cp.async.wait_all;" ::: "memory");
              fence_async_s();
              __syncwarp();
              if (lane == 0) mbar_arrive(bars + B_WOI);
            }
              }
            }
            if (kb == 8) yield_done();
            PCLK(kb * 4 + 1);
            PCLK(kb * 4 + 2);
            PCLK(kb * 4 + 3);
            prev = c.s; c.next();
          }
          const uint32_t cs = sb + prev * ST_BYTES + SM_CSQ + t * 8;
          mbar_wait_c(bars + B_CSQ, L);
          const uint32_t xs = sb + prev * ST_BYTES + SM_XST + w * 768 + 256 + q * 128;
          const float2 n0 = lds64f(xs + g * 8), n1 = lds64f(xs + g * 8 + 64);
          const float m0 = n0.x, m1 = n1.x;
#pragma unroll
          for (int u = 0; u < 4; u++) {
            rk[u >> 1][u & 1] = __uint_as_float(lds32(xs + t * 16 + ((u & 1 ? up1 : up0) ? -64 : 0) + (u & 1) * 8 + (u >> 1) * 64 + 4));
            sc[u >> 1][u & 1] = rk[u >> 1][u & 1] * ((u >> 1 ? n1.y : n0.y) * (0.23570226039551584f * 1.4426950408889634f));
          }
          float2 cv[27];
#pragma unroll
          for (int G = 0; G < 27; G++) cv[G] = lds64f(cs + G * 32);
          PCLK(36);
          wgmma_wait<0>();
          PCLK(37);
          release(prev);
          lagph ^= 1;
          TRC(tr, w, tb + 1);
          ACLK(0);
#pragma unroll
          for (int G = 9; G < 27; G++) Pk[G][1] = pack2(fmaf(m1, cv[G].x, acc[4 * G + 2]), fmaf(m1, cv[G].y, acc[4 * G + 3]));
          if (q < 3) {
#pragma unroll
            for (int i = 0; i < 6; i++) sts128(sb + att + (q >> 1) * ST_BYTES + (q & 1) * 3072 + i * 512, Pk[9 + HA_[i]][1], Pk[10 + HA_[i]][1], tag, Pk[9 + HC_[i]][1]);
          } else if (rb < 15) {
#pragma unroll
            for (int i = 0; i < 6; i++) ll_st128(hp + i * 32, __uint_as_float(Pk[9 + HA_[i]][1]), __uint_as_float(Pk[10 + HA_[i]][1]), tag, __uint_as_float(Pk[9 + HC_[i]][1]));
          }
#pragma unroll
          for (int G = 0; G < 27; G++) {
            Pk[G][0] = pack2(fmaf(m0, cv[G].x, acc[4 * G]), fmaf(m0, cv[G].y, acc[4 * G + 1]));
            if (G < 9) Pk[G][1] = pack2(fmaf(m1, cv[G].x, acc[4 * G + 2]), fmaf(m1, cv[G].y, acc[4 * G + 3]));
          }
        }
        ACLK(1);
        constexpr int GA_[4] = {0, 2, 4, 7}, GB_[4] = {1, 3, 5, 8}, GC_[4] = {2, 4, 6, 6};
        float S1[4][4], S2[4][4];
        uint32_t qa[4][2], qc[4][2];
#pragma unroll
        for (int h = 0; h < 4; h++) {
#pragma unroll
          for (int r = 0; r < 2; r++) {
            qa[h][r] = (h == 0 || h == 3 || t >= h) ? Pk[GA_[h]][r] : 0u;
            qc[h][r] = (h == 3 ? t == 3 : t <= h) ? Pk[GC_[h]][r] : 0u;
          }
#pragma unroll
          for (int i = 0; i < 4; i++) S1[h][i] = S2[h][i] = 0.f;
          mma16(S1[h], qa[h][0], qa[h][1], Pk[GB_[h]][0], Pk[GB_[h]][1], Pk[9 + GA_[h]][0], Pk[9 + GB_[h]][0]);
          mma16(S2[h], qa[h][0], qa[h][1], Pk[GB_[h]][0], Pk[GB_[h]][1], Pk[9 + GA_[h]][1], Pk[9 + GB_[h]][1]);
        }
#pragma unroll
        for (int h = 0; h < 4; h++) {
          mma8(S1[h], qc[h][0], qc[h][1], Pk[9 + GC_[h]][0]);
          mma8(S2[h], qc[h][0], qc[h][1], Pk[9 + GC_[h]][1]);
        }
        uint32_t V1[9], V2[9];
#pragma unroll
        for (int i = 0; i < 9; i++) { V1[i] = movm(Pk[18 + i][0]); V2[i] = movm(Pk[18 + i][1]); }
        uint4 hv[6];
#pragma unroll
        for (int i = 0; i < 6; i++) hv[i] = ll_ld128g(hs + i * 512);
        const uint32_t mup = (up0 ? 0xffffu : 0u) | (up1 ? 0xffff0000u : 0u);
        auto finish = [&](const float (&x0)[4], const float (&x1)[4], const uint32_t (&Vb)[9], uint32_t ma, int hi) {
          uint32_t p[4], n[4];
          float rs[4];
#pragma unroll
          for (int h = 0; h < 4; h++) {
            const float m = qmax(fmaxf(x0[h], x1[h])), e0 = ex2(x0[h] - m), e1 = ex2(x1[h] - m);
            n[h] = pack2(e0, e1);
            p[h] = pack2(e0 * rk[hi][0], e1 * rk[hi][1]);
          }
#pragma unroll
          for (int h = 0; h < 4; h += 2) {
            float D[4] = {0.f, 0.f, 0.f, 0.f};
            mma8(D, n[h], n[h + 1], 0x3f803f80u);
            rs[h] = rcp_fast(D[0]); rs[h + 1] = rcp_fast(D[2]);
          }
#pragma unroll
          for (int i = 0; i < 9; i++) {
            const int h = i < 4 ? 0 : i == 4 ? 1 : 2;
            const bool nx = (i == 2 || i == 4 || i == 6) ? 2 * t >= i : i == 3 || i > 6;
            float O[4] = {0.f, 0.f, 0.f, 0.f};
            mma16(O, p[h] & ma, p[h + 1] & ma, p[h] & ~ma, p[h + 1] & ~ma, V1[i], Vb[i]);
            const float r = nx ? rs[h + 1] : rs[h];
            stg32(od + i * 1024 + hi * 256, pack2((nx ? O[2] : O[0]) * r, (nx ? O[3] : O[1]) * r));
          }
        };
        {
          float x0[4], x1[4];
#pragma unroll
          for (int h = 0; h < 4; h++) { x0[h] = (up0 ? S1[h][2] : S2[h][2]) * sc[1][0]; x1[h] = (up1 ? S1[h][3] : S2[h][3]) * sc[1][1]; }
          finish(x0, x1, V2, mup, 1);
        }
        ACLK(2);
        bar_sync(1 + w, 128);
#pragma unroll 1
        for (int it = 0; it < (1 << 20); it++) {
          if (remote) {
            bool ok = true;
#pragma unroll
            for (int i = 0; i < 6; i++) ok = ok && hv[i].z == tag;
            if (__all_sync(~0u, ok)) break;
          }
#pragma unroll
          for (int i = 0; i < 6; i++) hv[i] = ll_ld128g(hs + i * 512);
          if (!remote) break;
        }
        uint32_t H[18];
#pragma unroll
        for (int i = 0; i < 6; i++) { H[HA_[i]] = hv[i].x; H[HA_[i] + 1] = hv[i].y; H[HC_[i]] = hv[i].w; }
        float S0[4][4];
#pragma unroll
        for (int h = 0; h < 4; h++) {
#pragma unroll
          for (int i = 0; i < 4; i++) S0[h][i] = 0.f;
          mma16(S0[h], qa[h][0], qa[h][1], Pk[GB_[h]][0], Pk[GB_[h]][1], H[GA_[h]], H[GB_[h]]);
        }
#pragma unroll
        for (int h = 0; h < 4; h++) mma8(S0[h], qc[h][0], qc[h][1], H[GC_[h]]);
        uint32_t V0[9];
#pragma unroll
        for (int i = 0; i < 9; i++) V0[i] = movm(H[9 + i]);
        ACLK(3);
        {
          const bool nohalo = (rb | q) == 0;
          const float b0 = up0 && nohalo ? -INFINITY : 0.f, b1 = up1 && nohalo ? -INFINITY : 0.f;
          float x0[4], x1[4];
#pragma unroll
          for (int h = 0; h < 4; h++) { x0[h] = fmaf(up0 ? S0[h][0] : S1[h][0], sc[0][0], b0); x1[h] = fmaf(up1 ? S0[h][1] : S1[h][1], sc[0][1], b1); }
          finish(x0, x1, V0, ~mup, 0);
        }
        ACLK(4);
        signal(EV_O);
        ACLK_OUT;
        TRC(tr, w, tb + 2);
      }
      if (c.s) { c.s = 0; c.ph ^= 1; }
      {
        float acc[36];
        const int hw = rb * 2 + w;
        const uint32_t xt = stg + (8 * q + g) * 144 + t * 4;
        uint32_t xm = stg + (8 * q + (lane & 7)) * 144 + (lane & 8) * 576 + (lane & 16);
        uint8_t* xn = xn_block(hw) + j * 9216 + q * 256 + lane * 4;
        uint32_t* sp = (uint32_t*)(Q.ST1 + (hw * 8 + j) * 32 + 8 * q) + lane;
        const uint4* sg = Q.ST1 + (hw * 8 + t) * 32 + 8 * q + g;
        asm volatile("" : "+r"(xm), "+l"(xn), "+l"(sp), "+l"(sg));
        mbar_wait_c(bars + B_RES + w * 8, L);
        TRC(tr, w, tb + 21);
#pragma unroll
        for (int i = 0; i < 18; i++) { const uint32_t x = lds32(xt + (i >> 1) * 16 + (i & 1) * 4608); acc[2 * i] = blo(x); acc[2 * i + 1] = bhi(x); asm volatile("" : "+f"(acc[2 * i]), "+f"(acc[2 * i + 1])); }
        mbar_wait_c(bars + B_WF, L);
        const uint32_t db = dlo(sb, 1152), of = bars + (w ? B_OF + 40 : B_AV + 96);
        uint32_t da[5];
#pragma unroll
        for (int e = 0; e < 5; e++) da[e] = __shfl_sync(~0u, dlo(sb + o_place(w, e), 1024), 0);
        if (w) {
#pragma unroll 1
          for (int kb = q; kb < 9; kb += 4) {
            const uint32_t e = (kb + 1) >> 1;
            mbar_wait_c(bars + B_OF + e * 8, L);
            check(Int<8>{}, sb + o_place(0, e) + (kb && !(kb & 1)) * 8192, z1_block(rb, 0, 0) + kb * 8192);
            if (lane <= !kb) mbar_arrive(bars + B_AV + (12 + e) * 8);
          }
          bar_sync(7, 256);
        }
        mbar_wait_c(of, L & w);
        TRC(tr, w, tb + 3);
        wgmma_fence();
#pragma unroll
        for (int kk = 0; kk < 4; kk++) wgmma_ss_n72(acc, dsc<128, 0>(da[0], kk * 2048), dsc<128, 0>(db, kk * 2304), 1);
        wgmma_commit();
#pragma unroll 1
        for (int h = 0; h < 2; h++) {
#pragma unroll
          for (int u = 0; u < 4; u++) {
            if (!(u & 1)) { mbar_wait_c(of + 8 + h * 16 + u * 4, u && h ? L : L & w); wgmma_fence(); }
            if (u == 3 && h && !w) bar_arrive(7, 256);
#pragma unroll
            for (int kk = 0; kk < 4; kk++) wgmma_ss_n72(acc, dsc<128, 0>(da[1 + (u >> 1)], (u & 1) * 8192 + kk * 2048), dsc<128, 0>(db + h * 2304, (1 + u) * 9216 + kk * 2304), 1);
            if (u != 2) wgmma_commit();
            if (u == 0) { wgmma_wait<1>(); if (lane + w == 0 && h) mbar_arrive(bars + B_X3); }
          }
          da[1] = da[3]; da[2] = da[4];
        }
        RCLK_INIT;
        wgmma_wait<0>();
        RCLK(0);
        if (lane < 2) mbar_arrive_cluster(ebar + B_XD - B_EMPTY + w * 8);
        TRC(tr && P5TRACE != 5, w, tb + 4);
        {
          float s0 = 0.f, s1 = 0.f, q0 = 0.f, q1 = 0.f;
#pragma unroll
          for (int i = 0; i < 36; i++) {
            if (i & 2) { s1 += acc[i]; q1 = fmaf(acc[i], acc[i], q1); } else { s0 += acc[i]; q0 = fmaf(acc[i], acc[i], q0); }
          }
          const bool o1 = t & 1, o2 = t & 2;
          const float ss = (o1 ? s1 : s0) + __shfl_xor_sync(~0u, o1 ? s0 : s1, 1), sq = (o1 ? q1 : q0) + __shfl_xor_sync(~0u, o1 ? q0 : q1, 1);
          const float v = (o2 ? sq : ss) + __shfl_xor_sync(~0u, o2 ? ss : sq, 2);
          asm volatile("st.relaxed.gpu.global.u32 [%0], %1;" ::"l"(sp), "r"((__float_as_uint(v) & ~3u) | (2 + L)) : "memory");
        }
        RCLK(1);
        RCLK(2);
        sg += spin<PDEL>(Q.zero);
        uint4 pa, pb;
#pragma unroll 1
        for (int it = 0; it < (1 << 20); it++) {
          pa = ll_ld128(sg); pb = ll_ld128(sg + 128);
          const uint32_t tg = 2 + L;
          if (__all_sync(~0u, !(((pa.x ^ tg) | (pa.y ^ tg) | (pa.z ^ tg) | (pa.w ^ tg) | (pb.x ^ tg) | (pb.y ^ tg) | (pb.z ^ tg) | (pb.w ^ tg)) & 3))) break;
        }
        RCLK(3);
        float mean0 = qsum(__uint_as_float(pa.x) + __uint_as_float(pb.x)) * (-1.f / DM), mean1 = qsum(__uint_as_float(pa.y) + __uint_as_float(pb.y)) * (-1.f / DM);
        const float rs0 = GA * rsqrtf(fmaxf(fmaf(qsum(__uint_as_float(pa.z) + __uint_as_float(pb.z)), 1.f / DM, -mean0 * mean0), 0.f) + LN_EPS);
        const float rs1 = GA * rsqrtf(fmaxf(fmaf(qsum(__uint_as_float(pa.w) + __uint_as_float(pb.w)), 1.f / DM, -mean1 * mean1), 0.f) + LN_EPS);
        mean0 *= rs0; mean1 *= rs1;
#pragma unroll
        for (int i = 0; i < 18; i++) {
          const float a = (i & 1) ? rs1 : rs0, b = (i & 1) ? mean1 : mean0;
          stg32(xn + (i >> 1) * 1024 + (i & 1) * 128, pack2(fmaf(acc[2 * i], a, b), fmaf(acc[2 * i + 1], a, b)));
        }
        signal(EV_X1);
        RCLK(4);
        if (w) {
#pragma unroll 1
          for (int u = q; u < 24; u += 4) {
            const uint32_t mb = u < 2 * SPL ? u >= SPL : u & 1, k = u < 2 * SPL ? u - mb * SPL : u >> 1;
            mbar_wait_c(bars + B_AF3 + mb * 96 + k * 8, L);
            check(Int<6>{}, sb + k * 12288 + mb * 6144, xn_block(rb * 2 + mb) + k * 6144);
            if (lane <= (u < 2 * SPL)) mbar_arrive(bars + B_AV + (u < SPL ? 12 + k : k) * 8);
          }
          TRVI(lane == 0, 5, 56 + L * 4 + q, rp);
        }
#pragma unroll
        for (int u = 0; u < 4; u++)
          stsm4(xm + u * 32, pack2(acc[8 * u], acc[8 * u + 1]), pack2(acc[8 * u + 2], acc[8 * u + 3]), pack2(acc[8 * u + 4], acc[8 * u + 5]), pack2(acc[8 * u + 6], acc[8 * u + 7]));
        asm volatile("stmatrix.sync.aligned.m8n8.x2.shared.b16 [%0], {%1,%2};" ::"r"(xm + 128), "r"(pack2(acc[32], acc[33])), "r"(pack2(acc[34], acc[35])) : "memory");
        fence_async_s();
        signal(EV_XS);
        RCLK(5);
        TRC(tr, w, tb + 5);
        RCLK(6);
        RCLK_OUT;
      }
      {
      float acc[160];
#pragma unroll
      for (int i = 0; i < 160; i++) acc[i] = 0.f;
      float s[2] = {0.f, 0.f}, qq[2] = {0.f, 0.f}, zo = 0.f;
      const uint32_t zp = sb + SM_ZP3 + (tid & 127) * 4;
      auto zstat = [&](int mb, bool on) {
        const bool o1 = t & 1, o2 = t & 2;
        const float ss = ((o1 ? s[1] : s[0]) + __shfl_xor_sync(~0u, o1 ? s[0] : s[1], 1)) * 0x1p60f, sq = (o1 ? qq[1] : qq[0]) + __shfl_xor_sync(~0u, o1 ? qq[0] : qq[1], 1);
        const uint32_t v = (__float_as_uint((o2 ? sq : ss) + zo + __shfl_xor_sync(~0u, o2 ? ss : sq, 2)) & ~3u) | (2 + L);
        asm volatile("{\n.reg .pred p, q, r;\nsetp.eq.u32 p, %4, 1;\nsetp.eq.u32 q, %4, 2;\nsetp.eq.and.u32 r, %5, 0, q;\n@p st.shared.u32 [%0], %2;\n@p bar.arrive 13, 256;\n"
                     "@q st.relaxed.gpu.global.u32 [%1], %2;\n@r mbarrier.arrive.shared::cta.b64 _, [%3];\n}" ::"r"(zp + mb * 512), "l"((uint32_t*)(Q.ZST + ((rb * 2 + mb) * 8 + j) * 32) + (tid & 127)),
                     "r"(v), "r"(bars + B_ZS + mb * 8), "r"(on ? 1 + w : 0), "r"(lane) : "memory");
        s[0] = s[1] = qq[0] = qq[1] = 0.f;
      };
      const uint32_t ebar3 = ebar + (B_E3 - B_EMPTY);
#pragma unroll 1
      for (int half = 0; half < 2; half++) {
        const bool big = half != w;
        auto rel3 = [&](int p) { if (lane < 2) mbar_arrive_cluster(ebar3 + p * 8); };
        if (half + w > 0) bar_sync(6 + w, 256);
        auto pass = [&](auto nk) {
          constexpr int NK = nk.value;
          uint32_t d0 = dlo(sb, 1024), ph = half & ~w, af = bars + B_AV;
          const uint32_t db = dlo(sb + SM_B3, NK == 3 ? 6144 : 2048);
          const bool lead = NK == 3 && !half;
          if (lead) {
#pragma unroll
            for (int u = 0; u < 2 * SPL; u++) {
              const int mb = u / SPL, p = u % SPL;
              if (!mb) mbar_wait_c(bars + B_F3 + p * 8, 0);
              mbar_wait_c(af + (mb ? p : 12 + p) * 8, mb ? L : 1);
              TRC(tr && u == 0, w, tb + 6);
              if (p == 0) SCLK(mb * 4);
              wgmma_fence();
#pragma unroll
              for (int kk = 0; kk < 3; kk++) {
                wgmma_ss_n128(acc + mb * 80, dsc<128, 0>(d0, p * 12288 + kk * 2048 + mb * 6144), dsc<1024, 1>(db, p * 12288 + kk * 2048), p + kk > 0);
                if (kk == 0 && u > SPL) { wgmma_commit(); wgmma_wait<1>(); rel3(p - 1); }
              }
              wgmma_commit();
            }
          }
#pragma unroll 1
          for (int it = 0; it < 6 / NK; it++) {
#pragma unroll
            for (int p = 0; p < 6; p++) {
              if (p < SPL && lead && it == 0) continue;
              mbar_wait_c(bars + B_F3 + p * 8, ph);
              if (NK == 3) mbar_wait_c(af + p * 8, L);
              TRC(tr && p == 0 && it == 0, w, tb + 6 + half * 4);
              if (NK == 2 ? !(p & 1) : p % 3 == 0) SCLK(half * 11 + (NK == 2 ? it * 3 + p / 2 : it * 2 + p / 3));
              wgmma_fence();
#pragma unroll
              for (int u = 0; u < 2 * NK; u++) {
                const int kk = u >> 1, mb = u & 1, e = p * NK + kk;
                const uint64_t da = dsc<128, 0>(d0, (e / 3) * 12288 + (e % 3) * 2048 + mb * 6144);
                if (NK == 3) wgmma_ss_n128(acc + mb * 80, da, dsc<1024, 1>(db, p * 12288 + kk * 2048), e > 0 || it > 0);
                else wgmma_ss_n160(acc + mb * 80, da, dsc<1024, 1>(db, p * 12288 + kk * 6144), e > 0 || it > 0);
                if (u == 0) { wgmma_commit(); wgmma_wait<1>(); if (p > 0 || it > 0) rel3((p + 5) % 6); }
                if (u == HO3 && p == 5 && it == 6 / NK - 1) bar_arrive(7 - w, 256);
              }
              wgmma_commit();
            }
            d0 += NK * 1536; af += 48;
            ph ^= 1;
          }
        };
        if (big) pass(Int<2>{}); else pass(Int<3>{});
        if (w) { bar_sync(13, 256); zo = __uint_as_float(lds32(zp + half * 512)); }
        if (half) zstat(1, true);
        mbar_wait_c(bars + B_GATE3, L);
        const uint32_t off2 = lds32(sb + SM_OFF);
        const int go = (j & 1) ? (big ? 0 : 20) : (big ? 16 : 0);
        const float* gbp = (const float*)(smem_raw + SM_OFF + 8);
        asm volatile("" : "+l"(gbp));
        uint8_t* zd = half ? z1_block(rb, 0, j) + go * 1024 + (q & 1) * 2048 + (q >> 1) * 512 + lane * 16 : z2_block(rb, j) + q * 9216 + go * 128 + ((g & 3) * 2 + (g >> 2)) * 16 + t * 4;
        wgmma_wait<0>();
        SCLK(half * 11 + 9);
        rel3(5);
        TRC(tr, w, tb + 7 + half * 4);
        auto gelu = [&](auto z2) {
          constexpr int NC = z2.value ? NC2 : NC1;
          float gate[NC], gb = GB, gn = GB;
          uint32_t qa[2][3] = {{0, 0, 0}, {0, 0, 0}};
#pragma unroll
          for (int e = 0; e < NC; e++) gate[e] = GB;
#pragma unroll
          for (int G = 0; G < 20; G++) {
            if (G == 16 && !big) break;
            if (G % (z2.value ? LD2 : LD1) == 0) { gb = gn; if (G < 20 - (z2.value ? LD2 : LD1)) asm volatile("ld.f32 %0, [%1];" : "=f"(gn) : "l"(gbp) : "memory"); }
#pragma unroll
            for (int r = 0; r < 2; r++) {
              float z[2];
              float& gt = gate[(G * 2 + r) % NC];
#pragma unroll
              for (int e = 0; e < 2; e++) {
                const float v = acc[4 * G + 2 * r + e];
                z[e] = fmaf(v, tanh_fast(v * fmaf(v, v, gt)), v);
                if (z2.value) { s[r] = fmaf(z[e], 0x1p-60f, s[r]); qq[r] = fmaf(z[e], z[e], qq[r]); }
              }
              const uint32_t pk = pack2(z[0], z[1]);
              if (z2.value) {
                stg32(zd + G * 128 + r * 4608, hsub2(pk, off2));
                gt = fmaf(qq[r], s[r], gb);
              } else {
                gt = fmaf(__uint_as_float(pk), 0x1p-60f, gb);
                if ((G & 3) == 3) stg128(zd + (G >> 2) * 4096 + r * (8 * ZB), qa[r][0], qa[r][1], qa[r][2], pk);
                else qa[r][G & 3] = pk;
              }
            }
          }
        };
#pragma unroll 1
        for (int mb = 0;; mb++) {
          if (half) gelu(Int<0>{}); else gelu(Int<1>{});
          if (mb) break;
          zstat(0, !half);
#pragma unroll
          for (int i = 0; i < 80; i++) acc[i] = acc[80 + i];
          zd += half ? 1024 : 128 * ZB;
        }
        signal(half ? EV_Z1 : EV_ZN);
        SCLK(half * 11 + 10);
        TRC(tr, w, tb + 8 + half * 4);
      }
      }
      uint32_t hA[18][4];
      {
        float acc[144];
        const float c0 = __uint_as_float(lds32(sb + SM_OFF + 4));
#pragma unroll
        for (int i = 0; i < 144; i++) {
          asm volatile("fma.rn.f32 %0, %1, %2, %3;" : "=f"(acc[i]) : "f"(__uint_as_float(Q.zero)), "f"((float)(i + 2)), "f"(c0));
        }
        uint32_t prev = 0;
        auto stage = [&](int kb) {
          mbar_wait_c(bars + B_FULL + c.s * 8, c.ph);
          TRC(tr && kb == 0, w, tb + 13);
          SCLK(22 + kb);
          const uint32_t st = sb + c.s * ST_BYTES, db = dlo(st + ST_B, 4608), rt = sb + SM_RT + kb * 128 + t * 8;
          uint32_t a[4][4];
#pragma unroll
          for (int kk = 0; kk < 4; kk++) {
            uint32_t r[4];
            ldsm4(r, st + (aoff ^ (kk << 5)));
            const uint2 sc = lds64(rt + kk * 32);
            a[kk][0] = hmul2(__byte_perm(r[0], r[2], 0x5410), sc.x); a[kk][2] = hmul2(__byte_perm(r[0], r[2], 0x7632), sc.y);
            a[kk][1] = hmul2(__byte_perm(r[1], r[3], 0x5410), sc.x); a[kk][3] = hmul2(__byte_perm(r[1], r[3], 0x7632), sc.y);
          }
          if (kb + w == 0) bar_sync(6, 256);
          wgmma_fence();
#pragma unroll
          for (int i = 0; i < 8; i++) {
            const int kk = i & 3, hf = i >> 2;
            wgmma_rs_n144(acc + hf * 72, a[kk], dsc<128, 0>(db, kk * 9216 + hf * 2304), 1);
            if (i == 0) { wgmma_commit(); wgmma_wait<1>(); if (kb) release(prev); }
            if (i == 3) wgmma_commit();
          }
          wgmma_commit();
          prev = c.s; c.next();
        };
#pragma unroll 1
        for (int kb = 0; kb < 32; kb += 2) {
          if (!(kb & 7)) mbar_wait_c(bars + B_RT + kb, L);
          stage(kb);
          stage(kb + 1);
        }
        mbar_wait_c(bars + B_CV + w * 8, L);
        const float gk = 0.5f / GA;
        const float c1 = __uint_as_float(lds32(sb + SM_OFF + 4));
        const float gb0 = -gk * (c1 + __uint_as_float(lds32(sb + SM_CV + w * 256 + (16 * q + g) * 4))), gb1 = -gk * (c1 + __uint_as_float(lds32(sb + SM_CV + w * 256 + (16 * q + g + 8) * 4)));
        if (w == 1) { mbar_wait_c(bars + B_FULL + c.s * 8, c.ph); release(c.s); c.next(); }
        mbar_wait_c(bars + B_FULL + c.s * 8, c.ph);
        const uint32_t zs = sb + c.s * ST_BYTES + ST_B + (tid & 127) * 16;
        uint4 zl, zh;
#pragma unroll
        for (int u = 0; u < 18; u++) {
          if (u == 0) wgmma_wait<1>();
          if (u == 9) {
            wgmma_wait<0>();
            release(prev);
            if (L == 0) signal(EV_PT);
            TRC(tr, w, tb + 14);
            SCLK(54);
          }
          if (!(u & 1)) { zl = lds128(zs + u * 2048); zh = lds128(zs + u * 2048 + 2048); }
          const uint4 z = (u & 1) ? make_uint4(zl.z, zh.z, zl.w, zh.w) : make_uint4(zl.x, zh.x, zl.y, zh.y);
          hA[u][0] = hmul2(z.x, pack2(fmaf(acc[8 * u], gk, gb0), fmaf(acc[8 * u + 1], gk, gb0)));
          hA[u][1] = hmul2(z.y, pack2(fmaf(acc[8 * u + 2], gk, gb1), fmaf(acc[8 * u + 3], gk, gb1)));
          hA[u][2] = hmul2(z.z, pack2(fmaf(acc[8 * u + 4], gk, gb0), fmaf(acc[8 * u + 5], gk, gb0)));
          hA[u][3] = hmul2(z.w, pack2(fmaf(acc[8 * u + 6], gk, gb1), fmaf(acc[8 * u + 7], gk, gb1)));
        }
        __syncwarp();
        release(c.s);
        c.next();
        if (w == 0) { mbar_wait_c(bars + B_FULL + c.s * 8, c.ph); release(c.s); c.next(); }
        TRC(tr, w, tb + 15);
      }
      {
        CLK_INIT;
        if (w == 1) bar_arrive(6, 256);
        uint32_t pk[16];
#pragma unroll
        for (int i = 0; i < 16; i++) pk[i] = 0u;
        auto dump = [&](int p) {
          const uint32_t d = sb + (p & 3) * ST_BYTES, cb = p + j >= 9 ? p + j - 9 : p + j;
          if (lane == 0) asm volatile("cp.async.bulk.wait_group.read 3;" ::: "memory");
          __syncwarp();
#pragma unroll
          for (int u = 0; u < 4; u++) stsm4(d + (aoff ^ (u << 5)), pk[4 * u], pk[4 * u + 1], pk[4 * u + 2], pk[4 * u + 3]);
          fence_async_s();
          __syncwarp();
          tma3d_red_p(lane == 0, &P.red, cb * 64, rb * 64 + q * 16, w, d + w * 8192 + q * 2048);
        };
#pragma unroll 1
        for (int p = 0; p < 9; p++) {
          float acc[32];
          CLK(0);
          mbar_wait_c(bars + B_FULL + c.s * 8, c.ph);
          const uint32_t db = dlo(sb + c.s * ST_BYTES + ST_B, 0);
          CLK(1);
          bar_sync(6 + w, 256);
          CLK(2);
          wgmma_fence();
#pragma unroll
          for (int kk = 0; kk < 18; kk++) {
            wgmma_rs_n64(acc, hA[kk], dsc<1024, 1>(db, kk * 2048), kk != 0);
            if (kk == PPK && (w == 0 || p < 8)) bar_arrive(7 - w, 256);
          }
          wgmma_commit();
          CLK(3);
          if (p > 0) dump(p - 1);
          CLK(5);
          wgmma_wait<0>();
          CLK(4);
          if (L == 0 || p < 5) release(c.s);
          c.next();
#pragma unroll
          for (int i = 0; i < 16; i++) pk[i] = pack2(acc[2 * i], acc[2 * i + 1]);
          if (p == 8) { TRC(tr, w, tb + 16); dump(8); TRC(tr, w, tb + 17); }
        }
        if (lane == 0) asm volatile("cp.async.bulk.wait_group 0;" ::: "memory");
        if (L == 0) signal(EV_PT);
        CLK_OUT;
        TRC(tr, w, tb + 18);
      }
    }
    if ((tid & 127) == 0) Q.flags[(rb * 2 + w) * 32 + FR_EP + j] = epoch + 1;
    if (tid == 0) Q.flags[FJ + j * 32 + FJ_EP + rb] = epoch + 1;
  }
}

typedef CUresult (*EncodeFn)(CUtensorMap*, CUtensorMapDataType, cuuint32_t, void*, const cuuint64_t*, const cuuint64_t*, const cuuint32_t*,
                             const cuuint32_t*, CUtensorMapInterleave, CUtensorMapSwizzle, CUtensorMapL2promotion, CUtensorMapFloatOOBfill);

static void make_map(EncodeFn fn, CUtensorMap* m, const void* ptr, int rank, uint64_t d0, uint64_t d1, uint64_t d2, uint64_t s1, uint64_t s2,
                     uint32_t b0, uint32_t b1, uint32_t b2, CUtensorMapSwizzle swz) {
  cuuint64_t dims[3] = {d0, d1, d2}, strides[2] = {s1, s2};
  cuuint32_t box[3] = {b0, b1, b2}, es[3] = {1, 1, 1};
  fn(m, CU_TENSOR_MAP_DATA_TYPE_BFLOAT16, rank, const_cast<void*>(ptr), dims, strides, box, es, CU_TENSOR_MAP_INTERLEAVE_NONE, swz,
     CU_TENSOR_MAP_L2_PROMOTION_L2_128B, CU_TENSOR_MAP_FLOAT_OOB_FILL_NONE);
}

}

extern "C" void kernel_launch(void* const* d_in, const int* in_sizes, int n_in, void* d_out, int out_size) {
  using namespace mk;
  (void)in_sizes; (void)n_in; (void)out_size;
  static EncodeFn fn = nullptr;
  static Scratch* sc = nullptr;
  if (!fn) {
    cudaDriverEntryPointQueryResult qr;
    cudaGetDriverEntryPoint("cuTensorMapEncodeTiled", (void**)&fn, cudaEnableDefault, &qr);
    cudaGetSymbolAddress((void**)&sc, g_scratch);
    cudaFuncSetAttribute(mega_kernel, cudaFuncAttributeMaxDynamicSharedMemorySize, SM_TOTAL);
  }
  Params p;
  Ptrs a;
  a.x = (const uint8_t*)d_in[0];
  a.wqkv = (const __nv_bfloat16*)d_in[1];
  a.wo = (const __nv_bfloat16*)d_in[2];
  a.w_in = (const __nv_bfloat16*)d_in[4];
  a.w_sp = (const __nv_bfloat16*)d_in[5];
  a.b_sp = (const __nv_bfloat16*)d_in[6];
  a.out = (uint8_t*)d_out;
  a.zero = 0;
  a.WQ = sc->WQ; a.flags = sc->flags; a.CSP = sc->CSP; a.XST = sc->XST; a.HALO = sc->HALO; a.ST1 = sc->ST1; a.ZST = sc->ZST; a.RT = sc->RT; a.Z = sc->Z; a.WO = sc->WO;
  make_map(fn, &p.wsp, a.w_sp, 3, 2048, 1024, 2, 8192, 4096, 64, 64, 2, CU_TENSOR_MAP_SWIZZLE_128B);
  for (int i = 0; i < 2; i++) {
    make_map(fn, &p.act[i], i ? a.out : a.x, 3, DM, 1024, 2, 2304, 1152, 64, 64, 1, CU_TENSOR_MAP_SWIZZLE_128B);
    make_map(fn, &p.row[i], i ? a.out : a.x, 3, 192, 6, 1024, 384, 2304, 192, 3, 8, CU_TENSOR_MAP_SWIZZLE_NONE);
    make_map(fn, &p.res[i], i ? a.out : a.x, 3, DM, 1024, 2, 2304, 1152, 72, 32, 2, CU_TENSOR_MAP_SWIZZLE_NONE);
  }
  make_map(fn, &p.red, d_out, 3, DM, 1024, 2, 2304, 1152, 64, 16, 1, CU_TENSOR_MAP_SWIZZLE_128B);
  for (int i = 0; i < 2; i++) make_map(fn, &p.winb[i], a.w_in + 32 * i, 3, 64, 576, 72 - i, 9216, 128, 64, 16, 3, CU_TENSOR_MAP_SWIZZLE_128B);
  make_map(fn, &p.wins, a.w_in, 3, 64, 576, 72, 9216, 128, 64, 48, 1, CU_TENSOR_MAP_SWIZZLE_128B);
  make_map(fn, &p.wout, d_in[7], 2, 576, 2304, 1, 1152, 0, 64, 144, 1, CU_TENSOR_MAP_SWIZZLE_128B);
  mega_kernel<<<NGRID, 384, SM_TOTAL, cudaStreamPerThread>>>(a, p);
}
```

```cpp
#include <cuda_runtime.h>
#include <cuda.h>
#include <cuda_bf16.h>
#include <stdint.h>

#define MK_TRACE 0
#define MK_DBG 0
#define P5TRACE 0
#define LAG1 1
#define C0S 32.f
#define OFM 0x10u
#define NC2 2
#define NC1 6
#define XRLX 0
#define PDEL 8
#define LD1 4
#define LD2 2
#define ZD1 8
#define ZD2 20
#define WPF 1
#define YPACE 2
#define HO2 8
#define SPL 4
#define XP0 0
#define EFM 0x33333022
#define EF(i) ((((EFM >> (4 * (i))) & 3) == 3) || (((EFM >> (4 * (i))) >> L) & 1))
#define AEP 2
#define PZI 4
#define P2L 1
#define KS 1
#define RFI 3
#define XK1 1
#define XK2 2
#define SDEL 10
#define FD0 0
#define FD1 0
#define FD2 0
#define FD3 14
#define FD4 0
#define FD5 0
#define APACE 7
#define HO3 1
#define PPK 13

namespace mk {

constexpr int SEQ = 2048, DM = 576, FH = 2304;
constexpr int NCTA = 128;
constexpr int NGRID = 132;
constexpr uint32_t ZB = 36864;
constexpr uint32_t WQ_SL = 72 * 3456;
constexpr uint32_t WO_SL = 72 * 1152;
constexpr float LN_EPS = 1e-5f;
constexpr float GA = 0.3292034911525734f, GB = 2.423681954311584f;

constexpr uint32_t ST_BYTES = 53248, ST_B = 16384, NST = 4;
constexpr uint32_t SM_STG = NST * ST_BYTES;
constexpr uint32_t SM_BAR = SM_STG + 2 * 9216, B_OFF = 896;
constexpr uint32_t SM_OFF = SM_BAR + B_OFF;
constexpr uint32_t SM_TOTAL = SM_BAR + 1024;
constexpr uint32_t SM_RT = SM_STG + 9216, SM_CV = SM_STG + 17408, SM_WT = SM_STG;
constexpr uint32_t SM_WOI = 44032, SM_CSQ = 49280, SM_XST = 50176;
enum { EV_PT = 0, EV_O = 1, EV_X1 = 2, EV_ZN = 3, EV_Z1 = 4, EV_XS = 5, EV_N = 6 };
constexpr uint32_t B_FULL = 0, B_FULLA = 32, B_RES = 96, B_WT = 112, B_GATE3 = 128, B_Z1 = 136, B_ZOK = 144, B_CV = 152, B_XRW = 168, B_F3 = 184, B_WF = 232, B_OF = 240,
                   B_RT = 320, B_AF3 = 352, B_RB = 544,
                   B_AD = 576, B_S5 = 608, B_AV = 616,
                   B_CSQ = 760,
                   B_LAG = 768, B_X3 = 776, B_ZS = 784, B_EVT = 800,
                   B_IMG = 912, B_WOI = 920, B_E3 = 928, B_XD = 976,
                   B_EMPTY = 992;
constexpr uint32_t SM_B3 = 9 * 16384, SM_ZP3 = SM_STG + 8192;

enum { FR_X2 = 0, FR_O = 1, FR_X1 = 3, FR_XR = 5, FR_OL = 7, FR_PZ = 9, FR_EP = 16, FJ = 32 * 32, FJ_WQ = 0, FJ_WO = 1, FJ_ZN = 3, FJ_P4 = 5, FJ_EP = 16, F_N = FJ + 8 * 32 };

struct Scratch {
  alignas(1024) uint32_t flags[F_N];
  alignas(1024) float CSP[2 * NCTA * 216];
  alignas(1024) uint2 RT[SEQ];
  alignas(1024) uint4 XST[2 * SEQ];
  alignas(1024) uint4 ST1[SEQ * 4];
  alignas(1024) uint4 ZST[SEQ * 4];
  alignas(1024) uint4 HALO[32 * 8 * 6 * 32];
  alignas(1024) uint8_t WO[8 * WO_SL];
  alignas(1024) uint8_t WQ[8 * WQ_SL];
  alignas(1024) uint8_t Z[576 * ZB];
};
__device__ Scratch g_scratch;

struct Ptrs {
  const __nv_bfloat16* wqkv;
  uint8_t* WQ;
  uint32_t* flags;
  float* CSP;
  const uint8_t* x;
  uint32_t zero;
  uint4 *XST, *HALO, *ST1, *ZST;
  uint2* RT;
  uint8_t *Z, *WO, *out;
  const __nv_bfloat16 *wo, *w_in, *w_sp, *b_sp;
};
struct Params {
  CUtensorMap wsp, winb[2], wins, wout;
  CUtensorMap act[2];
  CUtensorMap res[2];
  CUtensorMap row[2];
  CUtensorMap red;
};

__device__ __forceinline__ uint32_t smem_u32(const void* p) { return (uint32_t)__cvta_generic_to_shared(p); }
__device__ __forceinline__ void mbar_init(uint32_t bar, uint32_t cnt) { asm volatile("mbarrier.init.shared::cta.b64 [%0], %1;" ::"r"(bar), "r"(cnt)); }
__device__ __forceinline__ void mbar_arrive(uint32_t bar) { asm volatile("mbarrier.arrive.shared::cta.b64 _, [%0];" ::"r"(bar) : "memory"); }
__device__ __forceinline__ void mbar_wait(uint32_t bar, uint32_t parity) {
  asm volatile(
      "{\n.reg .pred p;\n.reg .u32 c;\nmov.u32 c, 0;\nLAB_WAIT:\n"
      "mbarrier.try_wait.parity.shared::cta.b64 p, [%0], %1;\n@p bra LAB_DONE;\n"
      "add.u32 c, c, 1;\nsetp.lt.u32 p, c, 0x100000;\n@p bra LAB_WAIT;\ntrap;\nLAB_DONE:\n}" ::"r"(bar), "r"(parity)
      : "memory");
}
__device__ __forceinline__ void mbar_wait_c(uint32_t bar, uint32_t parity) {
  asm volatile("{\n.reg .pred p;\nLAB_WAIT:\nmbarrier.try_wait.parity.shared::cta.b64 p, [%0], %1;\n@!p bra LAB_WAIT;\n}" ::"r"(bar), "r"(parity) : "memory");
}
__device__ __forceinline__ void flag_wait(const uint32_t* f, uint32_t target) {
  asm volatile(
      "{\n.reg .pred p;\n.reg .u32 c, v;\nmov.u32 c, 0;\nLAB_WAIT:\n"
      "ld.relaxed.gpu.global.u32 v, [%0];\nsub.u32 v, v, %1;\nsetp.ge.s32 p, v, 0;\n@p bra LAB_DONE;\n"
      "add.u32 c, c, 1;\nsetp.lt.u32 p, c, 0x400000;\n@p bra LAB_WAIT;\ntrap;\nLAB_DONE:\nfence.acquire.gpu;\n}" ::"l"(f), "r"(target)
      : "memory");
}
__device__ __forceinline__ void fence_gpu() { asm volatile("fence.acq_rel.gpu;" ::: "memory"); }
__device__ __forceinline__ void fence_async_g() { asm volatile("fence.proxy.async.global;" ::: "memory"); }
__device__ __forceinline__ void fence_async_s() { asm volatile("fence.proxy.async.shared::cta;" ::: "memory"); }
__device__ __forceinline__ uint32_t elect_one() {
  uint32_t p; asm volatile("{\n.reg .pred P;\nelect.sync _|P, 0xffffffff;\nselp.u32 %0, 1, 0, P;\n}" : "=r"(p)); return p;
}
__device__ __forceinline__ void expect_tx_p(uint32_t el, uint32_t bar, uint32_t bytes) {
  asm volatile("{\n.reg .pred P;\nsetp.ne.u32 P, %2, 0;\n@P mbarrier.arrive.expect_tx.shared::cta.b64 _, [%0], %1;\n}" ::"r"(bar), "r"(bytes), "r"(el) : "memory");
}
__device__ __forceinline__ void bulk_load_p(uint32_t el, uint32_t dst, const void* src, uint32_t bytes, uint32_t bar) {
  asm volatile("{\n.reg .pred P;\nsetp.ne.u32 P, %4, 0;\n@P cp.async.bulk.shared::cluster.global.mbarrier::complete_tx::bytes [%0], [%1], %2, [%3];\n}" ::"r"(dst), "l"(src), "r"(bytes), "r"(bar), "r"(el) : "memory");
}
__device__ __forceinline__ uint64_t policy_evict_first() { uint64_t p; asm("createpolicy.fractional.L2::evict_first.b64 %0, 1.0;" : "=l"(p)); return p; }
__device__ __forceinline__ void bulk_load_h(uint32_t el, uint32_t dst, const void* src, uint32_t bytes, uint32_t bar, bool ef, uint64_t pol) {
  if (ef) {
    asm volatile("{\n.reg .pred P;\nsetp.ne.u32 P, %4, 0;\n@P cp.async.bulk.shared::cluster.global.mbarrier::complete_tx::bytes.L2::cache_hint [%0], [%1], %2, [%3], %5;\n}" ::"r"(dst), "l"(src), "r"(bytes), "r"(bar), "r"(el), "l"(pol) : "memory");
  } else {
    asm volatile("{\n.reg .pred P;\nsetp.ne.u32 P, %4, 0;\n@P cp.async.bulk.shared::cluster.global.mbarrier::complete_tx::bytes [%0], [%1], %2, [%3];\n}" ::"r"(dst), "l"(src), "r"(bytes), "r"(bar), "r"(el) : "memory");
  }
}
__device__ __forceinline__ void bulk_mc_h(uint32_t el, uint32_t dst, const void* src, uint32_t bytes, uint32_t bar, bool ef, uint64_t pol) {
  if (ef) {
    asm volatile("{\n.reg .pred P;\nsetp.ne.u32 P, %4, 0;\n@P cp.async.bulk.shared::cluster.global.mbarrier::complete_tx::bytes.multicast::cluster.L2::cache_hint [%0], [%1], %2, [%3], %5, %6;\n}" ::"r"(dst), "l"(src), "r"(bytes), "r"(bar), "r"(el), "h"((uint16_t)3), "l"(pol) : "memory");
  } else {
    asm volatile("{\n.reg .pred P;\nsetp.ne.u32 P, %4, 0;\n@P cp.async.bulk.shared::cluster.global.mbarrier::complete_tx::bytes.multicast::cluster [%0], [%1], %2, [%3], %5;\n}" ::"r"(dst), "l"(src), "r"(bytes), "r"(bar), "r"(el), "h"((uint16_t)3) : "memory");
  }
}
__device__ __forceinline__ void tma3d_h(uint32_t el, uint32_t dst, const CUtensorMap* m, int c0, int c1, int c2, uint32_t bar, bool ef, uint64_t pol) {
  if (ef) {
    asm volatile("{\n.reg .pred P;\nsetp.ne.u32 P, %6, 0;\n@P cp.async.bulk.tensor.3d.shared::cluster.global.mbarrier::complete_tx::bytes.L2::cache_hint [%0], [%1, {%3, %4, %5}], [%2], %7;\n}" ::"r"(dst), "l"(m), "r"(bar), "r"(c0), "r"(c1), "r"(c2), "r"(el), "l"(pol) : "memory");
  } else {
    asm volatile("{\n.reg .pred P;\nsetp.ne.u32 P, %6, 0;\n@P cp.async.bulk.tensor.3d.shared::cluster.global.mbarrier::complete_tx::bytes [%0], [%1, {%3, %4, %5}], [%2];\n}" ::"r"(dst), "l"(m), "r"(bar), "r"(c0), "r"(c1), "r"(c2), "r"(el) : "memory");
  }
}
__device__ __forceinline__ void tma2d_mc_h(uint32_t el, uint32_t dst, const CUtensorMap* m, int c0, int c1, uint32_t bar, bool ef, uint64_t pol) {
  if (ef) {
    asm volatile("{\n.reg .pred P;\nsetp.ne.u32 P, %5, 0;\n@P cp.async.bulk.tensor.2d.shared::cluster.global.mbarrier::complete_tx::bytes.multicast::cluster.L2::cache_hint [%0], [%1, {%3, %4}], [%2], %6, %7;\n}" ::"r"(dst), "l"(m), "r"(bar), "r"(c0), "r"(c1), "r"(el), "h"((uint16_t)3), "l"(pol) : "memory");
  } else {
    asm volatile("{\n.reg .pred P;\nsetp.ne.u32 P, %5, 0;\n@P cp.async.bulk.tensor.2d.shared::cluster.global.mbarrier::complete_tx::bytes.multicast::cluster [%0], [%1, {%3, %4}], [%2], %6;\n}" ::"r"(dst), "l"(m), "r"(bar), "r"(c0), "r"(c1), "r"(el), "h"((uint16_t)3) : "memory");
  }
}
__device__ __forceinline__ void tma3d_mc_h(uint32_t el, uint32_t dst, const CUtensorMap* m, int c0, int c1, int c2, uint32_t bar, bool ef, uint64_t pol) {
  if (ef) {
    asm volatile("{\n.reg .pred P;\nsetp.ne.u32 P, %6, 0;\n@P cp.async.bulk.tensor.3d.shared::cluster.global.mbarrier::complete_tx::bytes.multicast::cluster.L2::cache_hint [%0], [%1, {%3, %4, %5}], [%2], %7, %8;\n}" ::"r"(dst), "l"(m), "r"(bar), "r"(c0), "r"(c1), "r"(c2), "r"(el), "h"((uint16_t)3), "l"(pol) : "memory");
  } else {
    asm volatile("{\n.reg .pred P;\nsetp.ne.u32 P, %6, 0;\n@P cp.async.bulk.tensor.3d.shared::cluster.global.mbarrier::complete_tx::bytes.multicast::cluster [%0], [%1, {%3, %4, %5}], [%2], %7;\n}" ::"r"(dst), "l"(m), "r"(bar), "r"(c0), "r"(c1), "r"(c2), "r"(el), "h"((uint16_t)3) : "memory");
  }
}
__device__ __forceinline__ void mbar_arrive_cluster(uint32_t addr) { asm volatile("mbarrier.arrive.shared::cluster.b64 _, [%0];" ::"r"(addr) : "memory"); }
__device__ __forceinline__ uint32_t mapa(uint32_t addr, uint32_t rank) { uint32_t r; asm("mapa.shared::cluster.u32 %0, %1, %2;" : "=r"(r) : "r"(addr), "r"(rank)); return r; }
__device__ __forceinline__ void bulk_store_p(uint32_t el, void* dst, uint32_t src, uint32_t bytes) {
  asm volatile("{\n.reg .pred P;\nsetp.ne.u32 P, %3, 0;\n@P cp.async.bulk.global.shared::cta.bulk_group [%0], [%1], %2;\n}" ::"l"(dst), "r"(src), "r"(bytes), "r"(el) : "memory");
}
__device__ __forceinline__ void flag_release_p(uint32_t el, uint32_t* f) {
  asm volatile("{\n.reg .pred P;\nsetp.ne.u32 P, %1, 0;\nfence.proxy.async;\n@P red.relaxed.gpu.global.add.u32 [%0], 1;\n}" ::"l"(f), "r"(el) : "memory");
}
__device__ __forceinline__ void flag_add_p(uint32_t el, uint32_t* f) {
  asm volatile("{\n.reg .pred P;\nsetp.ne.u32 P, %1, 0;\n@P red.relaxed.gpu.global.add.u32 [%0], 1;\n}" ::"l"(f), "r"(el) : "memory");
}
__device__ __forceinline__ void prefetch_l2(const void* src, uint32_t bytes) { asm volatile("cp.async.bulk.prefetch.L2.global [%0], %1;" ::"l"(src), "r"(bytes) : "memory"); }
__device__ __forceinline__ void prefetch_map(const CUtensorMap* m) { asm volatile("prefetch.tensormap [%0];" ::"l"(m) : "memory"); }
__device__ __forceinline__ void wgmma_fence() { asm volatile("wgmma.fence.sync.aligned;" ::: "memory"); }
__device__ __forceinline__ void wgmma_commit() { asm volatile("wgmma.commit_group.sync.aligned;" ::: "memory"); }
template <int N> __device__ __forceinline__ void wgmma_wait() { asm volatile("wgmma.wait_group.sync.aligned %0;" ::"n"(N) : "memory"); }
__device__ __forceinline__ uint32_t dlo(uint32_t addr, uint32_t lbo) { return ((addr & 0x3FFFF) >> 4) + ((lbo >> 4) << 16); }
template <uint32_t SBO, uint32_t SWZ> __device__ __forceinline__ uint64_t dsc(uint32_t lo, uint32_t off) {
  uint64_t d; asm("mov.b64 %0, {%1, %2};" : "=l"(d) : "r"(lo + (off >> 4)), "n"((SBO >> 4) | (SWZ << 30))); return d;
}
template <int R> __device__ __forceinline__ void reg_alloc() { asm volatile("setmaxnreg.inc.sync.aligned.u32 %0;" ::"n"(R)); }
template <int R> __device__ __forceinline__ void reg_dealloc() { asm volatile("setmaxnreg.dec.sync.aligned.u32 %0;" ::"n"(R)); }
__device__ __forceinline__ void bar_sync(int id, int n) { asm volatile("bar.sync %0, %1;" ::"r"(id), "r"(n) : "memory"); }
__device__ __forceinline__ void bar_arrive(int id, int n) { asm volatile("bar.arrive %0, %1;" ::"r"(id), "r"(n) : "memory"); }
__device__ __forceinline__ void ldsm4(uint32_t* r, uint32_t addr) {
  asm volatile("ldmatrix.sync.aligned.m8n8.x4.shared.b16 {%0,%1,%2,%3}, [%4];" : "=r"(r[0]), "=r"(r[1]), "=r"(r[2]), "=r"(r[3]) : "r"(addr) : "memory");
}
__device__ __forceinline__ uint32_t movm(uint32_t a) { uint32_t d; asm volatile("movmatrix.sync.aligned.m8n8.trans.b16 %0, %1;" : "=r"(d) : "r"(a)); return d; }
__device__ __forceinline__ void mma16(float* c, uint32_t a0, uint32_t a1, uint32_t a2, uint32_t a3, uint32_t b0, uint32_t b1) {
  asm volatile("mma.sync.aligned.m16n8k16.row.col.f32.bf16.bf16.f32 {%0,%1,%2,%3}, {%4,%5,%6,%7}, {%8,%9}, {%0,%1,%2,%3};"
               : "+f"(c[0]), "+f"(c[1]), "+f"(c[2]), "+f"(c[3]) : "r"(a0), "r"(a1), "r"(a2), "r"(a3), "r"(b0), "r"(b1));
}
__device__ __forceinline__ void mma8(float* c, uint32_t a0, uint32_t a1, uint32_t b0) {
  asm volatile("mma.sync.aligned.m16n8k8.row.col.f32.bf16.bf16.f32 {%0,%1,%2,%3}, {%4,%5}, {%6}, {%0,%1,%2,%3};"
               : "+f"(c[0]), "+f"(c[1]), "+f"(c[2]), "+f"(c[3]) : "r"(a0), "r"(a1), "r"(b0));
}
__device__ __forceinline__ uint32_t pack2(float lo, float hi) { uint32_t r; asm("cvt.rn.bf16x2.f32 %0, %1, %2;" : "=r"(r) : "f"(hi), "f"(lo)); return r; }
__device__ __forceinline__ float blo(uint32_t v) { return __uint_as_float(v << 16); }
__device__ __forceinline__ float bhi(uint32_t v) { return __uint_as_float(v & 0xffff0000u); }
__device__ __forceinline__ float tanh_fast(float x) { float y; asm("tanh.approx.f32 %0, %1;" : "=f"(y) : "f"(x)); return y; }
__device__ __forceinline__ float rcp_fast(float x) { float y; asm("rcp.approx.ftz.f32 %0, %1;" : "=f"(y) : "f"(x)); return y; }
__device__ __forceinline__ float rsq_fast(float x) { float y; asm("rsqrt.approx.ftz.f32 %0, %1;" : "=f"(y) : "f"(x)); return y; }
__device__ __forceinline__ float ex2(float x) { float y; asm("ex2.approx.ftz.f32 %0, %1;" : "=f"(y) : "f"(x)); return y; }
__device__ __forceinline__ float qsum(float v) { v += __shfl_xor_sync(~0u, v, 1); v += __shfl_xor_sync(~0u, v, 2); return v; }
__device__ __forceinline__ float qmax(float v) { v = fmaxf(v, __shfl_xor_sync(~0u, v, 1)); v = fmaxf(v, __shfl_xor_sync(~0u, v, 2)); return v; }
__device__ __forceinline__ void stg32(void* p, uint32_t v) { asm volatile("st.global.u32 [%0], %1;" ::"l"(p), "r"(v) : "memory"); }
__device__ __forceinline__ void stg128(void* p, uint32_t a, uint32_t b, uint32_t c, uint32_t d) { asm volatile("st.global.v4.u32 [%0], {%1,%2,%3,%4};" ::"l"(p), "r"(a), "r"(b), "r"(c), "r"(d) : "memory"); }
__device__ __forceinline__ uint32_t ldcg32(const void* p) { uint32_t v; asm volatile("ld.global.L1::no_allocate.u32 %0, [%1];" : "=r"(v) : "l"(p) : "memory"); return v; }
__device__ __forceinline__ void stg128_if(bool c, void* p, uint32_t a, uint32_t b, uint32_t cc, uint32_t d) {
  asm volatile("{\n.reg .pred P;\nsetp.ne.u32 P, %5, 0;\n@P st.global.v4.u32 [%0], {%1,%2,%3,%4};\n}" ::"l"(p), "r"(a), "r"(b), "r"(cc), "r"(d), "r"((uint32_t)c) : "memory");
}
__device__ __forceinline__ uint2 lds64(uint32_t a) { uint2 v; asm volatile("ld.shared.v2.u32 {%0,%1}, [%2];" : "=r"(v.x), "=r"(v.y) : "r"(a) : "memory"); return v; }
__device__ __forceinline__ uint4 ldcg128(const void* p) { uint4 v; asm volatile("ld.global.cg.v4.u32 {%0,%1,%2,%3}, [%4];" : "=r"(v.x), "=r"(v.y), "=r"(v.z), "=r"(v.w) : "l"(p) : "memory"); return v; }
__device__ __forceinline__ uint32_t ldnc16(const void* p) { uint16_t v; asm volatile("ld.global.nc.u16 %0, [%1];" : "=h"(v) : "l"(p)); return v; }
__device__ __forceinline__ uint4 ldnc128(const void* p) { uint4 v; asm volatile("ld.global.nc.v4.u32 {%0,%1,%2,%3}, [%4];" : "=r"(v.x), "=r"(v.y), "=r"(v.z), "=r"(v.w) : "l"(p)); return v; }
__device__ __forceinline__ void cp_async16(uint32_t dst, const void* src) { asm volatile("cp.async.cg.shared.global [%0], [%1], 16;" ::"r"(dst), "l"(src) : "memory"); }
__device__ __forceinline__ uint32_t hsub2(uint32_t a, uint32_t b) { uint32_t d; asm("sub.rn.bf16x2 %0, %1, %2;" : "=r"(d) : "r"(a), "r"(b)); return d; }
__device__ __forceinline__ void stg32_if(bool c, void* p, uint32_t v) {
  asm volatile("{\n.reg .pred P;\nsetp.ne.u32 P, %2, 0;\n@P st.global.u32 [%0], %1;\n}" ::"l"(p), "r"(v), "r"((uint32_t)c) : "memory");
}
__device__ __forceinline__ float wsum(float v) { for (int o = 16; o; o >>= 1) v += __shfl_xor_sync(~0u, v, o); return v; }
__device__ __forceinline__ uint32_t hmul2(uint32_t a, uint32_t b) { uint32_t d; asm("mul.rn.bf16x2 %0, %1, %2;" : "=r"(d) : "r"(a), "r"(b)); return d; }
__device__ __forceinline__ void sts32(uint32_t a, uint32_t v) { asm volatile("st.shared.u32 [%0], %1;" ::"r"(a), "r"(v) : "memory"); }
__device__ __forceinline__ uint32_t lds32(uint32_t a) { uint32_t v; asm volatile("ld.shared.u32 %0, [%1];" : "=r"(v) : "r"(a) : "memory"); return v; }
__device__ __forceinline__ void sts128(uint32_t a, uint32_t x, uint32_t y, uint32_t z, uint32_t w) { asm volatile("st.shared.v4.u32 [%0], {%1,%2,%3,%4};" ::"r"(a), "r"(x), "r"(y), "r"(z), "r"(w) : "memory"); }
__device__ __forceinline__ uint4 lds128(uint32_t a) { uint4 v; asm volatile("ld.shared.v4.u32 {%0,%1,%2,%3}, [%4];" : "=r"(v.x), "=r"(v.y), "=r"(v.z), "=r"(v.w) : "r"(a) : "memory"); return v; }
__device__ __forceinline__ void ll_st64(uint2* p, uint32_t v, uint32_t tag) {
  asm volatile("{\n.reg .b64 r;\nmov.b64 r, {%1,%2};\nst.relaxed.gpu.global.b64 [%0], r;\n}" ::"l"(p), "r"(v), "r"(tag) : "memory");
}
__device__ __forceinline__ uint2 ll_ld64(const uint2* p) {
  uint2 v; asm volatile("{\n.reg .b64 r;\nld.relaxed.gpu.global.b64 r, [%2];\nmov.b64 {%0,%1}, r;\n}" : "=r"(v.x), "=r"(v.y) : "l"(p) : "memory"); return v;
}
__device__ __forceinline__ void ll_st128(uint4* p, float a, float b, uint32_t tag, float c = 0.f) {
  asm volatile("{\n.reg .b128 r;\n.reg .b64 lo, hi;\nmov.b64 lo, {%1,%2};\nmov.b64 hi, {%3,%4};\nmov.b128 r, {lo, hi};\nst.relaxed.gpu.global.b128 [%0], r;\n}" ::"l"(p), "r"(__float_as_uint(a)), "r"(__float_as_uint(b)), "r"(tag), "r"(__float_as_uint(c)) : "memory");
}
__device__ __forceinline__ uint4 ll_ld128g(const void* p) {
  uint4 v; asm volatile("{\n.reg .b128 r;\n.reg .b64 lo, hi;\nld.relaxed.gpu.b128 r, [%4];\nmov.b128 {lo, hi}, r;\nmov.b64 {%0,%1}, lo;\nmov.b64 {%2,%3}, hi;\n}" : "=r"(v.x), "=r"(v.y), "=r"(v.z), "=r"(v.w) : "l"(p) : "memory"); return v;
}
__device__ __forceinline__ uint4 ll_ld128(const uint4* p) {
  uint4 v; asm volatile("{\n.reg .b128 r;\n.reg .b64 lo, hi;\nld.relaxed.gpu.global.b128 r, [%4];\nmov.b128 {lo, hi}, r;\nmov.b64 {%0,%1}, lo;\nmov.b64 {%2,%3}, hi;\n}" : "=r"(v.x), "=r"(v.y), "=r"(v.z), "=r"(v.w) : "l"(p) : "memory"); return v;
}
__device__ __forceinline__ void publish_p(uint32_t el, uint32_t* f) {
  asm volatile("{\n.reg .pred P;\nsetp.ne.u32 P, %1, 0;\n@P cp.async.bulk.commit_group;\n@P cp.async.bulk.wait_group 0;\n@P red.release.gpu.global.add.u32 [%0], 1;\n}" ::"l"(f), "r"(el) : "memory");
}
__device__ __forceinline__ void tma3d_red_p(uint32_t el, const CUtensorMap* m, int c0, int c1, int c2, uint32_t src) {
  asm volatile("{\n.reg .pred P;\nsetp.ne.u32 P, %5, 0;\n@P cp.reduce.async.bulk.tensor.3d.global.shared::cta.add.tile.bulk_group [%0, {%2, %3, %4}], [%1];\n@P cp.async.bulk.commit_group;\n}" ::"l"(m), "r"(src), "r"(c0), "r"(c1), "r"(c2), "r"(el) : "memory");
}
__device__ __forceinline__ void stsm4(uint32_t addr, uint32_t a, uint32_t b, uint32_t c, uint32_t d) {
  asm volatile("stmatrix.sync.aligned.m8n8.x4.shared.b16 [%0], {%1,%2,%3,%4};" ::"r"(addr), "r"(a), "r"(b), "r"(c), "r"(d) : "memory");
}
__device__ __forceinline__ void sts64(uint32_t a, uint32_t x, uint32_t y) { asm volatile("st.shared.v2.u32 [%0], {%1,%2};" ::"r"(a), "r"(x), "r"(y) : "memory"); }
__device__ __forceinline__ void ll_st128_if(bool on, uint4* p, float a, float b, uint32_t tag) {
  asm volatile("{\n.reg .pred P;\n.reg .b128 r;\n.reg .b64 lo, hi;\nsetp.ne.u32 P, %4, 0;\nmov.b64 lo, {%1,%2};\nmov.b64 hi, {%3,%3};\nmov.b128 r, {lo, hi};\n@P st.relaxed.gpu.global.b128 [%0], r;\n}" ::"l"(p), "r"(__float_as_uint(a)), "r"(__float_as_uint(b)), "r"(tag), "r"((uint32_t)on) : "memory");
}
__device__ __forceinline__ uint4 ldnc128_if(bool c, const void* p) {
  uint4 v = make_uint4(0u, 0u, 0u, 0u);
  asm volatile("{\n.reg .pred P;\nsetp.ne.u32 P, %5, 0;\n@P ld.global.nc.v4.u32 {%0,%1,%2,%3}, [%4];\n}" : "+r"(v.x), "+r"(v.y), "+r"(v.z), "+r"(v.w) : "l"(p), "r"((uint32_t)c));
  return v;
}
__device__ __forceinline__ uint32_t hfma2(uint32_t a, uint32_t b, uint32_t c) { uint32_t d; asm("fma.rn.bf16x2 %0, %1, %2, %3;" : "=r"(d) : "r"(a), "r"(b), "r"(c)); return d; }
__device__ __forceinline__ float2 lds64f(uint32_t a) { float2 v; asm volatile("ld.shared.v2.f32 {%0,%1}, [%2];" : "=f"(v.x), "=f"(v.y) : "r"(a) : "memory"); return v; }
#define TRC(cond, role, idx) do {} while (0)
#define TRV(role, idx, v) do {} while (0)
#define TRVI(c, role, idx, v) do {} while (0)

#define ACLK_INIT do {} while (0)
#define ACLK(i) do {} while (0)
#define ACLK_OUT do {} while (0)
#define QCLK(i) do {} while (0)
#define PH 1
#define RCLK(i) do {} while (0)
#define RCLK_INIT do {} while (0)
#define RCLK_OUT do {} while (0)
#define SCLK(i) do {} while (0)
#define SCLK2(i) do {} while (0)
#define SCLK3(i) do {} while (0)
#define PL 1
#define PCLK(i) do {} while (0)
#define PQ 1
#define CLK_INIT do {} while (0)
#define CLK(i) do {} while (0)
#define CLK_OUT do {} while (0)

__device__ __forceinline__ void wgmma_ss_n216(float* d, uint64_t da, uint64_t db, int scaleD) {
  asm volatile("{\n.reg .pred p;\nsetp.ne.b32 p, %110, 0;\nwgmma.mma_async.sync.aligned.m64n216k16.f32.bf16.bf16 "
    "{%0,%1,%2,%3,%4,%5,%6,%7,%8,%9,%10,%11,%12,%13,%14,%15,%16,%17,%18,%19,%20,%21,%22,%23,%24,%25,%26,%27,%28,%29,%30,%31,%32,%33,%34,%35,%36,%37,%38,%39,%40,%41,%42,%43,%44,%45,%46,%47,%48,%49,%50,%51,%52,%53,%54,%55,%56,%57,%58,%59,%60,%61,%62,%63,%64,%65,%66,%67,%68,%69,%70,%71,%72,%73,%74,%75,%76,%77,%78,%79,%80,%81,%82,%83,%84,%85,%86,%87,%88,%89,%90,%91,%92,%93,%94,%95,%96,%97,%98,%99,%100,%101,%102,%103,%104,%105,%106,%107}, "
    "%108, %109, p, 1, 1, 0, 1;\n}\n"
    : "+f"(d[0]), "+f"(d[1]), "+f"(d[2]), "+f"(d[3]), "+f"(d[4]), "+f"(d[5]), "+f"(d[6]), "+f"(d[7]), "+f"(d[8]), "+f"(d[9]), "+f"(d[10]), "+f"(d[11]), "+f"(d[12]), "+f"(d[13]), "+f"(d[14]), "+f"(d[15]), "+f"(d[16]), "+f"(d[17]), "+f"(d[18]), "+f"(d[19]), "+f"(d[20]), "+f"(d[21]), "+f"(d[22]), "+f"(d[23]), "+f"(d[24]), "+f"(d[25]), "+f"(d[26]), "+f"(d[27]), "+f"(d[28]), "+f"(d[29]), "+f"(d[30]), "+f"(d[31]), "+f"(d[32]), "+f"(d[33]), "+f"(d[34]), "+f"(d[35]), "+f"(d[36]), "+f"(d[37]), "+f"(d[38]), "+f"(d[39]), "+f"(d[40]), "+f"(d[41]), "+f"(d[42]), "+f"(d[43]), "+f"(d[44]), "+f"(d[45]), "+f"(d[46]), "+f"(d[47]), "+f"(d[48]), "+f"(d[49]), "+f"(d[50]), "+f"(d[51]), "+f"(d[52]), "+f"(d[53]), "+f"(d[54]), "+f"(d[55]), "+f"(d[56]), "+f"(d[57]), "+f"(d[58]), "+f"(d[59]), "+f"(d[60]), "+f"(d[61]), "+f"(d[62]), "+f"(d[63]), "+f"(d[64]), "+f"(d[65]), "+f"(d[66]), "+f"(d[67]), "+f"(d[68]), "+f"(d[69]), "+f"(d[70]), "+f"(d[71]), "+f"(d[72]), "+f"(d[73]), "+f"(d[74]), "+f"(d[75]), "+f"(d[76]), "+f"(d[77]), "+f"(d[78]), "+f"(d[79]), "+f"(d[80]), "+f"(d[81]), "+f"(d[82]), "+f"(d[83]), "+f"(d[84]), "+f"(d[85]), "+f"(d[86]), "+f"(d[87]), "+f"(d[88]), "+f"(d[89]), "+f"(d[90]), "+f"(d[91]), "+f"(d[92]), "+f"(d[93]), "+f"(d[94]), "+f"(d[95]), "+f"(d[96]), "+f"(d[97]), "+f"(d[98]), "+f"(d[99]), "+f"(d[100]), "+f"(d[101]), "+f"(d[102]), "+f"(d[103]), "+f"(d[104]), "+f"(d[105]), "+f"(d[106]), "+f"(d[107])
    : "l"(da), "l"(db), "r"(scaleD));
}
__device__ __forceinline__ void wgmma_ss_n72(float* d, uint64_t da, uint64_t db, int scaleD) {
  asm volatile("{\n.reg .pred p;\nsetp.ne.b32 p, %38, 0;\nwgmma.mma_async.sync.aligned.m64n72k16.f32.bf16.bf16 "
    "{%0,%1,%2,%3,%4,%5,%6,%7,%8,%9,%10,%11,%12,%13,%14,%15,%16,%17,%18,%19,%20,%21,%22,%23,%24,%25,%26,%27,%28,%29,%30,%31,%32,%33,%34,%35}, "
    "%36, %37, p, 1, 1, 0, 1;\n}\n"
    : "+f"(d[0]), "+f"(d[1]), "+f"(d[2]), "+f"(d[3]), "+f"(d[4]), "+f"(d[5]), "+f"(d[6]), "+f"(d[7]), "+f"(d[8]), "+f"(d[9]), "+f"(d[10]), "+f"(d[11]), "+f"(d[12]), "+f"(d[13]), "+f"(d[14]), "+f"(d[15]), "+f"(d[16]), "+f"(d[17]), "+f"(d[18]), "+f"(d[19]), "+f"(d[20]), "+f"(d[21]), "+f"(d[22]), "+f"(d[23]), "+f"(d[24]), "+f"(d[25]), "+f"(d[26]), "+f"(d[27]), "+f"(d[28]), "+f"(d[29]), "+f"(d[30]), "+f"(d[31]), "+f"(d[32]), "+f"(d[33]), "+f"(d[34]), "+f"(d[35])
    : "l"(da), "l"(db), "r"(scaleD));
}
__device__ __forceinline__ void wgmma_ss_n128(float* d, uint64_t da, uint64_t db, int scaleD) {
  asm volatile("{\n.reg .pred p;\nsetp.ne.b32 p, %66, 0;\nwgmma.mma_async.sync.aligned.m64n128k16.f32.bf16.bf16 "
    "{%0,%1,%2,%3,%4,%5,%6,%7,%8,%9,%10,%11,%12,%13,%14,%15,%16,%17,%18,%19,%20,%21,%22,%23,%24,%25,%26,%27,%28,%29,%30,%31,%32,%33,%34,%35,%36,%37,%38,%39,%40,%41,%42,%43,%44,%45,%46,%47,%48,%49,%50,%51,%52,%53,%54,%55,%56,%57,%58,%59,%60,%61,%62,%63}, "
    "%64, %65, p, 1, 1, 0, 1;\n}\n"
    : "+f"(d[0]), "+f"(d[1]), "+f"(d[2]), "+f"(d[3]), "+f"(d[4]), "+f"(d[5]), "+f"(d[6]), "+f"(d[7]), "+f"(d[8]), "+f"(d[9]), "+f"(d[10]), "+f"(d[11]), "+f"(d[12]), "+f"(d[13]), "+f"(d[14]), "+f"(d[15]), "+f"(d[16]), "+f"(d[17]), "+f"(d[18]), "+f"(d[19]), "+f"(d[20]), "+f"(d[21]), "+f"(d[22]), "+f"(d[23]), "+f"(d[24]), "+f"(d[25]), "+f"(d[26]), "+f"(d[27]), "+f"(d[28]), "+f"(d[29]), "+f"(d[30]), "+f"(d[31]), "+f"(d[32]), "+f"(d[33]), "+f"(d[34]), "+f"(d[35]), "+f"(d[36]), "+f"(d[37]), "+f"(d[38]), "+f"(d[39]), "+f"(d[40]), "+f"(d[41]), "+f"(d[42]), "+f"(d[43]), "+f"(d[44]), "+f"(d[45]), "+f"(d[46]), "+f"(d[47]), "+f"(d[48]), "+f"(d[49]), "+f"(d[50]), "+f"(d[51]), "+f"(d[52]), "+f"(d[53]), "+f"(d[54]), "+f"(d[55]), "+f"(d[56]), "+f"(d[57]), "+f"(d[58]), "+f"(d[59]), "+f"(d[60]), "+f"(d[61]), "+f"(d[62]), "+f"(d[63])
    : "l"(da), "l"(db), "r"(scaleD));
}
__device__ __forceinline__ void wgmma_ss_n160(float* d, uint64_t da, uint64_t db, int scaleD) {
  asm volatile("{\n.reg .pred p;\nsetp.ne.b32 p, %82, 0;\nwgmma.mma_async.sync.aligned.m64n160k16.f32.bf16.bf16 "
    "{%0,%1,%2,%3,%4,%5,%6,%7,%8,%9,%10,%11,%12,%13,%14,%15,%16,%17,%18,%19,%20,%21,%22,%23,%24,%25,%26,%27,%28,%29,%30,%31,%32,%33,%34,%35,%36,%37,%38,%39,%40,%41,%42,%43,%44,%45,%46,%47,%48,%49,%50,%51,%52,%53,%54,%55,%56,%57,%58,%59,%60,%61,%62,%63,%64,%65,%66,%67,%68,%69,%70,%71,%72,%73,%74,%75,%76,%77,%78,%79}, "
    "%80, %81, p, 1, 1, 0, 1;\n}\n"
    : "+f"(d[0]), "+f"(d[1]), "+f"(d[2]), "+f"(d[3]), "+f"(d[4]), "+f"(d[5]), "+f"(d[6]), "+f"(d[7]), "+f"(d[8]), "+f"(d[9]), "+f"(d[10]), "+f"(d[11]), "+f"(d[12]), "+f"(d[13]), "+f"(d[14]), "+f"(d[15]), "+f"(d[16]), "+f"(d[17]), "+f"(d[18]), "+f"(d[19]), "+f"(d[20]), "+f"(d[21]), "+f"(d[22]), "+f"(d[23]), "+f"(d[24]), "+f"(d[25]), "+f"(d[26]), "+f"(d[27]), "+f"(d[28]), "+f"(d[29]), "+f"(d[30]), "+f"(d[31]), "+f"(d[32]), "+f"(d[33]), "+f"(d[34]), "+f"(d[35]), "+f"(d[36]), "+f"(d[37]), "+f"(d[38]), "+f"(d[39]), "+f"(d[40]), "+f"(d[41]), "+f"(d[42]), "+f"(d[43]), "+f"(d[44]), "+f"(d[45]), "+f"(d[46]), "+f"(d[47]), "+f"(d[48]), "+f"(d[49]), "+f"(d[50]), "+f"(d[51]), "+f"(d[52]), "+f"(d[53]), "+f"(d[54]), "+f"(d[55]), "+f"(d[56]), "+f"(d[57]), "+f"(d[58]), "+f"(d[59]), "+f"(d[60]), "+f"(d[61]), "+f"(d[62]), "+f"(d[63]), "+f"(d[64]), "+f"(d[65]), "+f"(d[66]), "+f"(d[67]), "+f"(d[68]), "+f"(d[69]), "+f"(d[70]), "+f"(d[71]), "+f"(d[72]), "+f"(d[73]), "+f"(d[74]), "+f"(d[75]), "+f"(d[76]), "+f"(d[77]), "+f"(d[78]), "+f"(d[79])
    : "l"(da), "l"(db), "r"(scaleD));
}
__device__ __forceinline__ void wgmma_rs_n144(float* d, const uint32_t* a, uint64_t db, int scaleD) {
  asm volatile("{\n.reg .pred p;\nsetp.ne.b32 p, %77, 0;\nwgmma.mma_async.sync.aligned.m64n144k16.f32.bf16.bf16 "
    "{%0,%1,%2,%3,%4,%5,%6,%7,%8,%9,%10,%11,%12,%13,%14,%15,%16,%17,%18,%19,%20,%21,%22,%23,%24,%25,%26,%27,%28,%29,%30,%31,%32,%33,%34,%35,%36,%37,%38,%39,%40,%41,%42,%43,%44,%45,%46,%47,%48,%49,%50,%51,%52,%53,%54,%55,%56,%57,%58,%59,%60,%61,%62,%63,%64,%65,%66,%67,%68,%69,%70,%71}, "
    "{%72,%73,%74,%75}, %76, p, 1, 1, 1;\n}\n"
    : "+f"(d[0]), "+f"(d[1]), "+f"(d[2]), "+f"(d[3]), "+f"(d[4]), "+f"(d[5]), "+f"(d[6]), "+f"(d[7]), "+f"(d[8]), "+f"(d[9]), "+f"(d[10]), "+f"(d[11]), "+f"(d[12]), "+f"(d[13]), "+f"(d[14]), "+f"(d[15]), "+f"(d[16]), "+f"(d[17]), "+f"(d[18]), "+f"(d[19]), "+f"(d[20]), "+f"(d[21]), "+f"(d[22]), "+f"(d[23]), "+f"(d[24]), "+f"(d[25]), "+f"(d[26]), "+f"(d[27]), "+f"(d[28]), "+f"(d[29]), "+f"(d[30]), "+f"(d[31]), "+f"(d[32]), "+f"(d[33]), "+f"(d[34]), "+f"(d[35]), "+f"(d[36]), "+f"(d[37]), "+f"(d[38]), "+f"(d[39]), "+f"(d[40]), "+f"(d[41]), "+f"(d[42]), "+f"(d[43]), "+f"(d[44]), "+f"(d[45]), "+f"(d[46]), "+f"(d[47]), "+f"(d[48]), "+f"(d[49]), "+f"(d[50]), "+f"(d[51]), "+f"(d[52]), "+f"(d[53]), "+f"(d[54]), "+f"(d[55]), "+f"(d[56]), "+f"(d[57]), "+f"(d[58]), "+f"(d[59]), "+f"(d[60]), "+f"(d[61]), "+f"(d[62]), "+f"(d[63]), "+f"(d[64]), "+f"(d[65]), "+f"(d[66]), "+f"(d[67]), "+f"(d[68]), "+f"(d[69]), "+f"(d[70]), "+f"(d[71])
    : "r"(a[0]), "r"(a[1]), "r"(a[2]), "r"(a[3]), "l"(db), "r"(scaleD));
}
__device__ __forceinline__ void wgmma_rs_n64(float* d, const uint32_t* a, uint64_t db, int scaleD) {
  asm volatile("{\n.reg .pred p;\nsetp.ne.b32 p, %37, 0;\nwgmma.mma_async.sync.aligned.m64n64k16.f32.bf16.bf16 "
    "{%0,%1,%2,%3,%4,%5,%6,%7,%8,%9,%10,%11,%12,%13,%14,%15,%16,%17,%18,%19,%20,%21,%22,%23,%24,%25,%26,%27,%28,%29,%30,%31}, "
    "{%32,%33,%34,%35}, %36, p, 1, 1, 1;\n}\n"
    : "+f"(d[0]), "+f"(d[1]), "+f"(d[2]), "+f"(d[3]), "+f"(d[4]), "+f"(d[5]), "+f"(d[6]), "+f"(d[7]), "+f"(d[8]), "+f"(d[9]), "+f"(d[10]), "+f"(d[11]), "+f"(d[12]), "+f"(d[13]), "+f"(d[14]), "+f"(d[15]), "+f"(d[16]), "+f"(d[17]), "+f"(d[18]), "+f"(d[19]), "+f"(d[20]), "+f"(d[21]), "+f"(d[22]), "+f"(d[23]), "+f"(d[24]), "+f"(d[25]), "+f"(d[26]), "+f"(d[27]), "+f"(d[28]), "+f"(d[29]), "+f"(d[30]), "+f"(d[31])
    : "r"(a[0]), "r"(a[1]), "r"(a[2]), "r"(a[3]), "l"(db), "r"(scaleD));
}

template <int V> struct Int { static constexpr int value = V; };
struct Cur {
  uint32_t s, ph;
  __device__ __forceinline__ void next() { if (++s == NST) { s = 0; ph ^= 1; } }
};

__device__ __forceinline__ uint32_t o_place(uint32_t w, uint32_t e) { return (((w ? 0xd5310u : 0xa8d57u) >> (4 * e)) & 15) * 8192 + 90112; }
#define z1_block(rb, w, j) (Q.Z + ((rb) * 16 + (w) * 8 + (j)) * ZB)
#define xn_block(hw) (Q.Z + (512 + (hw) * 2) * ZB)
#define z2_block(kb, j) (Q.Z + (256 + (kb) * 8 + (j)) * ZB)
template <int N> __device__ __forceinline__ void pause(uint32_t zero) {
  if (N <= 0) return;
  uint32_t z = clock() + threadIdx.x;
  do {
#pragma unroll (N > 8 ? 1 : 8)
    for (int i = 0; i < N; i++) asm volatile("shfl.sync.bfly.b32 %0, %0, 1, 0x1f, 0xffffffff;" : "+r"(z)::"memory");
  } while (__any_sync(~0u, z & zero));
}

__global__ void __cluster_dims__(2, 1, 1) __launch_bounds__(384, 1) mega_kernel(const Ptrs Q, const __grid_constant__ Params P) {
  extern __shared__ __align__(1024) uint8_t smem_raw[];
  const uint32_t sb = smem_u32(smem_raw);
  const uint32_t bars = sb + SM_BAR;
  const int tid = threadIdx.x;
  int lane = tid & 31;
  const int wid = __shfl_sync(~0u, tid >> 5, 0);
  const int cl = blockIdx.x >> 1;
  const int bid = (cl < 4 ? cl * 8 + 32 : cl - 4 + (max(cl - 29, 0) * 37 >> 8)) * 2 + (blockIdx.x & 1);
  const int rb = bid & 15, j = bid >> 4;
  uint4 wv[5];
  {
    const int n8 = min(tid >> 3, 26), part = n8 / 9;
    const uint8_t* src = (const uint8_t*)Q.wqkv + (8 * rb + (tid & 7)) * (3 * DM * 2) + (part * (DM - 72) + 72 * j + 8 * n8) * 2;
#pragma unroll
    for (int u = 0; u < 5; u++) wv[u] = ldnc128_if(tid < 216 && cl < 64 && (u < 4 || rb < 8), src + u * (128 * 3 * DM * 2));
  }
  if (cl >= 64) return;
  if (wid >= 7 && lane == 0) {
    if (wid < 10) {
#pragma unroll
      for (uint32_t b = 0; b < B_AD / 3; b += 8) mbar_init(bars + (wid - 7) * (B_AD / 3) + b, 1);
    } else if (wid == 10) {
#pragma unroll
      for (uint32_t b = B_AD; b < B_EVT; b += 8) mbar_init(bars + b, b < B_CSQ ? 2 : b < B_LAG ? 3 : 4);
    } else {
#pragma unroll
      for (uint32_t b = B_EVT; b < 1024; b += 8) if (b < B_OFF || b >= B_IMG) mbar_init(bars + b, b < B_IMG ? 4 : b < B_EMPTY ? 8 : 16);
    }
    asm volatile("fence.mbarrier_init.release.cluster;" ::: "memory");
  }
  __syncthreads();

  if (wid >= 8) {
    reg_dealloc<40>();
    const uint32_t el = elect_one();
    const uint64_t pol = policy_evict_first();
    uint32_t* const fj = Q.flags + FJ + j * 32;
    if (wid == 8) {
      if (el) { prefetch_map(&P.wsp); prefetch_map(&P.winb[j & 1]); prefetch_map(&P.wins); prefetch_map(&P.wout); prefetch_map(&P.act[1]); prefetch_map(&P.res[0]); prefetch_map(&P.res[1]); prefetch_map(&P.row[1]); prefetch_map(&P.red); }
      const uint32_t epoch = ldcg32(fj + FJ_EP + rb);
      Cur c{0, 1};
      const uint32_t rk = bid & 1;
      uint32_t st, full;
      auto slot = [&](uint32_t bytes) {
        st = sb + c.s * ST_BYTES; full = bars + B_FULL + c.s * 8;
        mbar_wait(full, c.ph);
        expect_tx_p(el, full, bytes);
        mbar_wait(full - B_FULL + B_EMPTY, c.ph);
      };
#pragma unroll 1
      for (int L = 0; L < 2; L++) {
#pragma unroll 1
        for (int i = 0; i < 9; i++) {
          if (L == 0 && i == 0) {
            flag_wait(fj + FJ_WQ, (epoch + 1) * 16);
            fence_async_g();
            TRC(el, 2, 45);
          }
          slot(27648);
          bulk_mc_h(el, st + ST_B + rk * 13824, Q.WQ + j * WQ_SL + i * 27648 + rk * 13824, 13824, full, EF(0), pol);
          c.next();
        }
        if (L == 0) {
          flag_wait(fj + FJ_WO, (epoch + 1) * 16);
          fence_async_g();
          TRC(el, 2, 46);
        }
#pragma unroll 1
        while (c.s) {
          mbar_wait(bars + B_EMPTY + c.s * 8, c.ph);
          if (el) { mbar_arrive(bars + B_FULL + c.s * 8); asm volatile("mbarrier.arrive.shared::cta.b64 _, [%0], 16;" ::"r"(bars + B_EMPTY + c.s * 8) : "memory"); }
          c.next();
        }
        expect_tx_p(el, bars + B_WF, WO_SL);
        mbar_wait(bars + B_EMPTY, c.ph);
        mbar_wait(bars + B_EMPTY + 8, c.ph);
        bulk_mc_h(el, sb + rk * (WO_SL / 2), Q.WO + j * WO_SL + rk * (WO_SL / 2), WO_SL / 2, bars + B_WF, EF(1), pol);
#pragma unroll 1
        for (int r = 0; r < 10; r++) {
          const bool big = r >= 2 && r < 8;
          const int a0 = (r < 5 ? 36 : 0) + ((9 * j) >> 1) + (big ? 2 - 2 * (j & 1) : 3 * (j & 1) + rk), ks = big ? 32 : 48;
          int k = big ? (r < 5 ? r - 2 : r - 5) * 192 + rk * 16 : (r & 1) * 288;
          const CUtensorMap* m = big ? &P.winb[j & 1] : &P.wins;
          const uint32_t dst = sb + SM_B3 + rk * 6144;
#pragma unroll
          for (int p = 0; p < 6; p++, k += ks) {
            if ((p == 0 || p > 3) && r == 0) mbar_wait(bars + (p < 5 ? B_XD + p * 2 : B_S5), L);
            if (p) mbar_wait_c(bars + B_E3 + p * 8, ~r & 1); else mbar_wait(bars + B_E3, ~r & 1);
            expect_tx_p(el, bars + B_F3 + p * 8, 12288);
            tma3d_mc_h(el, dst + p * 12288, m, 0, k, a0, bars + B_F3 + p * 8, EF(2), pol);
          }
        }
        TRC(el, 2, L * 16 + 6);
        mbar_wait(bars + B_ZOK, L);
        fence_async_g();
        TRC(el, 2, L * 16 + 7);
        const uint8_t* src = z2_block(0, j) + rk * 18432;
#pragma unroll 1
        for (int r = 0; r < 8; r++) {
          const int k = (r & 3) * 512 + (r >> 2) * 64;
#pragma unroll
          for (int p = 0; p < 4; p++, src += 8 * ZB) {
            if ((p == 1 || p == 2) && r == 0) mbar_wait(bars + B_E3 - 8 + p * 24, 1);
            mbar_wait_c(bars + B_AD + p * 8, ~r & 1);
            if (p) mbar_wait_c(bars + B_EMPTY + p * 8, c.ph); else mbar_wait(bars + B_EMPTY, c.ph);
            expect_tx_p(el, bars + B_FULL + p * 8, ST_BYTES);
            bulk_mc_h(el, sb + p * ST_BYTES + ST_B + rk * 18432, src, 18432, bars + B_FULL + p * 8, EF(4), pol);
            tma3d_h(el, sb + p * ST_BYTES, &P.wsp, k + p * 128, rb * 64, 0, bars + B_FULL + p * 8, EF(3), pol);
          }
          c.ph ^= 1;
        }
        mbar_wait(bars + B_Z1, L);
        fence_async_g();
#pragma unroll 1
        for (int i = 0; i < 11; i++) {
          const int cb = i - 2 + j;
          if (i < 4) mbar_wait(bars + B_AD + c.s * 8, 1);
          slot(ZB);
          if (i < 2) bulk_load_h(el, st + ST_B, z1_block(rb, i, j), ZB, full, true, pol);
          else tma2d_mc_h(el, st + ST_B + rk * 18432, &P.wout, (cb >= 9 ? cb - 9 : cb) * 64, 288 * j + rk * 144, full, EF(5), pol);
          c.next();
        }
      }
    } else if (wid < 11) {
      uint32_t id = bid * 2 + wid - 9;
#define AGENT_IDS asm volatile("" : "+r"(lane), "+r"(id)); const uint32_t w = id & 1, hw = id & 31, rb = hw >> 1, j = id >> 5, ev = bars + B_EVT + w * EV_N * 8; \
      uint32_t* const fr = Q.flags + hw * 32; uint32_t* const fj = Q.flags + FJ + j * 32; (void)fr; (void)fj; (void)ev; (void)rb
      uint32_t t8 = 0;
      Cur c{0, 1};
#pragma unroll 1
      for (int L = 0; L < 2; L++) {
#pragma unroll 1
        for (int ph = 0; ph < 3; ph++) {
          if (ph + L > 0) {
            AGENT_IDS;
            uint32_t* f = fr + (ph == 0 ? FR_X2 : ph == 1 ? FR_O + L - (int)w * 32 : FR_X1 + L);
            mbar_wait_c(ev + ph * 8, L);
            TRC(el, 3, w * 32 + L * 16 + ph * 3);
            if (ph || XRLX) { if (ph < 2 || SDEL < 0) flag_add_p(el, f); } else flag_release_p(el, f);
            TRC(el, 3, w * 32 + L * 16 + ph * 3 + 1);
            if (ph == 1) {
#pragma unroll 1
              for (int e = 0; e < 5; e++) {
                const uint32_t nb = e ? 16384 : 8192, full = bars + B_OF + w * 40 + e * 8, dst = sb + o_place(w, e);
                const uint8_t* src = z1_block(rb, w, 0) + (e ? e * 16384 - 8192 : 0);
                expect_tx_p(el, full, nb);
                if (e == 0) {
                  pause<FD1>(Q.zero);
                  if (w) pause<FD2>(Q.zero);
                  flag_wait(f + w * (FR_OL - FR_O), t8 * (2 - w));
                  if (w) fence_async_g();
                }
                if (w && (e == 0 || e == 3)) mbar_wait_c(bars + (e ? B_X3 : B_OF + YPACE * 8), L);
                bulk_load_h(el, dst, src, nb, full, EF(6), pol);
                TRC(el && e == 0, 3, w * 32 + L * 16 + ph * 3 + 2);
              }
              continue;
            }
            if (ph == 2) {
              const uint8_t* src = xn_block(hw);
              uint32_t full = bars + B_AF3 + w * 96, dst = sb + w * 6144;
              mbar_wait_c(bars + B_XD + 8, L);
#pragma unroll 1
              for (int k = 0; k < 12; k++, src += 6144, dst += 12288, full += 8) {
                expect_tx_p(el, full, 6144);
                if (k >= APACE) mbar_wait_c(full - APACE * 8, L);
                if (k == 0) { if (SDEL < 0) flag_wait(f, t8); else pause<SDEL>(Q.zero); }
                if (k == 11 && L == 1) flag_wait(fj + FJ_P4, t8 * 4);
                bulk_load_h(el, dst, src, 6144, full, EF(7), pol);
                TRC(el && k == 0, 3, w * 32 + L * 16 + ph * 3 + 2);
              }
              break;
            }
            const uint32_t full = bars + B_FULLA + w * 32 + c.s * 8, dst = sb + c.s * ST_BYTES + w * 8192;
            mbar_wait_c(bars + B_EMPTY + c.s * 8, c.ph);
            expect_tx_p(el, full, 8192);
            pause<FD0>(Q.zero);
            flag_wait(f, t8);
            fence_async_g();
            tma3d_h(el, dst, &P.act[1], 0, rb * 64, w, full, false, pol);
            c.next();
            TRC(el, 3, w * 32 + L * 16 + ph * 3 + 2);
          }
#pragma unroll 1
          for (int i = L; i < 9; i++) {
            AGENT_IDS;
            const uint32_t full = bars + B_FULLA + w * 32 + c.s * 8, dst = sb + c.s * ST_BYTES + w * 8192;
            if (L == 0 && i == AEP) t8 = (ldcg32(fr + FR_EP + j) + 1) * 8;
            mbar_wait_c(bars + B_EMPTY + c.s * 8, c.ph);
            expect_tx_p(el, full, 8192);
            tma3d_h(el, dst, &P.act[L], i * 64, rb * 64, w, full, false, pol);
            c.next();
            if (i == PZI || i == PZI + 1) {
              uint8_t* d = (i == PZI ? xn_block(hw) : z1_block(rb, 0, 0) + w * 4608) + j * 9216 + lane * 16;
#pragma unroll 1
              for (int u = i == PZI ? 0 : 3; u < 6; u++, d += 1536) { stg128(d, ~0u, ~0u, ~0u, ~0u); stg128(d + 512, ~0u, ~0u, ~0u, ~0u); stg128(d + 1024, ~0u, ~0u, ~0u, ~0u); }
            }
            if (i == PZI) { stg128(Q.ST1 + (hw * 8 + j) * 32 + lane, ~0u, ~0u, ~0u, ~0u); stg128(Q.ZST + (hw * 8 + j) * 32 + lane, ~0u, ~0u, ~0u, ~0u); }
            if (i == RFI) {
              expect_tx_p(el, bars + B_WT + w * 8, 9216);
              tma3d_h(el, sb + SM_STG + w * 9216, &P.row[L], 0, 3 * w, rb * 64 + 8 * j, bars + B_WT + w * 8, false, pol);
            }
            if (i == 4 && L > w) {
              expect_tx_p(el, bars + B_CSQ, 864);
              bulk_load_p(el, sb + 3 * ST_BYTES + SM_CSQ, Q.CSP + (NCTA + (id >> 1)) * 216, 864, bars + B_CSQ);
            }
          }
          if (c.s) { c.s = 0; c.ph ^= 1; }
          {
            AGENT_IDS;
            const uint32_t tag = (t8 >> 2) - 1 + L;
            uint4* const xs = Q.XST + hw * 128;
            const uint32_t tab = sb + L * (3 * ST_BYTES) + SM_XST + w * 768 + lane * 8;
            TRC(el, 3, w * 32 + L * 16 + 13);
#pragma unroll 1
            for (int it = 0; it < (1 << 22); it++) {
              const uint4 a = ll_ld128(xs + 2 * lane), b = ll_ld128(xs + 64 + 2 * lane), h = ll_ld128(xs - (rb ? 192 : 0) + 2 * (lane | 24));
              if (__all_sync(~0u, a.z == tag && b.z == tag && h.z == tag)) { sts64(tab, h.x, h.y); sts64(tab + 256, a.x, a.y); sts64(tab + 512, b.x, b.y); break; }
            }
            __syncwarp();
            if (el) mbar_arrive(bars + B_CSQ);
            TRC(el, 3, w * 32 + L * 16 + 14);
            uint32_t* f = Q.flags + rb * 64 + FR_PZ + L;
            flag_release_p(el, f);
            expect_tx_p(el, bars + B_RES + w * 8, 9216);
            tma3d_h(el, sb + SM_STG + w * 9216, &P.res[L], j * 72, hw * 32, 0, bars + B_RES + w * 8, !L, pol);
            pause<FD3>(Q.zero);
            flag_wait(f, t8 * 2);
            fence_async_g();
            TRC(el, 3, w * 32 + L * 16 + 15);
          }
        }
        if (wid == 10) {
          AGENT_IDS;
          mbar_wait_c(ev - (EV_N - EV_ZN) * 8, L);
          mbar_wait_c(ev + EV_ZN * 8, L);
          asm volatile("fence.release.gpu;" ::: "memory");
          flag_add_p(el, fj + FJ_ZN + L);
          flag_add_p(el, fr - 32 + FR_XR + L);
          pause<FD4>(Q.zero);
          flag_wait(fj + FJ_ZN + L, t8 * 2);
          flag_wait(fr - 32 + FR_XR + L, t8);
          if (el) mbar_arrive(bars + B_ZOK);
        } else if (WPF) {
          AGENT_IDS;
          mbar_wait_c(ev + EV_ZN * 8, L);
          if (el) asm volatile("cp.async.bulk.prefetch.tensor.3d.L2.global [%0, {%1, %2, %3}];" ::"l"(&P.wsp), "r"(j * 128), "r"(rb * 64), "r"(0) : "memory");
        }
        float cv;
        {
        AGENT_IDS;
        cv = (lane & 3) ? 0.f : -blo(ldnc16(Q.b_sp + 128 * rb + 16 * j + 2 * (lane >> 2) + w));
        mbar_wait_c(ev + EV_Z1 * 8, L);
        const uint32_t ro = (w * 64 + 8 * j + (lane >> 2)) * 128, x0 = ((lane & 3) * 2) ^ (lane >> 2);
#pragma unroll 1
        for (int i = 0; i < 32; i++) {
          const bool tail = (i >> 1) == 12;
          const int kb = tail ? i + 6 : i < 24 ? i : i - 2;
          if (!(i & 7)) mbar_wait_c(bars + B_RT + i, L);
          if (i == 24) mbar_wait_c(bars + B_WT + w * 8, 1);
          if (!tail) mbar_wait(bars + B_FULL + c.s * 8, c.ph ^ 1);
          if (i == 3) {
            uint32_t id2 = id;
            asm volatile("" : "+r"(id2));
            expect_tx_p(el, bars + B_WT + w * 8, 3072);
#pragma unroll 1
            for (int r = 0; r < 8; r++)
              bulk_load_p(el, sb + SM_WT + w * 3200 + r * 400, (const uint8_t*)Q.w_sp + (64 * (id2 & 30) + 16 * (id2 >> 5) + 2 * r + w) * (SEQ * 2) + 29 * 128, 384, bars + B_WT + w * 8);
          }
#pragma unroll
          for (int e = 0; e < 2; e++) {
            const uint4 a = lds128(!tail ? sb + c.s * ST_BYTES + ro + ((x0 ^ e) << 4) : sb + SM_WT + w * 3200 + (lane >> 2) * 400 + (i - 24) * 256 + (lane & 3) * 32 + e * 16);
            const uint4 m = lds128(sb + SM_RT + 4096 + kb * 128 + (lane & 3) * 32 + e * 16);
            cv = fmaf(blo(a.x), blo(m.x), fmaf(bhi(a.x), bhi(m.x), fmaf(blo(a.y), blo(m.y), fmaf(bhi(a.y), bhi(m.y), cv))));
            cv = fmaf(blo(a.z), blo(m.z), fmaf(bhi(a.z), bhi(m.z), fmaf(blo(a.w), blo(m.w), fmaf(bhi(a.w), bhi(m.w), cv))));
          }
          if (!tail) {
            __syncwarp();
            if (el) mbar_arrive(bars + B_AD + c.s * 8);
            c.next();
          }
        }
        }
        AGENT_IDS;
        TRC(el, 3, w * 32 + L * 16 + 11);
        asm volatile("" : "+r"(t8));
        const uint32_t tag = (t8 >> 2) - 1 + L;
        cv = qsum(cv);
        uint2* const cs = (uint2*)(Q.XST + hw * 128 + 1);
        if ((lane & 3) == 0) ll_st64(cs + 32 * j + (lane >> 2) * 4, __float_as_uint(cv), tag);
        pause<FD5>(Q.zero);
#pragma unroll 1
        for (int it = 0; it < (1 << 22); it++) {
          const uint2 a = ll_ld64(cs + 4 * lane), b = ll_ld64(cs + 128 + 4 * lane);
          if (__all_sync(~0u, a.y == tag && b.y == tag)) { sts32(sb + SM_CV + w * 256 + lane * 4, a.x); sts32(sb + SM_CV + w * 256 + 128 + lane * 4, b.x); break; }
        }
        __syncwarp();
        if (el) mbar_arrive(bars + B_CV + w * 8);
        TRC(el, 3, w * 32 + L * 16 + 12);
#pragma unroll 1
        for (int kb = 30; kb < 32; kb++) {
          mbar_wait_c(bars + B_FULL + c.s * 8, c.ph ^ 1);
          if (el) mbar_arrive(bars + B_AD + c.s * 8);
          c.next();
        }
        c.ph ^= ((c.s + 11) >> 2) & 1; c.s = (c.s + 11) & 3;
        if (L == 0) {
          mbar_wait_c(ev + EV_PT * 8, 0);
          flag_add_p(el, fj + FJ_P4);
        }
      }
    } else {
      const uint32_t epoch = ldcg32(fj + FJ_EP + rb);
      mbar_wait(bars + B_IMG, 0);
      TRC(el, 2, 41);
      flag_release_p(el, fj + FJ_WQ);
      TRC(el, 2, 42);
#pragma unroll 1
      for (int L = 0; L < 2; L++) {
        float* const csf = Q.CSP + (NCTA + bid) * 216;
        if (L == 0) {
          flag_wait(fj + FJ_WQ, (epoch + 1) * 16);
          fence_async_g();
          expect_tx_p(el, bars + B_XRW, 13824);
          bulk_load_p(el, sb + ST_BYTES + SM_WOI, Q.CSP + j * 16 * 216, 6912, bars + B_XRW);
          bulk_load_p(el, sb + 2 * ST_BYTES + SM_WOI, Q.CSP + (j * 16 + 8) * 216, 6912, bars + B_XRW);
          mbar_wait(bars + B_XRW, 0);
#pragma unroll 1
          for (int f = lane; f < 54; f += 32) {
            float s[4] = {0.f, 0.f, 0.f, 0.f};
#pragma unroll 2
            for (int r = 0; r < 16; r++) {
              const uint4 v = lds128(sb + ST_BYTES + SM_WOI + (r >> 3) * ST_BYTES + (r & 7) * 864 + f * 16);
              s[0] += __uint_as_float(v.x); s[1] += __uint_as_float(v.y); s[2] += __uint_as_float(v.z); s[3] += __uint_as_float(v.w);
            }
            sts128(sb + SM_CSQ + f * 16, __float_as_uint(s[0]), __float_as_uint(s[1]), __float_as_uint(s[2]), __float_as_uint(s[3]));
            stg128(csf + f * 4, __float_as_uint(s[0]), __float_as_uint(s[1]), __float_as_uint(s[2]), __float_as_uint(s[3]));
          }
          __syncwarp();
          if (el) mbar_arrive(bars + B_CSQ);
          TRC(el, 2, 43);
          mbar_wait(bars + B_WOI, 0);
          bulk_store_p(el, Q.WO + j * WO_SL + rb * (41 * 128), sb + SM_WOI, (rb < 15 ? 41 : 33) * 128);
          publish_p(el, fj + FJ_WO);
          TRC(el, 2, 44);
          if (el) prefetch_l2((const uint8_t*)Q.w_in + bid * 41472, 41472);
          float o0 = 0.f, o1 = 0.f;
#pragma unroll 1
          for (int u = 0; u < 2; u++) {
            const uint8_t* src = (u ? (const uint8_t*)Q.w_sp + 500 * (SEQ * 2) + 2048 : (const uint8_t*)Q.w_in + 100 * (2 * FH * 2) + FH * 2) + lane * 16;
            const uint4 a = ldnc128(src), b = ldnc128(src + 300 * (2 * FH * 2) + 2048);
            const uint32_t x[8] = {a.x, a.y, a.z, a.w, b.x, b.y, b.z, b.w};
            float sq = 0.f;
#pragma unroll
            for (int e = 0; e < 8; e++) sq = fmaf(blo(x[e]), blo(x[e]), fmaf(bhi(x[e]), bhi(x[e]), sq));
            o0 = o1;
            asm("sqrt.approx.f32 %0, %1;" : "=f"(o1) : "f"(wsum(sq) * (u ? C0S * C0S * SEQ / 512.f : 2.f * GA * GA * DM / 512.f)));
          }
          const uint32_t off = (__float_as_uint(o0) & 0x7f800000u) >> 16 | 0x8000u | OFM;
          if (el) sts128(sb + SM_OFF, off * 0x10001u, min(__float_as_uint(o1) & 0x7f800000u, 0x7e000000u) | 0x00400000u, __float_as_uint(GB), 0u);
        }
        mbar_wait(bars + B_EVT + EV_O * 8, L);
        mbar_wait(bars + B_EVT + (EV_N + EV_O) * 8, L);
        flag_release_p(el, Q.flags + rb * 64 + FR_OL + L);
#pragma unroll 1
        for (int w = 0; w < 2; w++) {
          mbar_wait(bars + B_EVT + (w * EV_N + EV_XS) * 8, L);
          if (!w) mbar_wait(bars + B_AF3 + XP0 * 8, L);
          if (el) asm volatile("cp.async.bulk.tensor.3d.global.shared::cta.tile.bulk_group [%0, {%2, %3, %4}], [%1];\ncp.async.bulk.commit_group;\ncp.async.bulk.wait_group.read 0;" ::"l"(&P.res[1]), "r"(sb + SM_STG + w * 9216), "r"(j * 72), "r"(rb * 64 + w * 32), "r"(0) : "memory");
          __syncwarp();
          if (lane < 2 && !w) mbar_arrive_cluster(mapa(bars + B_S5, lane));
        }
        if (el) { asm volatile("cp.async.bulk.wait_group 0;" ::: "memory"); mbar_arrive(bars + B_GATE3); }
        const uint32_t tag = epoch * 2 + L + 1;
        asm volatile("" : "+r"(lane));
#pragma unroll 1
        for (int b = 0; b < 8; b++) {
          if (!(b & 3)) {
            const int mb = b >> 2;
            mbar_wait(bars + B_ZS + mb * 8, L);
            pause<ZD1>(Q.zero);
            TRC(el && !mb, 2, L * 16 + 8);
            uint4 v;
#pragma unroll 1
            for (int it = 0; it < (1 << 22); it++) {
              v = ll_ld128(Q.ZST + ((rb * 2 + mb) * 8 + (lane >> 2)) * 32 + 4 * j + (lane & 3));
              if (__all_sync(~0u, max(max(v.x, v.y), max(v.z, v.w)) != ~0u)) break;
            }
            const bool o = lane & 16;
            float ss = __uint_as_float(o ? v.y : v.x) + __shfl_xor_sync(~0u, __uint_as_float(o ? v.x : v.y), 16), sq = __uint_as_float(o ? v.w : v.z) + __shfl_xor_sync(~0u, __uint_as_float(o ? v.z : v.w), 16);
            ss += __shfl_xor_sync(~0u, ss, 4); sq += __shfl_xor_sync(~0u, sq, 4); ss += __shfl_xor_sync(~0u, ss, 8); sq += __shfl_xor_sync(~0u, sq, 8);
            const float mean = ss * (1.f / FH), rs = blo(pack2(rsq_fast(fmaxf(fmaf(sq, 1.f / FH, -mean * mean), 0.f) + 4.f * GA * GA * LN_EPS), 0.f));
            if (!(lane & 12)) ll_st64(Q.RT + (mb * 16 + rb) * 64 + 8 * j + 2 * (lane & 3) + (lane >> 4), pack2(rs, rs * (mean - blo(lds32(sb + SM_OFF)))), tag);
            TRC(el && !mb, 2, L * 16 + 10);
            pause<ZD2>(Q.zero);
          }
          uint4 v[4];
#pragma unroll 1
          for (int it = 0; it < (1 << 22); it++) {
            bool ok = true;
#pragma unroll
            for (int u = 0; u < 4; u++) { v[u] = ll_ld128((const uint4*)Q.RT + b * 128 + u * 32 + lane); ok = ok && v[u].y == tag && v[u].w == tag; }
            if (__all_sync(~0u, ok)) break;
          }
#pragma unroll
          for (int u = 0; u < 4; u++) {
            const uint32_t rt = sb + SM_RT + b * 512 + u * 128, ro = (lane >> 3) * 32 + (lane & 3) * 8 + ((lane >> 2) & 1) * 2;
            sts32(rt + 4096 + lane * 4, __byte_perm(v[u].x, v[u].z, 0x7632));
            asm volatile("st.shared.u16 [%0], %1;\nst.shared.u16 [%0 + 4], %2;" ::"r"(rt + ro), "h"((uint16_t)v[u].x), "h"((uint16_t)v[u].z) : "memory");
          }
          __syncwarp();
          if (el && (b & 1)) mbar_arrive(bars + B_RT + (b - 1) * 4);
          TRC(el && b < 2, 2, L * 16 + 11 + b);
        }
        TRC(el, 2, L * 16 + 9);
        mbar_wait(bars + B_EVT + EV_Z1 * 8, L);
        mbar_wait(bars + B_EVT + (EV_N + EV_Z1) * 8, L);
        fence_gpu();
        if (el) mbar_arrive(bars + B_Z1);
      }
    }
  } else {
    const int w = wid >> 2, q = wid & 3;
    int g = lane >> 2, t = lane & 3;
    const uint32_t ev = bars + B_EVT + w * EV_N * 8;
    const bool tr = (tid & 127) == 0;
    (void)tr;
    Cur c{0, 0};
    const uint32_t ebar = mapa(bars + B_EMPTY, (bid & 1) ^ (lane & 1));
    auto release = [&](uint32_t s) { if (lane < 2) mbar_arrive_cluster(ebar + s * 8); };
    const uint32_t stg = sb + SM_STG + w * 9216;
    uint32_t ia = 0;
    auto wait_ab = [&]() { mbar_wait_c(bars + B_FULL + c.s * 8, c.ph); mbar_wait_c(bars + B_FULLA + w * 32 + c.s * 8, (ia >> c.s) & 1); ia ^= 1u << c.s; };
    uint32_t lagph = 0;
    auto yield = [&](int left, int lag) { if (w == 1 && left == lag) mbar_wait_c(bars + B_LAG, lagph); };
    auto yield_done = [&]() { if (w == 0 && lane == 0) mbar_arrive(bars + B_LAG); };
    uint32_t rp = 0;
    auto check = [&](auto n, uint32_t dst, const uint8_t* src) {
      const uint32_t a = dst + lane * 32 + (lane >> 2) * 4;
#pragma unroll 1
      for (int it = 0; it < (1 << 16); it++) {
        uint32_t x = lds32(a);
#pragma unroll
        for (int e = 1; e < n.value; e++) x = max(x, lds32(a + e * 1024));
        if (!__any_sync(~0u, x == ~0u)) break;
        fence_async_s();
        __syncwarp();
        expect_tx_p(lane == 0, bars + B_RB + q * 8, n.value * 1024);
        bulk_load_p(lane == 0, dst, src, n.value * 1024, bars + B_RB + q * 8);
        mbar_wait_c(bars + B_RB + q * 8, rp & 1);
        rp++;
      }
    };
    auto signal = [&](int e) { __syncwarp(); if (lane == 0) mbar_arrive(ev + e * 8); };
    TRC(tr, w, 0);

    {
      uint8_t* dst = Q.WQ + j * WQ_SL + rb * 3456 + tid * 16;
#pragma unroll
      for (int u = 0; u < 5; u++) {
        stg128_if((u < 4 || rb < 8) && tid < 216, dst + u * (16 * 3456), wv[u].x, wv[u].y, wv[u].z, wv[u].w);
        if (u == 0) TRC(tr, w, 60);
      }
      if (Q.zero == 0) {
        float s[8];
#pragma unroll
        for (int u = 0; u < 5; u++) {
          const uint32_t x[4] = {wv[u].x, wv[u].y, wv[u].z, wv[u].w};
#pragma unroll
          for (int e = 0; e < 4; e++) { s[2 * e] = u ? s[2 * e] + blo(x[e]) : blo(x[e]); s[2 * e + 1] = u ? s[2 * e + 1] + bhi(x[e]) : bhi(x[e]); }
        }
#pragma unroll
        for (int m = 4; m; m >>= 1) {
#pragma unroll
          for (int e = 0; e < m; e++) s[e] = ((tid & m) ? s[e + m] : s[e]) + __shfl_xor_sync(~0u, (tid & m) ? s[e] : s[e + m], m);
        }
        stg32_if(tid < 216, Q.CSP + bid * 216 + tid, __float_as_uint(s[0]));
      }
      __syncwarp();
      if (lane == 0) mbar_arrive(bars + B_IMG);
    }
    reg_alloc<232>();
    auto fetch_wo = [&]() {
#pragma unroll 1
      for (int u = tid; u < 328; u += 256) {
        const int m = min(41 * rb + (u >> 3), 647), k8 = m / 9;
        cp_async16(sb + SM_WOI + u * 16, (const uint8_t*)Q.wo + (8 * k8 + (u & 7)) * (DM * 2) + (72 * j + 8 * (m - k8 * 9)) * 2);
      }
    };
    const uint32_t epoch = ldcg32(Q.flags + (rb * 2 + w) * 32 + FR_EP + j);
    TRC(tr, w, 1);

#pragma unroll 1
    for (int L = 0; L < 2; L++) {
      const int tb = 2 + L * 24;
      asm volatile("" : "+r"(lane), "+r"(g), "+r"(t));
      (void)tb;
      const uint32_t tag = epoch * 2 + L + 1;
      uint32_t aoff = (w * 64 + q * 16 + (lane & 15)) * 128 + (((lane >> 4) ^ (lane & 7)) << 4);
      {
        uint32_t Pk[27][2];
        float rk[2][2], sc[2][2];
        const bool up0 = 2 * t > g, up1 = 2 * t + 1 > g;
        constexpr int HA_[6] = {0, 2, 4, 7, 12, 15}, HC_[6] = {6, 9, 10, 11, 14, 17};
        const bool remote = q == 0 && rb > 0;
        uint4* hp = Q.HALO + ((((rb - (q == 0)) * 2 + w) * 8 + j) * 6) * 32 + lane;
        const uint32_t att = 2 * ST_BYTES + w * 8192 + lane * 16;
        const uint8_t* hs = remote ? (const uint8_t*)hp : smem_raw + att + (q == 3 ? ST_BYTES : q == 2 ? 3072 : 0);
        uint8_t* od = z1_block(rb, q >> 1, 0) + (9 * j) * 1024 + (4 * (q & 1) + w) * 128 + lane * 4;
        ACLK_INIT;
        {
          float acc[108];
#pragma unroll
          for (int i = 0; i < 108; i++) acc[i] = 0.f;
          float sx[2] = {0.f, 0.f}, sq[2] = {0.f, 0.f};
          uint32_t prev = 0;
#pragma unroll 1
          for (int kb = 0; kb < 9; kb++) {
            wait_ab();
            yield(9 - kb, LAG1);
            TRC(tr && kb == 0, w, tb + 0);
            PCLK(kb * 4);
            const uint32_t st = sb + c.s * ST_BYTES, da = dlo(st + w * 8192, 16), db = dlo(st + ST_B, 3456);
            wgmma_fence();
#pragma unroll
            for (int kk = 0; kk < 4; kk++) {
              wgmma_ss_n216(acc, dsc<1024, 1>(da, kk * 32), dsc<128, 0>(db, kk * 6912), 1);
              if (kk == 0) { wgmma_commit(); wgmma_wait<1>(); if (kb > 0) release(prev); }
              if (kk == 3) wgmma_commit();
              if (kk == XK1) {
            if (kb >= KS && kb < KS + 3) {
              mbar_wait_c(bars + B_WT + w * 8, 0);
#pragma unroll
              for (int u = 0; u < 3; u++) {
                const uint2 x = lds64(stg + (2 * q + (lane >> 4)) * 1152 + (lane & 15) * 8 + (kb - KS) * 384 + u * 128);
                sx[0] += blo(x.x) + bhi(x.x); sx[1] += blo(x.y) + bhi(x.y);
                sq[0] = fmaf(blo(x.x), blo(x.x), fmaf(bhi(x.x), bhi(x.x), sq[0])); sq[1] = fmaf(blo(x.y), blo(x.y), fmaf(bhi(x.y), bhi(x.y), sq[1]));
              }
            }
            if (kb == KS + 3) {
              const bool o = lane & 1;
              float v = (o ? sq[0] + sq[1] : sx[0] + sx[1]) + __shfl_xor_sync(~0u, o ? sx[0] + sx[1] : sq[0] + sq[1], 1);
              v += __shfl_xor_sync(~0u, v, 2); v += __shfl_xor_sync(~0u, v, 4); v += __shfl_xor_sync(~0u, v, 8);
              const float m = v * (-1.f / DM), r = rsq_fast(fmaxf(fmaf(__shfl_xor_sync(~0u, v, 1), 1.f / DM, -m * m), 0.f) + LN_EPS);
              ll_st128_if(!(lane & 15), Q.XST + (rb * 2 + w) * 128 + 16 * j + 4 * q + (lane >> 3), m, r, tag);
            }
              }
              if (kk == XK2 && L == 0) {
            if (kb == 0) fetch_wo();
            if (kb == 3) {
              asm volatile("cp.async.wait_all;" ::: "memory");
              fence_async_s();
              __syncwarp();
              if (lane == 0) mbar_arrive(bars + B_WOI);
            }
              }
            }
            if (kb == 8) yield_done();
            PCLK(kb * 4 + 1);
            PCLK(kb * 4 + 2);
            PCLK(kb * 4 + 3);
            prev = c.s; c.next();
          }
          const uint32_t cs = sb + prev * ST_BYTES + SM_CSQ + t * 8;
          mbar_wait_c(bars + B_CSQ, L);
          const uint32_t xs = sb + prev * ST_BYTES + SM_XST + w * 768 + 256 + q * 128;
          const float2 n0 = lds64f(xs + g * 8), n1 = lds64f(xs + g * 8 + 64);
          const float m0 = n0.x, m1 = n1.x;
#pragma unroll
          for (int u = 0; u < 4; u++) {
            rk[u >> 1][u & 1] = __uint_as_float(lds32(xs + t * 16 + ((u & 1 ? up1 : up0) ? -64 : 0) + (u & 1) * 8 + (u >> 1) * 64 + 4));
            sc[u >> 1][u & 1] = rk[u >> 1][u & 1] * ((u >> 1 ? n1.y : n0.y) * (0.23570226039551584f * 1.4426950408889634f));
          }
          float2 cv[27];
#pragma unroll
          for (int G = 0; G < 27; G++) cv[G] = lds64f(cs + G * 32);
          PCLK(36);
          wgmma_wait<0>();
          PCLK(37);
          release(prev);
          lagph ^= 1;
          TRC(tr, w, tb + 1);
          ACLK(0);
#pragma unroll
          for (int G = 9; G < 27; G++) Pk[G][1] = pack2(fmaf(m1, cv[G].x, acc[4 * G + 2]), fmaf(m1, cv[G].y, acc[4 * G + 3]));
          if (q < 3) {
#pragma unroll
            for (int i = 0; i < 6; i++) sts128(sb + att + (q >> 1) * ST_BYTES + (q & 1) * 3072 + i * 512, Pk[9 + HA_[i]][1], Pk[10 + HA_[i]][1], tag, Pk[9 + HC_[i]][1]);
          } else if (rb < 15) {
#pragma unroll
            for (int i = 0; i < 6; i++) ll_st128(hp + i * 32, __uint_as_float(Pk[9 + HA_[i]][1]), __uint_as_float(Pk[10 + HA_[i]][1]), tag, __uint_as_float(Pk[9 + HC_[i]][1]));
          }
#pragma unroll
          for (int G = 0; G < 27; G++) {
            Pk[G][0] = pack2(fmaf(m0, cv[G].x, acc[4 * G]), fmaf(m0, cv[G].y, acc[4 * G + 1]));
            if (G < 9) Pk[G][1] = pack2(fmaf(m1, cv[G].x, acc[4 * G + 2]), fmaf(m1, cv[G].y, acc[4 * G + 3]));
          }
        }
        ACLK(1);
        constexpr int GA_[4] = {0, 2, 4, 7}, GB_[4] = {1, 3, 5, 8}, GC_[4] = {2, 4, 6, 6};
        float S1[4][4], S2[4][4];
        uint32_t qa[4][2], qc[4][2];
#pragma unroll
        for (int h = 0; h < 4; h++) {
#pragma unroll
          for (int r = 0; r < 2; r++) {
            qa[h][r] = (h == 0 || h == 3 || t >= h) ? Pk[GA_[h]][r] : 0u;
            qc[h][r] = (h == 3 ? t == 3 : t <= h) ? Pk[GC_[h]][r] : 0u;
          }
#pragma unroll
          for (int i = 0; i < 4; i++) S1[h][i] = S2[h][i] = 0.f;
          mma16(S1[h], qa[h][0], qa[h][1], Pk[GB_[h]][0], Pk[GB_[h]][1], Pk[9 + GA_[h]][0], Pk[9 + GB_[h]][0]);
          mma16(S2[h], qa[h][0], qa[h][1], Pk[GB_[h]][0], Pk[GB_[h]][1], Pk[9 + GA_[h]][1], Pk[9 + GB_[h]][1]);
        }
#pragma unroll
        for (int h = 0; h < 4; h++) {
          mma8(S1[h], qc[h][0], qc[h][1], Pk[9 + GC_[h]][0]);
          mma8(S2[h], qc[h][0], qc[h][1], Pk[9 + GC_[h]][1]);
        }
        uint32_t V1[9], V2[9];
#pragma unroll
        for (int i = 0; i < 9; i++) { V1[i] = movm(Pk[18 + i][0]); V2[i] = movm(Pk[18 + i][1]); }
        uint4 hv[6];
#pragma unroll
        for (int i = 0; i < 6; i++) hv[i] = ll_ld128g(hs + i * 512);
        const uint32_t mup = (up0 ? 0xffffu : 0u) | (up1 ? 0xffff0000u : 0u);
        auto finish = [&](const float (&x0)[4], const float (&x1)[4], const uint32_t (&Vb)[9], uint32_t ma, int hi) {
          uint32_t p[4], n[4];
          float rs[4];
#pragma unroll
          for (int h = 0; h < 4; h++) {
            const float m = qmax(fmaxf(x0[h], x1[h])), e0 = ex2(x0[h] - m), e1 = ex2(x1[h] - m);
            n[h] = pack2(e0, e1);
            p[h] = pack2(e0 * rk[hi][0], e1 * rk[hi][1]);
          }
#pragma unroll
          for (int h = 0; h < 4; h += 2) {
            float D[4] = {0.f, 0.f, 0.f, 0.f};
            mma8(D, n[h], n[h + 1], 0x3f803f80u);
            rs[h] = rcp_fast(D[0]); rs[h + 1] = rcp_fast(D[2]);
          }
#pragma unroll
          for (int i = 0; i < 9; i++) {
            const int h = i < 4 ? 0 : i == 4 ? 1 : 2;
            const bool nx = (i == 2 || i == 4 || i == 6) ? 2 * t >= i : i == 3 || i > 6;
            float O[4] = {0.f, 0.f, 0.f, 0.f};
            mma16(O, p[h] & ma, p[h + 1] & ma, p[h] & ~ma, p[h + 1] & ~ma, V1[i], Vb[i]);
            const float r = nx ? rs[h + 1] : rs[h];
            stg32(od + i * 1024 + hi * 256, pack2((nx ? O[2] : O[0]) * r, (nx ? O[3] : O[1]) * r));
          }
        };
        {
          float x0[4], x1[4];
#pragma unroll
          for (int h = 0; h < 4; h++) { x0[h] = (up0 ? S1[h][2] : S2[h][2]) * sc[1][0]; x1[h] = (up1 ? S1[h][3] : S2[h][3]) * sc[1][1]; }
          finish(x0, x1, V2, mup, 1);
        }
        ACLK(2);
        bar_sync(1 + w, 128);
#pragma unroll 1
        for (int it = 0; it < (1 << 20); it++) {
          if (remote) {
            bool ok = true;
#pragma unroll
            for (int i = 0; i < 6; i++) ok = ok && hv[i].z == tag;
            if (__all_sync(~0u, ok)) break;
          }
#pragma unroll
          for (int i = 0; i < 6; i++) hv[i] = ll_ld128g(hs + i * 512);
          if (!remote) break;
        }
        uint32_t H[18];
#pragma unroll
        for (int i = 0; i < 6; i++) { H[HA_[i]] = hv[i].x; H[HA_[i] + 1] = hv[i].y; H[HC_[i]] = hv[i].w; }
        float S0[4][4];
#pragma unroll
        for (int h = 0; h < 4; h++) {
#pragma unroll
          for (int i = 0; i < 4; i++) S0[h][i] = 0.f;
          mma16(S0[h], qa[h][0], qa[h][1], Pk[GB_[h]][0], Pk[GB_[h]][1], H[GA_[h]], H[GB_[h]]);
        }
#pragma unroll
        for (int h = 0; h < 4; h++) mma8(S0[h], qc[h][0], qc[h][1], H[GC_[h]]);
        uint32_t V0[9];
#pragma unroll
        for (int i = 0; i < 9; i++) V0[i] = movm(H[9 + i]);
        ACLK(3);
        {
          const bool nohalo = (rb | q) == 0;
          const float b0 = up0 && nohalo ? -INFINITY : 0.f, b1 = up1 && nohalo ? -INFINITY : 0.f;
          float x0[4], x1[4];
#pragma unroll
          for (int h = 0; h < 4; h++) { x0[h] = fmaf(up0 ? S0[h][0] : S1[h][0], sc[0][0], b0); x1[h] = fmaf(up1 ? S0[h][1] : S1[h][1], sc[0][1], b1); }
          finish(x0, x1, V0, ~mup, 0);
        }
        ACLK(4);
        signal(EV_O);
        ACLK_OUT;
        TRC(tr, w, tb + 2);
      }
      if (c.s) { c.s = 0; c.ph ^= 1; }
      {
        float acc[36];
        const int hw = rb * 2 + w;
        const uint32_t xt = stg + (8 * q + g) * 144 + t * 4;
        uint32_t xm = stg + (8 * q + (lane & 7)) * 144 + (lane & 8) * 576 + (lane & 16);
        uint8_t* xn = xn_block(hw) + j * 9216 + q * 256 + lane * 4;
        uint32_t* sp = (uint32_t*)(Q.ST1 + (hw * 8 + j) * 32 + 8 * q) + lane;
        const uint4* sg = Q.ST1 + (hw * 8 + t) * 32 + 8 * q + g;
        asm volatile("" : "+r"(xm), "+l"(xn), "+l"(sp), "+l"(sg));
        mbar_wait_c(bars + B_RES + w * 8, L);
        TRC(tr, w, tb + 21);
#pragma unroll
        for (int i = 0; i < 18; i++) { const uint32_t x = lds32(xt + (i >> 1) * 16 + (i & 1) * 4608); acc[2 * i] = blo(x); acc[2 * i + 1] = bhi(x); asm volatile("" : "+f"(acc[2 * i]), "+f"(acc[2 * i + 1])); }
        mbar_wait_c(bars + B_WF, L);
        const uint32_t db = dlo(sb, 1152), of = bars + (w ? B_OF + 40 : B_AV + 96);
        uint32_t da[5];
#pragma unroll
        for (int e = 0; e < 5; e++) da[e] = __shfl_sync(~0u, dlo(sb + o_place(w, e), 1024), 0);
        if (w) {
#pragma unroll 1
          for (int kb = q; kb < 9; kb += 4) {
            const uint32_t e = (kb + 1) >> 1;
            mbar_wait_c(bars + B_OF + e * 8, L);
            check(Int<8>{}, sb + o_place(0, e) + (kb && !(kb & 1)) * 8192, z1_block(rb, 0, 0) + kb * 8192);
            if (lane <= !kb) mbar_arrive(bars + B_AV + (12 + e) * 8);
          }
          bar_sync(7, 256);
        }
        mbar_wait_c(of, L & w);
        TRC(tr, w, tb + 3);
        wgmma_fence();
#pragma unroll
        for (int kk = 0; kk < 4; kk++) wgmma_ss_n72(acc, dsc<128, 0>(da[0], kk * 2048), dsc<128, 0>(db, kk * 2304), 1);
        wgmma_commit();
#pragma unroll 1
        for (int h = 0; h < 2; h++) {
#pragma unroll
          for (int u = 0; u < 4; u++) {
            if (!(u & 1)) { mbar_wait_c(of + 8 + h * 16 + u * 4, u && h ? L : L & w); wgmma_fence(); }
            if (u == 3 && h && !w) bar_arrive(7, 256);
#pragma unroll
            for (int kk = 0; kk < 4; kk++) wgmma_ss_n72(acc, dsc<128, 0>(da[1 + (u >> 1)], (u & 1) * 8192 + kk * 2048), dsc<128, 0>(db + h * 2304, (1 + u) * 9216 + kk * 2304), 1);
            if (u != 2) wgmma_commit();
            if (u == 0) { wgmma_wait<1>(); if (lane + w == 0 && h) mbar_arrive(bars + B_X3); }
          }
          da[1] = da[3]; da[2] = da[4];
        }
        RCLK_INIT;
        wgmma_wait<0>();
        RCLK(0);
        if (lane < 2) mbar_arrive_cluster(ebar + B_XD - B_EMPTY + w * 8);
        TRC(tr && P5TRACE != 5, w, tb + 4);
        {
          float s0 = 0.f, s1 = 0.f, q0 = 0.f, q1 = 0.f;
#pragma unroll
          for (int i = 0; i < 36; i++) {
            if (i & 2) { s1 += acc[i]; q1 = fmaf(acc[i], acc[i], q1); } else { s0 += acc[i]; q0 = fmaf(acc[i], acc[i], q0); }
          }
          const bool o1 = t & 1, o2 = t & 2;
          const float ss = (o1 ? s1 : s0) + __shfl_xor_sync(~0u, o1 ? s0 : s1, 1), sq = (o1 ? q1 : q0) + __shfl_xor_sync(~0u, o1 ? q0 : q1, 1);
          const float v = (o2 ? sq : ss) + __shfl_xor_sync(~0u, o2 ? ss : sq, 2);
          asm volatile("st.relaxed.gpu.global.u32 [%0], %1;" ::"l"(sp), "r"(__float_as_uint(v)) : "memory");
        }
        RCLK(1);
        RCLK(2);
        pause<PDEL>(Q.zero);
        uint4 pa, pb;
        auto there = [&](const uint4& a, const uint4& b) { return __all_sync(~0u, max(max(max(a.x, a.y), max(a.z, a.w)), max(max(b.x, b.y), max(b.z, b.w))) != ~0u); };
#pragma unroll 1
        for (int it = 0; it < (1 << 20); it++) {
          pa = ll_ld128(sg); pb = ll_ld128(sg + 128);
          if (there(pa, pb)) break;
        }
        RCLK(3);
        float mean0 = qsum(__uint_as_float(pa.x) + __uint_as_float(pb.x)) * (-1.f / DM), mean1 = qsum(__uint_as_float(pa.y) + __uint_as_float(pb.y)) * (-1.f / DM);
        const float rs0 = GA * rsq_fast(fmaxf(fmaf(qsum(__uint_as_float(pa.z) + __uint_as_float(pb.z)), 1.f / DM, -mean0 * mean0), 0.f) + LN_EPS);
        const float rs1 = GA * rsq_fast(fmaxf(fmaf(qsum(__uint_as_float(pa.w) + __uint_as_float(pb.w)), 1.f / DM, -mean1 * mean1), 0.f) + LN_EPS);
        mean0 *= rs0; mean1 *= rs1;
#pragma unroll
        for (int i = 0; i < 18; i++) {
          const float a = (i & 1) ? rs1 : rs0, b = (i & 1) ? mean1 : mean0;
          stg32(xn + (i >> 1) * 1024 + (i & 1) * 128, pack2(fmaf(acc[2 * i], a, b), fmaf(acc[2 * i + 1], a, b)));
        }
        signal(EV_X1);
        RCLK(4);
        if (w) {
#pragma unroll 1
          for (int u = q; u < 24; u += 4) {
            const uint32_t mb = u < 2 * SPL ? u >= SPL : u & 1, k = u < 2 * SPL ? u - mb * SPL : u >> 1;
            mbar_wait_c(bars + B_AF3 + mb * 96 + k * 8, L);
            SCLK3(u);
            check(Int<6>{}, sb + k * 12288 + mb * 6144, xn_block(rb * 2 + mb) + k * 6144);
            SCLK3(24 + u);
            if (lane <= (u < 2 * SPL)) mbar_arrive(bars + B_AV + (u < SPL ? 12 + k : k) * 8);
          }
          TRVI(lane == 0 && P5TRACE != 5, 5, 56 + L * 4 + q, rp);
        }
#pragma unroll
        for (int u = 0; u < 4; u++)
          stsm4(xm + u * 32, pack2(acc[8 * u], acc[8 * u + 1]), pack2(acc[8 * u + 2], acc[8 * u + 3]), pack2(acc[8 * u + 4], acc[8 * u + 5]), pack2(acc[8 * u + 6], acc[8 * u + 7]));
        asm volatile("stmatrix.sync.aligned.m8n8.x2.shared.b16 [%0], {%1,%2};" ::"r"(xm + 128), "r"(pack2(acc[32], acc[33])), "r"(pack2(acc[34], acc[35])) : "memory");
        fence_async_s();
        signal(EV_XS);
        RCLK(5);
        TRC(tr, w, tb + 5);
        RCLK(6);
        RCLK_OUT;
      }
      {
      float acc[160];
#pragma unroll
      for (int i = 0; i < 160; i++) acc[i] = 0.f;
      float s[2] = {0.f, 0.f}, qq[2] = {0.f, 0.f}, zo = 0.f;
      const uint32_t zp = sb + SM_ZP3 + (tid & 127) * 4;
      auto zstat = [&](int mb, bool on) {
        const bool o1 = t & 1, o2 = t & 2;
        const float ss = ((o1 ? s[1] : s[0]) + __shfl_xor_sync(~0u, o1 ? s[0] : s[1], 1)) * 0x1p60f, sq = (o1 ? qq[1] : qq[0]) + __shfl_xor_sync(~0u, o1 ? qq[0] : qq[1], 1);
        const uint32_t v = __float_as_uint((o2 ? sq : ss) + zo + __shfl_xor_sync(~0u, o2 ? ss : sq, 2));
        asm volatile("{\n.reg .pred p, q, r;\nsetp.eq.u32 p, %4, 1;\nsetp.eq.u32 q, %4, 2;\nsetp.eq.and.u32 r, %5, 0, q;\n@p st.shared.u32 [%0], %2;\n@p bar.arrive 13, 256;\n"
                     "@q st.relaxed.gpu.global.u32 [%1], %2;\n@r mbarrier.arrive.shared::cta.b64 _, [%3];\n}" ::"r"(zp + mb * 512), "l"((uint32_t*)(Q.ZST + ((rb * 2 + mb) * 8 + j) * 32) + (tid & 127)),
                     "r"(v), "r"(bars + B_ZS + mb * 8), "r"(on ? 1 + w : 0), "r"(lane) : "memory");
        s[0] = s[1] = qq[0] = qq[1] = 0.f;
      };
      const uint32_t ebar3 = ebar + (B_E3 - B_EMPTY);
#pragma unroll 1
      for (int half = 0; half < 2; half++) {
        const bool big = half != w;
        auto rel3 = [&](int p) { if (lane < 2) mbar_arrive_cluster(ebar3 + p * 8); };
        if (half + w > 0) bar_sync(6 + w, 256);
        auto pass = [&](auto nk) {
          constexpr int NK = nk.value;
          uint32_t d0 = dlo(sb, 1024), ph = half & ~w, af = bars + B_AV;
          const uint32_t db = dlo(sb + SM_B3, NK == 3 ? 6144 : 2048);
          const bool lead = NK == 3 && !half;
          if (lead) {
#pragma unroll
            for (int u = 0; u < 2 * SPL; u++) {
              const int mb = u / SPL, p = u % SPL;
              if (!mb) mbar_wait_c(bars + B_F3 + p * 8, 0);
              mbar_wait_c(af + (mb ? p : 12 + p) * 8, mb ? L : 1);
              TRC(tr && u == 0, w, tb + 6);
              SCLK2(u);
              if (p == 0) SCLK(mb * 4);
              wgmma_fence();
#pragma unroll
              for (int kk = 0; kk < 3; kk++) {
                wgmma_ss_n128(acc + mb * 80, dsc<128, 0>(d0, p * 12288 + kk * 2048 + mb * 6144), dsc<1024, 1>(db, p * 12288 + kk * 2048), p + kk > 0);
                if (kk == 0 && u > SPL) { wgmma_commit(); wgmma_wait<1>(); rel3(p - 1); }
              }
              wgmma_commit();
            }
          }
#pragma unroll 1
          for (int it = 0; it < 6 / NK; it++) {
#pragma unroll
            for (int p = 0; p < 6; p++) {
              if (p < SPL && lead && it == 0) continue;
              mbar_wait_c(bars + B_F3 + p * 8, ph);
              if (NK == 3) mbar_wait_c(af + p * 8, L);
              TRC(tr && p == 0 && it == 0, w, tb + 6 + half * 4);
              if (lead) SCLK2(12 + it * 6 + p);
              if (NK == 2 ? !(p & 1) : p % 3 == 0) SCLK(half * 11 + (NK == 2 ? it * 3 + p / 2 : it * 2 + p / 3));
              wgmma_fence();
#pragma unroll
              for (int u = 0; u < 2 * NK; u++) {
                const int kk = u >> 1, mb = u & 1, e = p * NK + kk;
                const uint64_t da = dsc<128, 0>(d0, (e / 3) * 12288 + (e % 3) * 2048 + mb * 6144);
                if (NK == 3) wgmma_ss_n128(acc + mb * 80, da, dsc<1024, 1>(db, p * 12288 + kk * 2048), e > 0 || it > 0);
                else wgmma_ss_n160(acc + mb * 80, da, dsc<1024, 1>(db, p * 12288 + kk * 6144), e > 0 || it > 0);
                if (u == 0) { wgmma_commit(); wgmma_wait<1>(); if (p > 0 || it > 0) rel3((p + 5) % 6); }
                if (u == HO3 && p == 5 && it == 6 / NK - 1) bar_arrive(7 - w, 256);
              }
              wgmma_commit();
            }
            d0 += NK * 1536; af += 48;
            ph ^= 1;
          }
        };
        if (big) pass(Int<2>{}); else pass(Int<3>{});
        if (w) { bar_sync(13, 256); zo = __uint_as_float(lds32(zp + half * 512)); }
        if (half) zstat(1, true);
        mbar_wait_c(bars + B_GATE3, L);
        const uint32_t off2 = lds32(sb + SM_OFF);
        const int go = (j & 1) ? (big ? 0 : 20) : (big ? 16 : 0);
        const float* gbp = (const float*)(smem_raw + SM_OFF + 8);
        asm volatile("" : "+l"(gbp));
        uint8_t* zd = half ? z1_block(rb, 0, j) + go * 1024 + (q & 1) * 2048 + (q >> 1) * 512 + lane * 16 : z2_block(rb, j) + q * 9216 + go * 128 + ((g & 3) * 2 + (g >> 2)) * 16 + t * 4;
        wgmma_wait<0>();
        SCLK(half * 11 + 9);
        rel3(5);
        TRC(tr, w, tb + 7 + half * 4);
        auto gelu = [&](auto z2) {
          constexpr int NC = z2.value ? NC2 : NC1;
          float gate[NC], gb = GB, gn = GB;
          uint32_t qa[2][3] = {{0, 0, 0}, {0, 0, 0}};
#pragma unroll
          for (int e = 0; e < NC; e++) gate[e] = GB;
#pragma unroll
          for (int G = 0; G < 20; G++) {
            if (G == 16 && !big) break;
            if (G % (z2.value ? LD2 : LD1) == 0) { gb = gn; if (G < 20 - (z2.value ? LD2 : LD1)) asm volatile("ld.f32 %0, [%1];" : "=f"(gn) : "l"(gbp) : "memory"); }
#pragma unroll
            for (int r = 0; r < 2; r++) {
              float z[2];
              float& gt = gate[(G * 2 + r) % NC];
#pragma unroll
              for (int e = 0; e < 2; e++) {
                const float v = acc[4 * G + 2 * r + e];
                z[e] = fmaf(v, tanh_fast(v * fmaf(v, v, gt)), v);
                if (z2.value) { s[r] = fmaf(z[e], 0x1p-60f, s[r]); qq[r] = fmaf(z[e], z[e], qq[r]); }
              }
              const uint32_t pk = pack2(z[0], z[1]);
              if (z2.value) {
                stg32(zd + G * 128 + r * 4608, hsub2(pk, off2));
                gt = fmaf(qq[r], s[r], gb);
              } else {
                gt = fmaf(__uint_as_float(pk), 0x1p-60f, gb);
                if ((G & 3) == 3) stg128(zd + (G >> 2) * 4096 + r * (8 * ZB), qa[r][0], qa[r][1], qa[r][2], pk);
                else qa[r][G & 3] = pk;
              }
            }
          }
        };
#pragma unroll 1
        for (int mb = 0;; mb++) {
          if (half) gelu(Int<0>{}); else gelu(Int<1>{});
          if (mb) break;
          zstat(0, !half);
#pragma unroll
          for (int i = 0; i < 80; i++) acc[i] = acc[80 + i];
          zd += half ? 1024 : 128 * ZB;
        }
        signal(half ? EV_Z1 : EV_ZN);
        SCLK(half * 11 + 10);
        TRC(tr, w, tb + 8 + half * 4);
      }
      }
      uint32_t hA[18][4];
      {
        float acc[144];
        const float c0 = __uint_as_float(lds32(sb + SM_OFF + 4));
#pragma unroll
        for (int i = 0; i < 144; i++) {
          asm volatile("fma.rn.f32 %0, %1, %2, %3;" : "=f"(acc[i]) : "f"(__uint_as_float(Q.zero)), "f"((float)(i + 2)), "f"(c0));
        }
        uint32_t prev = 0;
        auto stage = [&](int kb) {
          mbar_wait_c(bars + B_FULL + c.s * 8, c.ph);
          TRC(tr && kb == 0, w, tb + 13);
          SCLK(22 + kb);
          const uint32_t st = sb + c.s * ST_BYTES, db = dlo(st + ST_B, 4608), rt = sb + SM_RT + kb * 128 + t * 8;
          uint32_t a[4][4];
#pragma unroll
          for (int kk = 0; kk < 4; kk++) {
            uint32_t r[4];
            ldsm4(r, st + (aoff ^ (kk << 5)));
            const uint2 sc = lds64(rt + kk * 32);
            a[kk][0] = hmul2(__byte_perm(r[0], r[2], 0x5410), sc.x); a[kk][2] = hmul2(__byte_perm(r[0], r[2], 0x7632), sc.y);
            a[kk][1] = hmul2(__byte_perm(r[1], r[3], 0x5410), sc.x); a[kk][3] = hmul2(__byte_perm(r[1], r[3], 0x7632), sc.y);
          }
          if (kb + w == 0) bar_sync(6, 256);
          wgmma_fence();
#pragma unroll
          for (int i = 0; i < 8; i++) {
            const int kk = i & 3, hf = i >> 2;
            wgmma_rs_n144(acc + hf * 72, a[kk], dsc<128, 0>(db, kk * 9216 + hf * 2304), 1);
            if (i == 0) { wgmma_commit(); wgmma_wait<1>(); if (kb) release(prev); }
            if (i == 3) wgmma_commit();
          }
          wgmma_commit();
          prev = c.s; c.next();
        };
#pragma unroll 1
        for (int kb = 0; kb < 32; kb += 2) {
          if (!(kb & 7)) mbar_wait_c(bars + B_RT + kb, L);
          stage(kb);
          stage(kb + 1);
        }
        mbar_wait_c(bars + B_CV + w * 8, L);
        const float gk = 0.5f / GA;
        const float c1 = __uint_as_float(lds32(sb + SM_OFF + 4));
        const float gb0 = -gk * (c1 + __uint_as_float(lds32(sb + SM_CV + w * 256 + (16 * q + g) * 4))), gb1 = -gk * (c1 + __uint_as_float(lds32(sb + SM_CV + w * 256 + (16 * q + g + 8) * 4)));
        if (w == 1) { mbar_wait_c(bars + B_FULL + c.s * 8, c.ph); release(c.s); c.next(); }
        mbar_wait_c(bars + B_FULL + c.s * 8, c.ph);
        const uint32_t zs = sb + c.s * ST_BYTES + ST_B + (tid & 127) * 16;
        uint4 zl, zh;
#pragma unroll
        for (int u = 0; u < 18; u++) {
          if (u == 0) wgmma_wait<1>();
          if (u == 9) {
            wgmma_wait<0>();
            release(prev);
            if (L == 0) signal(EV_PT);
            TRC(tr, w, tb + 14);
            SCLK(54);
          }
          if (!(u & 1)) { zl = lds128(zs + u * 2048); zh = lds128(zs + u * 2048 + 2048); }
          const uint4 z = (u & 1) ? make_uint4(zl.z, zh.z, zl.w, zh.w) : make_uint4(zl.x, zh.x, zl.y, zh.y);
          hA[u][0] = hmul2(z.x, pack2(fmaf(acc[8 * u], gk, gb0), fmaf(acc[8 * u + 1], gk, gb0)));
          hA[u][1] = hmul2(z.y, pack2(fmaf(acc[8 * u + 2], gk, gb1), fmaf(acc[8 * u + 3], gk, gb1)));
          hA[u][2] = hmul2(z.z, pack2(fmaf(acc[8 * u + 4], gk, gb0), fmaf(acc[8 * u + 5], gk, gb0)));
          hA[u][3] = hmul2(z.w, pack2(fmaf(acc[8 * u + 6], gk, gb1), fmaf(acc[8 * u + 7], gk, gb1)));
        }
        __syncwarp();
        release(c.s);
        c.next();
        if (w == 0) { mbar_wait_c(bars + B_FULL + c.s * 8, c.ph); release(c.s); c.next(); }
        TRC(tr, w, tb + 15);
      }
      {
        CLK_INIT;
        if (w == 1) bar_arrive(6, 256);
        uint32_t pk[16];
#pragma unroll
        for (int i = 0; i < 16; i++) pk[i] = 0u;
        auto dump = [&](int p) {
          const uint32_t d = sb + (p & 3) * ST_BYTES, cb = p + j >= 9 ? p + j - 9 : p + j;
          if (lane == 0) asm volatile("cp.async.bulk.wait_group.read 3;" ::: "memory");
          __syncwarp();
#pragma unroll
          for (int u = 0; u < 4; u++) stsm4(d + (aoff ^ (u << 5)), pk[4 * u], pk[4 * u + 1], pk[4 * u + 2], pk[4 * u + 3]);
          fence_async_s();
          __syncwarp();
          tma3d_red_p(lane == 0, &P.red, cb * 64, rb * 64 + q * 16, w, d + w * 8192 + q * 2048);
        };
#pragma unroll 1
        for (int p = 0; p < 9; p++) {
          float acc[32];
          CLK(0);
          mbar_wait_c(bars + B_FULL + c.s * 8, c.ph);
          const uint32_t db = dlo(sb + c.s * ST_BYTES + ST_B, 0);
          CLK(1);
          bar_sync(6 + w, 256);
          CLK(2);
          wgmma_fence();
#pragma unroll
          for (int kk = 0; kk < 18; kk++) {
            wgmma_rs_n64(acc, hA[kk], dsc<1024, 1>(db, kk * 2048), kk != 0);
            if (kk == PPK && (w == 0 || p < 8)) bar_arrive(7 - w, 256);
          }
          wgmma_commit();
          CLK(3);
          if (p > 0) dump(p - 1);
          CLK(5);
          wgmma_wait<0>();
          CLK(4);
          if (L == 0 || p < 5) release(c.s);
          c.next();
#pragma unroll
          for (int i = 0; i < 16; i++) pk[i] = pack2(acc[2 * i], acc[2 * i + 1]);
          if (p == 8) { TRC(tr, w, tb + 16); dump(8); TRC(tr, w, tb + 17); }
        }
        if (lane == 0) asm volatile("cp.async.bulk.wait_group 0;" ::: "memory");
        if (L == 0) signal(EV_PT);
        CLK_OUT;
        TRC(tr, w, tb + 18);
      }
    }
    if ((tid & 127) == 0) Q.flags[(rb * 2 + w) * 32 + FR_EP + j] = epoch + 1;
    if (tid == 0) Q.flags[FJ + j * 32 + FJ_EP + rb] = epoch + 1;
  }
}

typedef CUresult (*EncodeFn)(CUtensorMap*, CUtensorMapDataType, cuuint32_t, void*, const cuuint64_t*, const cuuint64_t*, const cuuint32_t*,
                             const cuuint32_t*, CUtensorMapInterleave, CUtensorMapSwizzle, CUtensorMapL2promotion, CUtensorMapFloatOOBfill);

static void make_map(EncodeFn fn, CUtensorMap* m, const void* ptr, int rank, uint64_t d0, uint64_t d1, uint64_t d2, uint64_t s1, uint64_t s2,
                     uint32_t b0, uint32_t b1, uint32_t b2, CUtensorMapSwizzle swz) {
  cuuint64_t dims[3] = {d0, d1, d2}, strides[2] = {s1, s2};
  cuuint32_t box[3] = {b0, b1, b2}, es[3] = {1, 1, 1};
  fn(m, CU_TENSOR_MAP_DATA_TYPE_BFLOAT16, rank, const_cast<void*>(ptr), dims, strides, box, es, CU_TENSOR_MAP_INTERLEAVE_NONE, swz,
     CU_TENSOR_MAP_L2_PROMOTION_L2_128B, CU_TENSOR_MAP_FLOAT_OOB_FILL_NONE);
}

}

extern "C" void kernel_launch(void* const* d_in, const int* in_sizes, int n_in, void* d_out, int out_size) {
  using namespace mk;
  (void)in_sizes; (void)n_in; (void)out_size;
  static EncodeFn fn = nullptr;
  static Scratch* sc = nullptr;
  if (!fn) {
    cudaDriverEntryPointQueryResult qr;
    cudaGetDriverEntryPoint("cuTensorMapEncodeTiled", (void**)&fn, cudaEnableDefault, &qr);
    cudaGetSymbolAddress((void**)&sc, g_scratch);
    cudaFuncSetAttribute(mega_kernel, cudaFuncAttributeMaxDynamicSharedMemorySize, SM_TOTAL);
  }
  Params p;
  Ptrs a;
  a.x = (const uint8_t*)d_in[0];
  a.wqkv = (const __nv_bfloat16*)d_in[1];
  a.wo = (const __nv_bfloat16*)d_in[2];
  a.w_in = (const __nv_bfloat16*)d_in[4];
  a.w_sp = (const __nv_bfloat16*)d_in[5];
  a.b_sp = (const __nv_bfloat16*)d_in[6];
  a.out = (uint8_t*)d_out;
  a.zero = 0;
  a.WQ = sc->WQ; a.flags = sc->flags; a.CSP = sc->CSP; a.XST = sc->XST; a.HALO = sc->HALO; a.ST1 = sc->ST1; a.ZST = sc->ZST; a.RT = sc->RT; a.Z = sc->Z; a.WO = sc->WO;
  make_map(fn, &p.wsp, a.w_sp, 3, 2048, 1024, 2, 8192, 4096, 64, 64, 2, CU_TENSOR_MAP_SWIZZLE_128B);
  for (int i = 0; i < 2; i++) {
    make_map(fn, &p.act[i], i ? a.out : a.x, 3, DM, 1024, 2, 2304, 1152, 64, 64, 1, CU_TENSOR_MAP_SWIZZLE_128B);
    make_map(fn, &p.row[i], i ? a.out : a.x, 3, 192, 6, 1024, 384, 2304, 192, 3, 8, CU_TENSOR_MAP_SWIZZLE_NONE);
    make_map(fn, &p.res[i], i ? a.out : a.x, 3, DM, 1024, 2, 2304, 1152, 72, 32, 2, CU_TENSOR_MAP_SWIZZLE_NONE);
  }
  make_map(fn, &p.red, d_out, 3, DM, 1024, 2, 2304, 1152, 64, 16, 1, CU_TENSOR_MAP_SWIZZLE_128B);
  for (int i = 0; i < 2; i++) make_map(fn, &p.winb[i], a.w_in + 32 * i, 3, 64, 576, 72 - i, 9216, 128, 64, 16, 3, CU_TENSOR_MAP_SWIZZLE_128B);
  make_map(fn, &p.wins, a.w_in, 3, 64, 576, 72, 9216, 128, 64, 48, 1, CU_TENSOR_MAP_SWIZZLE_128B);
  make_map(fn, &p.wout, d_in[7], 2, 576, 2304, 1, 1152, 0, 64, 144, 1, CU_TENSOR_MAP_SWIZZLE_128B);
  mega_kernel<<<NGRID, 384, SM_TOTAL, cudaStreamPerThread>>>(a, p);
}
```

```cpp
#include <cuda_runtime.h>
#include <cuda.h>
#include <cuda_bf16.h>
#include <stdint.h>

#define MK_TRACE 0
#define MK_DBG 0
#define P5TRACE 0
#define LAG1 1
#define C0S 32.f
#define OFM 0x10u
#define NC2 2
#define NC1 6
#define XRLX 0
#define PDEL 8
#define LD1 4
#define LD2 2
#define ZD1 8
#define ZD2 20
#define WPF 1
#define YPACE 2
#define SPL 3
#define XP0 10
#define EFM 0x33333022
#define EF(i) ((((EFM >> (4 * (i))) & 3) == 3) || (((EFM >> (4 * (i))) >> L) & 1))
#define AEP 2
#define PZI 4
#define KS 1
#define RFI 3
#define XK1 1
#define XK2 2
#define SDEL 10
#define FD0 0
#define FD1 0
#define FD2 0
#define FD3 14
#define FD4 0
#define FD5 0
#define PHM 15
#define APACE 7
#define HO3 1
#define PPK 13

namespace mk {

constexpr int SEQ = 2048, DM = 576, FH = 2304;
constexpr int NCTA = 128;
constexpr int NGRID = 132;
constexpr uint32_t ZB = 36864;
constexpr uint32_t WQ_SL = 72 * 3456;
constexpr uint32_t WO_SL = 72 * 1152;
constexpr float LN_EPS = 1e-5f;
constexpr float GA = 0.3292034911525734f, GB = 2.423681954311584f;

constexpr uint32_t ST_BYTES = 53248, ST_B = 16384, NST = 4;
constexpr uint32_t SM_STG = NST * ST_BYTES;
constexpr uint32_t SM_BAR = SM_STG + 2 * 9216, B_OFF = 896;
constexpr uint32_t SM_OFF = SM_BAR + B_OFF;
constexpr uint32_t SM_TOTAL = SM_BAR + 1024;
constexpr uint32_t SM_RT = SM_STG + 9216, SM_CV = SM_STG + 17408, SM_WT = SM_STG;
constexpr uint32_t SM_WOI = 44032, SM_CSQ = 49280, SM_XST = 50176;
enum { EV_PT = 0, EV_O = 1, EV_X1 = 2, EV_ZN = 3, EV_Z1 = 4, EV_XS = 5, EV_N = 6 };
constexpr uint32_t B_FULL = 0, B_FULLA = 32, B_RES = 96, B_WT = 112, B_GATE3 = 128, B_Z1 = 136, B_ZOK = 144, B_CV = 152, B_XRW = 168, B_F3 = 184, B_WF = 232, B_OF = 240,
                   B_RT = 320, B_AF3 = 352, B_RB = 544,
                   B_AD = 576, B_S5 = 608, B_AV = 616,
                   B_CSQ = 760,
                   B_LAG = 768, B_X3 = 776, B_ZS = 784, B_EVT = 800,
                   B_IMG = 912, B_WOI = 920, B_E3 = 928, B_XD = 976,
                   B_EMPTY = 992;
constexpr uint32_t SM_B3 = 9 * 16384, SM_ZP3 = SM_STG + 8192;

enum { FR_X2 = 0, FR_O = 1, FR_X1 = 3, FR_XR = 5, FR_OL = 7, FR_PZ = 9, FR_EP = 16, FJ = 32 * 32, FJ_WQ = 0, FJ_WO = 1, FJ_ZN = 3, FJ_P4 = 5, FJ_EP = 16, F_N = FJ + 8 * 32 };

struct Scratch {
  alignas(1024) uint32_t flags[F_N];
  alignas(1024) float CSP[2 * NCTA * 216];
  alignas(1024) uint2 RT[SEQ];
  alignas(1024) uint4 XST[2 * SEQ];
  alignas(1024) uint4 ST1[SEQ * 4];
  alignas(1024) uint4 ZST[SEQ * 4];
  alignas(1024) uint4 HALO[32 * 8 * 6 * 32];
  alignas(1024) uint8_t WO[8 * WO_SL];
  alignas(1024) uint8_t WQ[8 * WQ_SL];
  alignas(1024) uint8_t Z[576 * ZB];
};
__device__ Scratch g_scratch;

struct Ptrs {
  const __nv_bfloat16* wqkv;
  uint8_t* WQ;
  uint32_t* flags;
  float* CSP;
  const uint8_t* x;
  uint32_t zero;
  uint4 *XST, *HALO, *ST1, *ZST;
  uint2* RT;
  uint8_t *Z, *WO, *out;
  const __nv_bfloat16 *wo, *w_in, *w_sp, *b_sp;
};
struct Params {
  CUtensorMap wsp, winb[2], wins, wout;
  CUtensorMap act[2];
  CUtensorMap res[2];
  CUtensorMap row[2];
  CUtensorMap red;
};

__device__ __forceinline__ uint32_t smem_u32(const void* p) { return (uint32_t)__cvta_generic_to_shared(p); }
__device__ __forceinline__ void mbar_init(uint32_t bar, uint32_t cnt) { asm volatile("mbarrier.init.shared::cta.b64 [%0], %1;" ::"r"(bar), "r"(cnt)); }
__device__ __forceinline__ void mbar_arrive(uint32_t bar) { asm volatile("mbarrier.arrive.shared::cta.b64 _, [%0];" ::"r"(bar) : "memory"); }
__device__ __forceinline__ void mbar_wait(uint32_t bar, uint32_t parity) {
  asm volatile(
      "{\n.reg .pred p;\n.reg .u32 c;\nmov.u32 c, 0;\nLAB_WAIT:\n"
      "mbarrier.try_wait.parity.shared::cta.b64 p, [%0], %1;\n@p bra LAB_DONE;\n"
      "add.u32 c, c, 1;\nsetp.lt.u32 p, c, 0x100000;\n@p bra LAB_WAIT;\ntrap;\nLAB_DONE:\n}" ::"r"(bar), "r"(parity)
      : "memory");
}
__device__ __forceinline__ void mbar_wait_c(uint32_t bar, uint32_t parity) {
  asm volatile("{\n.reg .pred p;\nLAB_WAIT:\nmbarrier.try_wait.parity.shared::cta.b64 p, [%0], %1;\n@!p bra LAB_WAIT;\n}" ::"r"(bar), "r"(parity) : "memory");
}
__device__ __forceinline__ void flag_wait(const uint32_t* f, uint32_t target) {
  asm volatile(
      "{\n.reg .pred p;\n.reg .u32 c, v;\nmov.u32 c, 0;\nLAB_WAIT:\n"
      "ld.relaxed.gpu.global.u32 v, [%0];\nsub.u32 v, v, %1;\nsetp.ge.s32 p, v, 0;\n@p bra LAB_DONE;\n"
      "add.u32 c, c, 1;\nsetp.lt.u32 p, c, 0x400000;\n@p bra LAB_WAIT;\ntrap;\nLAB_DONE:\nfence.acquire.gpu;\n}" ::"l"(f), "r"(target)
      : "memory");
}
__device__ __forceinline__ void fence_gpu() { asm volatile("fence.acq_rel.gpu;" ::: "memory"); }
__device__ __forceinline__ void fence_async_g() { asm volatile("fence.proxy.async.global;" ::: "memory"); }
__device__ __forceinline__ void fence_async_s() { asm volatile("fence.proxy.async.shared::cta;" ::: "memory"); }
__device__ __forceinline__ uint32_t elect_one() {
  uint32_t p; asm volatile("{\n.reg .pred P;\nelect.sync _|P, 0xffffffff;\nselp.u32 %0, 1, 0, P;\n}" : "=r"(p)); return p;
}
__device__ __forceinline__ void expect_tx_p(uint32_t el, uint32_t bar, uint32_t bytes) {
  asm volatile("{\n.reg .pred P;\nsetp.ne.u32 P, %2, 0;\n@P mbarrier.arrive.expect_tx.shared::cta.b64 _, [%0], %1;\n}" ::"r"(bar), "r"(bytes), "r"(el) : "memory");
}
__device__ __forceinline__ void bulk_load_p(uint32_t el, uint32_t dst, const void* src, uint32_t bytes, uint32_t bar) {
  asm volatile("{\n.reg .pred P;\nsetp.ne.u32 P, %4, 0;\n@P cp.async.bulk.shared::cluster.global.mbarrier::complete_tx::bytes [%0], [%1], %2, [%3];\n}" ::"r"(dst), "l"(src), "r"(bytes), "r"(bar), "r"(el) : "memory");
}
__device__ __forceinline__ uint64_t policy_evict_first() { uint64_t p; asm("createpolicy.fractional.L2::evict_first.b64 %0, 1.0;" : "=l"(p)); return p; }
__device__ __forceinline__ void bulk_load_h(uint32_t el, uint32_t dst, const void* src, uint32_t bytes, uint32_t bar, bool ef, uint64_t pol) {
  if (ef) {
    asm volatile("{\n.reg .pred P;\nsetp.ne.u32 P, %4, 0;\n@P cp.async.bulk.shared::cluster.global.mbarrier::complete_tx::bytes.L2::cache_hint [%0], [%1], %2, [%3], %5;\n}" ::"r"(dst), "l"(src), "r"(bytes), "r"(bar), "r"(el), "l"(pol) : "memory");
  } else {
    asm volatile("{\n.reg .pred P;\nsetp.ne.u32 P, %4, 0;\n@P cp.async.bulk.shared::cluster.global.mbarrier::complete_tx::bytes [%0], [%1], %2, [%3];\n}" ::"r"(dst), "l"(src), "r"(bytes), "r"(bar), "r"(el) : "memory");
  }
}
__device__ __forceinline__ void bulk_mc_h(uint32_t el, uint32_t dst, const void* src, uint32_t bytes, uint32_t bar, bool ef, uint64_t pol) {
  if (ef) {
    asm volatile("{\n.reg .pred P;\nsetp.ne.u32 P, %4, 0;\n@P cp.async.bulk.shared::cluster.global.mbarrier::complete_tx::bytes.multicast::cluster.L2::cache_hint [%0], [%1], %2, [%3], %5, %6;\n}" ::"r"(dst), "l"(src), "r"(bytes), "r"(bar), "r"(el), "h"((uint16_t)3), "l"(pol) : "memory");
  } else {
    asm volatile("{\n.reg .pred P;\nsetp.ne.u32 P, %4, 0;\n@P cp.async.bulk.shared::cluster.global.mbarrier::complete_tx::bytes.multicast::cluster [%0], [%1], %2, [%3], %5;\n}" ::"r"(dst), "l"(src), "r"(bytes), "r"(bar), "r"(el), "h"((uint16_t)3) : "memory");
  }
}
__device__ __forceinline__ void tma3d_h(uint32_t el, uint32_t dst, const CUtensorMap* m, int c0, int c1, int c2, uint32_t bar, bool ef, uint64_t pol) {
  if (ef) {
    asm volatile("{\n.reg .pred P;\nsetp.ne.u32 P, %6, 0;\n@P cp.async.bulk.tensor.3d.shared::cluster.global.mbarrier::complete_tx::bytes.L2::cache_hint [%0], [%1, {%3, %4, %5}], [%2], %7;\n}" ::"r"(dst), "l"(m), "r"(bar), "r"(c0), "r"(c1), "r"(c2), "r"(el), "l"(pol) : "memory");
  } else {
    asm volatile("{\n.reg .pred P;\nsetp.ne.u32 P, %6, 0;\n@P cp.async.bulk.tensor.3d.shared::cluster.global.mbarrier::complete_tx::bytes [%0], [%1, {%3, %4, %5}], [%2];\n}" ::"r"(dst), "l"(m), "r"(bar), "r"(c0), "r"(c1), "r"(c2), "r"(el) : "memory");
  }
}
__device__ __forceinline__ void tma2d_mc_h(uint32_t el, uint32_t dst, const CUtensorMap* m, int c0, int c1, uint32_t bar, bool ef, uint64_t pol) {
  if (ef) {
    asm volatile("{\n.reg .pred P;\nsetp.ne.u32 P, %5, 0;\n@P cp.async.bulk.tensor.2d.shared::cluster.global.mbarrier::complete_tx::bytes.multicast::cluster.L2::cache_hint [%0], [%1, {%3, %4}], [%2], %6, %7;\n}" ::"r"(dst), "l"(m), "r"(bar), "r"(c0), "r"(c1), "r"(el), "h"((uint16_t)3), "l"(pol) : "memory");
  } else {
    asm volatile("{\n.reg .pred P;\nsetp.ne.u32 P, %5, 0;\n@P cp.async.bulk.tensor.2d.shared::cluster.global.mbarrier::complete_tx::bytes.multicast::cluster [%0], [%1, {%3, %4}], [%2], %6;\n}" ::"r"(dst), "l"(m), "r"(bar), "r"(c0), "r"(c1), "r"(el), "h"((uint16_t)3) : "memory");
  }
}
__device__ __forceinline__ void tma3d_mc_h(uint32_t el, uint32_t dst, const CUtensorMap* m, int c0, int c1, int c2, uint32_t bar, bool ef, uint64_t pol) {
  if (ef) {
    asm volatile("{\n.reg .pred P;\nsetp.ne.u32 P, %6, 0;\n@P cp.async.bulk.tensor.3d.shared::cluster.global.mbarrier::complete_tx::bytes.multicast::cluster.L2::cache_hint [%0], [%1, {%3, %4, %5}], [%2], %7, %8;\n}" ::"r"(dst), "l"(m), "r"(bar), "r"(c0), "r"(c1), "r"(c2), "r"(el), "h"((uint16_t)3), "l"(pol) : "memory");
  } else {
    asm volatile("{\n.reg .pred P;\nsetp.ne.u32 P, %6, 0;\n@P cp.async.bulk.tensor.3d.shared::cluster.global.mbarrier::complete_tx::bytes.multicast::cluster [%0], [%1, {%3, %4, %5}], [%2], %7;\n}" ::"r"(dst), "l"(m), "r"(bar), "r"(c0), "r"(c1), "r"(c2), "r"(el), "h"((uint16_t)3) : "memory");
  }
}
__device__ __forceinline__ void mbar_arrive_cluster(uint32_t addr) { asm volatile("mbarrier.arrive.shared::cluster.b64 _, [%0];" ::"r"(addr) : "memory"); }
__device__ __forceinline__ uint32_t mapa(uint32_t addr, uint32_t rank) { uint32_t r; asm("mapa.shared::cluster.u32 %0, %1, %2;" : "=r"(r) : "r"(addr), "r"(rank)); return r; }
__device__ __forceinline__ void bulk_store_p(uint32_t el, void* dst, uint32_t src, uint32_t bytes) {
  asm volatile("{\n.reg .pred P;\nsetp.ne.u32 P, %3, 0;\n@P cp.async.bulk.global.shared::cta.bulk_group [%0], [%1], %2;\n}" ::"l"(dst), "r"(src), "r"(bytes), "r"(el) : "memory");
}
__device__ __forceinline__ void flag_release_p(uint32_t el, uint32_t* f) {
  asm volatile("{\n.reg .pred P;\nsetp.ne.u32 P, %1, 0;\nfence.proxy.async;\n@P red.relaxed.gpu.global.add.u32 [%0], 1;\n}" ::"l"(f), "r"(el) : "memory");
}
__device__ __forceinline__ void flag_add_p(uint32_t el, uint32_t* f) {
  asm volatile("{\n.reg .pred P;\nsetp.ne.u32 P, %1, 0;\n@P red.relaxed.gpu.global.add.u32 [%0], 1;\n}" ::"l"(f), "r"(el) : "memory");
}
__device__ __forceinline__ void prefetch_l2(const void* src, uint32_t bytes) { asm volatile("cp.async.bulk.prefetch.L2.global [%0], %1;" ::"l"(src), "r"(bytes) : "memory"); }
__device__ __forceinline__ void prefetch_map(const CUtensorMap* m) { asm volatile("prefetch.tensormap [%0];" ::"l"(m) : "memory"); }
__device__ __forceinline__ void wgmma_fence() { asm volatile("wgmma.fence.sync.aligned;" ::: "memory"); }
__device__ __forceinline__ void wgmma_commit() { asm volatile("wgmma.commit_group.sync.aligned;" ::: "memory"); }
template <int N> __device__ __forceinline__ void wgmma_wait() { asm volatile("wgmma.wait_group.sync.aligned %0;" ::"n"(N) : "memory"); }
__device__ __forceinline__ uint32_t dlo(uint32_t addr, uint32_t lbo) { return ((addr & 0x3FFFF) >> 4) + ((lbo >> 4) << 16); }
template <uint32_t SBO, uint32_t SWZ> __device__ __forceinline__ uint64_t dsc(uint32_t lo, uint32_t off) {
  uint64_t d; asm("mov.b64 %0, {%1, %2};" : "=l"(d) : "r"(lo + (off >> 4)), "n"((SBO >> 4) | (SWZ << 30))); return d;
}
template <int R> __device__ __forceinline__ void reg_alloc() { asm volatile("setmaxnreg.inc.sync.aligned.u32 %0;" ::"n"(R)); }
template <int R> __device__ __forceinline__ void reg_dealloc() { asm volatile("setmaxnreg.dec.sync.aligned.u32 %0;" ::"n"(R)); }
__device__ __forceinline__ void bar_sync(int id, int n) { asm volatile("bar.sync %0, %1;" ::"r"(id), "r"(n) : "memory"); }
__device__ __forceinline__ void bar_arrive(int id, int n) { asm volatile("bar.arrive %0, %1;" ::"r"(id), "r"(n) : "memory"); }
__device__ __forceinline__ void ldsm4(uint32_t* r, uint32_t addr) {
  asm volatile("ldmatrix.sync.aligned.m8n8.x4.shared.b16 {%0,%1,%2,%3}, [%4];" : "=r"(r[0]), "=r"(r[1]), "=r"(r[2]), "=r"(r[3]) : "r"(addr) : "memory");
}
__device__ __forceinline__ uint32_t movm(uint32_t a) { uint32_t d; asm volatile("movmatrix.sync.aligned.m8n8.trans.b16 %0, %1;" : "=r"(d) : "r"(a)); return d; }
__device__ __forceinline__ void mma16(float* c, uint32_t a0, uint32_t a1, uint32_t a2, uint32_t a3, uint32_t b0, uint32_t b1) {
  asm volatile("mma.sync.aligned.m16n8k16.row.col.f32.bf16.bf16.f32 {%0,%1,%2,%3}, {%4,%5,%6,%7}, {%8,%9}, {%0,%1,%2,%3};"
               : "+f"(c[0]), "+f"(c[1]), "+f"(c[2]), "+f"(c[3]) : "r"(a0), "r"(a1), "r"(a2), "r"(a3), "r"(b0), "r"(b1));
}
__device__ __forceinline__ void mma8(float* c, uint32_t a0, uint32_t a1, uint32_t b0) {
  asm volatile("mma.sync.aligned.m16n8k8.row.col.f32.bf16.bf16.f32 {%0,%1,%2,%3}, {%4,%5}, {%6}, {%0,%1,%2,%3};"
               : "+f"(c[0]), "+f"(c[1]), "+f"(c[2]), "+f"(c[3]) : "r"(a0), "r"(a1), "r"(b0));
}
__device__ __forceinline__ uint32_t pack2(float lo, float hi) { uint32_t r; asm("cvt.rn.bf16x2.f32 %0, %1, %2;" : "=r"(r) : "f"(hi), "f"(lo)); return r; }
__device__ __forceinline__ float blo(uint32_t v) { return __uint_as_float(v << 16); }
__device__ __forceinline__ float bhi(uint32_t v) { return __uint_as_float(v & 0xffff0000u); }
__device__ __forceinline__ float tanh_fast(float x) { float y; asm("tanh.approx.f32 %0, %1;" : "=f"(y) : "f"(x)); return y; }
__device__ __forceinline__ float rcp_fast(float x) { float y; asm("rcp.approx.ftz.f32 %0, %1;" : "=f"(y) : "f"(x)); return y; }
__device__ __forceinline__ float rsq_fast(float x) { float y; asm("rsqrt.approx.ftz.f32 %0, %1;" : "=f"(y) : "f"(x)); return y; }
__device__ __forceinline__ float ex2(float x) { float y; asm("ex2.approx.ftz.f32 %0, %1;" : "=f"(y) : "f"(x)); return y; }
__device__ __forceinline__ float qsum(float v) { v += __shfl_xor_sync(~0u, v, 1); v += __shfl_xor_sync(~0u, v, 2); return v; }
__device__ __forceinline__ float qmax(float v) { v = fmaxf(v, __shfl_xor_sync(~0u, v, 1)); v = fmaxf(v, __shfl_xor_sync(~0u, v, 2)); return v; }
__device__ __forceinline__ void stg32(void* p, uint32_t v) { asm volatile("st.global.u32 [%0], %1;" ::"l"(p), "r"(v) : "memory"); }
__device__ __forceinline__ void stg128(void* p, uint32_t a, uint32_t b, uint32_t c, uint32_t d) { asm volatile("st.global.v4.u32 [%0], {%1,%2,%3,%4};" ::"l"(p), "r"(a), "r"(b), "r"(c), "r"(d) : "memory"); }
__device__ __forceinline__ uint32_t ldcg32(const void* p) { uint32_t v; asm volatile("ld.global.L1::no_allocate.u32 %0, [%1];" : "=r"(v) : "l"(p) : "memory"); return v; }
__device__ __forceinline__ void stg128_if(bool c, void* p, uint32_t a, uint32_t b, uint32_t cc, uint32_t d) {
  asm volatile("{\n.reg .pred P;\nsetp.ne.u32 P, %5, 0;\n@P st.global.v4.u32 [%0], {%1,%2,%3,%4};\n}" ::"l"(p), "r"(a), "r"(b), "r"(cc), "r"(d), "r"((uint32_t)c) : "memory");
}
__device__ __forceinline__ uint2 lds64(uint32_t a) { uint2 v; asm volatile("ld.shared.v2.u32 {%0,%1}, [%2];" : "=r"(v.x), "=r"(v.y) : "r"(a) : "memory"); return v; }
__device__ __forceinline__ uint4 ldcg128(const void* p) { uint4 v; asm volatile("ld.global.cg.v4.u32 {%0,%1,%2,%3}, [%4];" : "=r"(v.x), "=r"(v.y), "=r"(v.z), "=r"(v.w) : "l"(p) : "memory"); return v; }
__device__ __forceinline__ uint32_t ldnc16(const void* p) { uint16_t v; asm volatile("ld.global.nc.u16 %0, [%1];" : "=h"(v) : "l"(p)); return v; }
__device__ __forceinline__ uint4 ldnc128(const void* p) { uint4 v; asm volatile("ld.global.nc.v4.u32 {%0,%1,%2,%3}, [%4];" : "=r"(v.x), "=r"(v.y), "=r"(v.z), "=r"(v.w) : "l"(p)); return v; }
__device__ __forceinline__ void cp_async16(uint32_t dst, const void* src) { asm volatile("cp.async.cg.shared.global [%0], [%1], 16;" ::"r"(dst), "l"(src) : "memory"); }
__device__ __forceinline__ uint32_t hsub2(uint32_t a, uint32_t b) { uint32_t d; asm("sub.rn.bf16x2 %0, %1, %2;" : "=r"(d) : "r"(a), "r"(b)); return d; }
__device__ __forceinline__ void stg32_if(bool c, void* p, uint32_t v) {
  asm volatile("{\n.reg .pred P;\nsetp.ne.u32 P, %2, 0;\n@P st.global.u32 [%0], %1;\n}" ::"l"(p), "r"(v), "r"((uint32_t)c) : "memory");
}
__device__ __forceinline__ float wsum(float v) { for (int o = 16; o; o >>= 1) v += __shfl_xor_sync(~0u, v, o); return v; }
__device__ __forceinline__ uint32_t hmul2(uint32_t a, uint32_t b) { uint32_t d; asm("mul.rn.bf16x2 %0, %1, %2;" : "=r"(d) : "r"(a), "r"(b)); return d; }
__device__ __forceinline__ void sts32(uint32_t a, uint32_t v) { asm volatile("st.shared.u32 [%0], %1;" ::"r"(a), "r"(v) : "memory"); }
__device__ __forceinline__ uint32_t lds32(uint32_t a) { uint32_t v; asm volatile("ld.shared.u32 %0, [%1];" : "=r"(v) : "r"(a) : "memory"); return v; }
__device__ __forceinline__ void sts128(uint32_t a, uint32_t x, uint32_t y, uint32_t z, uint32_t w) { asm volatile("st.shared.v4.u32 [%0], {%1,%2,%3,%4};" ::"r"(a), "r"(x), "r"(y), "r"(z), "r"(w) : "memory"); }
__device__ __forceinline__ uint4 lds128(uint32_t a) { uint4 v; asm volatile("ld.shared.v4.u32 {%0,%1,%2,%3}, [%4];" : "=r"(v.x), "=r"(v.y), "=r"(v.z), "=r"(v.w) : "r"(a) : "memory"); return v; }
__device__ __forceinline__ void ll_st64(uint2* p, uint32_t v, uint32_t tag) {
  asm volatile("{\n.reg .b64 r;\nmov.b64 r, {%1,%2};\nst.relaxed.gpu.global.b64 [%0], r;\n}" ::"l"(p), "r"(v), "r"(tag) : "memory");
}
__device__ __forceinline__ uint2 ll_ld64(const uint2* p) {
  uint2 v; asm volatile("{\n.reg .b64 r;\nld.relaxed.gpu.global.b64 r, [%2];\nmov.b64 {%0,%1}, r;\n}" : "=r"(v.x), "=r"(v.y) : "l"(p) : "memory"); return v;
}
__device__ __forceinline__ void ll_st128(uint4* p, float a, float b, uint32_t tag, float c = 0.f) {
  asm volatile("{\n.reg .b128 r;\n.reg .b64 lo, hi;\nmov.b64 lo, {%1,%2};\nmov.b64 hi, {%3,%4};\nmov.b128 r, {lo, hi};\nst.relaxed.gpu.global.b128 [%0], r;\n}" ::"l"(p), "r"(__float_as_uint(a)), "r"(__float_as_uint(b)), "r"(tag), "r"(__float_as_uint(c)) : "memory");
}
__device__ __forceinline__ uint4 ll_ld128g(const void* p) {
  uint4 v; asm volatile("{\n.reg .b128 r;\n.reg .b64 lo, hi;\nld.relaxed.gpu.b128 r, [%4];\nmov.b128 {lo, hi}, r;\nmov.b64 {%0,%1}, lo;\nmov.b64 {%2,%3}, hi;\n}" : "=r"(v.x), "=r"(v.y), "=r"(v.z), "=r"(v.w) : "l"(p) : "memory"); return v;
}
__device__ __forceinline__ uint4 ll_ld128(const uint4* p) {
  uint4 v; asm volatile("{\n.reg .b128 r;\n.reg .b64 lo, hi;\nld.relaxed.gpu.global.b128 r, [%4];\nmov.b128 {lo, hi}, r;\nmov.b64 {%0,%1}, lo;\nmov.b64 {%2,%3}, hi;\n}" : "=r"(v.x), "=r"(v.y), "=r"(v.z), "=r"(v.w) : "l"(p) : "memory"); return v;
}
__device__ __forceinline__ void publish_p(uint32_t el, uint32_t* f) {
  asm volatile("{\n.reg .pred P;\nsetp.ne.u32 P, %1, 0;\n@P cp.async.bulk.commit_group;\n@P cp.async.bulk.wait_group 0;\n@P red.release.gpu.global.add.u32 [%0], 1;\n}" ::"l"(f), "r"(el) : "memory");
}
__device__ __forceinline__ void tma3d_red_p(uint32_t el, const CUtensorMap* m, int c0, int c1, int c2, uint32_t src) {
  asm volatile("{\n.reg .pred P;\nsetp.ne.u32 P, %5, 0;\n@P cp.reduce.async.bulk.tensor.3d.global.shared::cta.add.tile.bulk_group [%0, {%2, %3, %4}], [%1];\n@P cp.async.bulk.commit_group;\n}" ::"l"(m), "r"(src), "r"(c0), "r"(c1), "r"(c2), "r"(el) : "memory");
}
__device__ __forceinline__ void stsm4(uint32_t addr, uint32_t a, uint32_t b, uint32_t c, uint32_t d) {
  asm volatile("stmatrix.sync.aligned.m8n8.x4.shared.b16 [%0], {%1,%2,%3,%4};" ::"r"(addr), "r"(a), "r"(b), "r"(c), "r"(d) : "memory");
}
__device__ __forceinline__ void sts64(uint32_t a, uint32_t x, uint32_t y) { asm volatile("st.shared.v2.u32 [%0], {%1,%2};" ::"r"(a), "r"(x), "r"(y) : "memory"); }
__device__ __forceinline__ void ll_st128_if(bool on, uint4* p, float a, float b, uint32_t tag) {
  asm volatile("{\n.reg .pred P;\n.reg .b128 r;\n.reg .b64 lo, hi;\nsetp.ne.u32 P, %4, 0;\nmov.b64 lo, {%1,%2};\nmov.b64 hi, {%3,%3};\nmov.b128 r, {lo, hi};\n@P st.relaxed.gpu.global.b128 [%0], r;\n}" ::"l"(p), "r"(__float_as_uint(a)), "r"(__float_as_uint(b)), "r"(tag), "r"((uint32_t)on) : "memory");
}
__device__ __forceinline__ uint4 ldnc128_if(bool c, const void* p) {
  uint4 v = make_uint4(0u, 0u, 0u, 0u);
  asm volatile("{\n.reg .pred P;\nsetp.ne.u32 P, %5, 0;\n@P ld.global.nc.v4.u32 {%0,%1,%2,%3}, [%4];\n}" : "+r"(v.x), "+r"(v.y), "+r"(v.z), "+r"(v.w) : "l"(p), "r"((uint32_t)c));
  return v;
}
__device__ __forceinline__ uint32_t hfma2(uint32_t a, uint32_t b, uint32_t c) { uint32_t d; asm("fma.rn.bf16x2 %0, %1, %2, %3;" : "=r"(d) : "r"(a), "r"(b), "r"(c)); return d; }
__device__ __forceinline__ float2 lds64f(uint32_t a) { float2 v; asm volatile("ld.shared.v2.f32 {%0,%1}, [%2];" : "=f"(v.x), "=f"(v.y) : "r"(a) : "memory"); return v; }
#define TRC(cond, role, idx) do {} while (0)
#define TRV(role, idx, v) do {} while (0)
#define TRVI(c, role, idx, v) do {} while (0)

#define ACLK_INIT do {} while (0)
#define ACLK(i) do {} while (0)
#define ACLK_OUT do {} while (0)
#define QCLK(i) do {} while (0)
#define PH 1
#define RCLK(i) do {} while (0)
#define RCLK_INIT do {} while (0)
#define RCLK_OUT do {} while (0)
#define SCLK(i) do {} while (0)
#define SCLK2(i) do {} while (0)
#define SCLK3(i) do {} while (0)
#define PL 1
#define PCLK(i) do {} while (0)
#define PQ 1
#define CLK_INIT do {} while (0)
#define CLK(i) do {} while (0)
#define CLK_OUT do {} while (0)

__device__ __forceinline__ void wgmma_ss_n216(float* d, uint64_t da, uint64_t db, int scaleD) {
  asm volatile("{\n.reg .pred p;\nsetp.ne.b32 p, %110, 0;\nwgmma.mma_async.sync.aligned.m64n216k16.f32.bf16.bf16 "
    "{%0,%1,%2,%3,%4,%5,%6,%7,%8,%9,%10,%11,%12,%13,%14,%15,%16,%17,%18,%19,%20,%21,%22,%23,%24,%25,%26,%27,%28,%29,%30,%31,%32,%33,%34,%35,%36,%37,%38,%39,%40,%41,%42,%43,%44,%45,%46,%47,%48,%49,%50,%51,%52,%53,%54,%55,%56,%57,%58,%59,%60,%61,%62,%63,%64,%65,%66,%67,%68,%69,%70,%71,%72,%73,%74,%75,%76,%77,%78,%79,%80,%81,%82,%83,%84,%85,%86,%87,%88,%89,%90,%91,%92,%93,%94,%95,%96,%97,%98,%99,%100,%101,%102,%103,%104,%105,%106,%107}, "
    "%108, %109, p, 1, 1, 0, 1;\n}\n"
    : "+f"(d[0]), "+f"(d[1]), "+f"(d[2]), "+f"(d[3]), "+f"(d[4]), "+f"(d[5]), "+f"(d[6]), "+f"(d[7]), "+f"(d[8]), "+f"(d[9]), "+f"(d[10]), "+f"(d[11]), "+f"(d[12]), "+f"(d[13]), "+f"(d[14]), "+f"(d[15]), "+f"(d[16]), "+f"(d[17]), "+f"(d[18]), "+f"(d[19]), "+f"(d[20]), "+f"(d[21]), "+f"(d[22]), "+f"(d[23]), "+f"(d[24]), "+f"(d[25]), "+f"(d[26]), "+f"(d[27]), "+f"(d[28]), "+f"(d[29]), "+f"(d[30]), "+f"(d[31]), "+f"(d[32]), "+f"(d[33]), "+f"(d[34]), "+f"(d[35]), "+f"(d[36]), "+f"(d[37]), "+f"(d[38]), "+f"(d[39]), "+f"(d[40]), "+f"(d[41]), "+f"(d[42]), "+f"(d[43]), "+f"(d[44]), "+f"(d[45]), "+f"(d[46]), "+f"(d[47]), "+f"(d[48]), "+f"(d[49]), "+f"(d[50]), "+f"(d[51]), "+f"(d[52]), "+f"(d[53]), "+f"(d[54]), "+f"(d[55]), "+f"(d[56]), "+f"(d[57]), "+f"(d[58]), "+f"(d[59]), "+f"(d[60]), "+f"(d[61]), "+f"(d[62]), "+f"(d[63]), "+f"(d[64]), "+f"(d[65]), "+f"(d[66]), "+f"(d[67]), "+f"(d[68]), "+f"(d[69]), "+f"(d[70]), "+f"(d[71]), "+f"(d[72]), "+f"(d[73]), "+f"(d[74]), "+f"(d[75]), "+f"(d[76]), "+f"(d[77]), "+f"(d[78]), "+f"(d[79]), "+f"(d[80]), "+f"(d[81]), "+f"(d[82]), "+f"(d[83]), "+f"(d[84]), "+f"(d[85]), "+f"(d[86]), "+f"(d[87]), "+f"(d[88]), "+f"(d[89]), "+f"(d[90]), "+f"(d[91]), "+f"(d[92]), "+f"(d[93]), "+f"(d[94]), "+f"(d[95]), "+f"(d[96]), "+f"(d[97]), "+f"(d[98]), "+f"(d[99]), "+f"(d[100]), "+f"(d[101]), "+f"(d[102]), "+f"(d[103]), "+f"(d[104]), "+f"(d[105]), "+f"(d[106]), "+f"(d[107])
    : "l"(da), "l"(db), "r"(scaleD));
}
__device__ __forceinline__ void wgmma_ss_n72(float* d, uint64_t da, uint64_t db, int scaleD) {
  asm volatile("{\n.reg .pred p;\nsetp.ne.b32 p, %38, 0;\nwgmma.mma_async.sync.aligned.m64n72k16.f32.bf16.bf16 "
    "{%0,%1,%2,%3,%4,%5,%6,%7,%8,%9,%10,%11,%12,%13,%14,%15,%16,%17,%18,%19,%20,%21,%22,%23,%24,%25,%26,%27,%28,%29,%30,%31,%32,%33,%34,%35}, "
    "%36, %37, p, 1, 1, 0, 1;\n}\n"
    : "+f"(d[0]), "+f"(d[1]), "+f"(d[2]), "+f"(d[3]), "+f"(d[4]), "+f"(d[5]), "+f"(d[6]), "+f"(d[7]), "+f"(d[8]), "+f"(d[9]), "+f"(d[10]), "+f"(d[11]), "+f"(d[12]), "+f"(d[13]), "+f"(d[14]), "+f"(d[15]), "+f"(d[16]), "+f"(d[17]), "+f"(d[18]), "+f"(d[19]), "+f"(d[20]), "+f"(d[21]), "+f"(d[22]), "+f"(d[23]), "+f"(d[24]), "+f"(d[25]), "+f"(d[26]), "+f"(d[27]), "+f"(d[28]), "+f"(d[29]), "+f"(d[30]), "+f"(d[31]), "+f"(d[32]), "+f"(d[33]), "+f"(d[34]), "+f"(d[35])
    : "l"(da), "l"(db), "r"(scaleD));
}
__device__ __forceinline__ void wgmma_ss_n128(float* d, uint64_t da, uint64_t db, int scaleD) {
  asm volatile("{\n.reg .pred p;\nsetp.ne.b32 p, %66, 0;\nwgmma.mma_async.sync.aligned.m64n128k16.f32.bf16.bf16 "
    "{%0,%1,%2,%3,%4,%5,%6,%7,%8,%9,%10,%11,%12,%13,%14,%15,%16,%17,%18,%19,%20,%21,%22,%23,%24,%25,%26,%27,%28,%29,%30,%31,%32,%33,%34,%35,%36,%37,%38,%39,%40,%41,%42,%43,%44,%45,%46,%47,%48,%49,%50,%51,%52,%53,%54,%55,%56,%57,%58,%59,%60,%61,%62,%63}, "
    "%64, %65, p, 1, 1, 0, 1;\n}\n"
    : "+f"(d[0]), "+f"(d[1]), "+f"(d[2]), "+f"(d[3]), "+f"(d[4]), "+f"(d[5]), "+f"(d[6]), "+f"(d[7]), "+f"(d[8]), "+f"(d[9]), "+f"(d[10]), "+f"(d[11]), "+f"(d[12]), "+f"(d[13]), "+f"(d[14]), "+f"(d[15]), "+f"(d[16]), "+f"(d[17]), "+f"(d[18]), "+f"(d[19]), "+f"(d[20]), "+f"(d[21]), "+f"(d[22]), "+f"(d[23]), "+f"(d[24]), "+f"(d[25]), "+f"(d[26]), "+f"(d[27]), "+f"(d[28]), "+f"(d[29]), "+f"(d[30]), "+f"(d[31]), "+f"(d[32]), "+f"(d[33]), "+f"(d[34]), "+f"(d[35]), "+f"(d[36]), "+f"(d[37]), "+f"(d[38]), "+f"(d[39]), "+f"(d[40]), "+f"(d[41]), "+f"(d[42]), "+f"(d[43]), "+f"(d[44]), "+f"(d[45]), "+f"(d[46]), "+f"(d[47]), "+f"(d[48]), "+f"(d[49]), "+f"(d[50]), "+f"(d[51]), "+f"(d[52]), "+f"(d[53]), "+f"(d[54]), "+f"(d[55]), "+f"(d[56]), "+f"(d[57]), "+f"(d[58]), "+f"(d[59]), "+f"(d[60]), "+f"(d[61]), "+f"(d[62]), "+f"(d[63])
    : "l"(da), "l"(db), "r"(scaleD));
}
__device__ __forceinline__ void wgmma_ss_n160(float* d, uint64_t da, uint64_t db, int scaleD) {
  asm volatile("{\n.reg .pred p;\nsetp.ne.b32 p, %82, 0;\nwgmma.mma_async.sync.aligned.m64n160k16.f32.bf16.bf16 "
    "{%0,%1,%2,%3,%4,%5,%6,%7,%8,%9,%10,%11,%12,%13,%14,%15,%16,%17,%18,%19,%20,%21,%22,%23,%24,%25,%26,%27,%28,%29,%30,%31,%32,%33,%34,%35,%36,%37,%38,%39,%40,%41,%42,%43,%44,%45,%46,%47,%48,%49,%50,%51,%52,%53,%54,%55,%56,%57,%58,%59,%60,%61,%62,%63,%64,%65,%66,%67,%68,%69,%70,%71,%72,%73,%74,%75,%76,%77,%78,%79}, "
    "%80, %81, p, 1, 1, 0, 1;\n}\n"
    : "+f"(d[0]), "+f"(d[1]), "+f"(d[2]), "+f"(d[3]), "+f"(d[4]), "+f"(d[5]), "+f"(d[6]), "+f"(d[7]), "+f"(d[8]), "+f"(d[9]), "+f"(d[10]), "+f"(d[11]), "+f"(d[12]), "+f"(d[13]), "+f"(d[14]), "+f"(d[15]), "+f"(d[16]), "+f"(d[17]), "+f"(d[18]), "+f"(d[19]), "+f"(d[20]), "+f"(d[21]), "+f"(d[22]), "+f"(d[23]), "+f"(d[24]), "+f"(d[25]), "+f"(d[26]), "+f"(d[27]), "+f"(d[28]), "+f"(d[29]), "+f"(d[30]), "+f"(d[31]), "+f"(d[32]), "+f"(d[33]), "+f"(d[34]), "+f"(d[35]), "+f"(d[36]), "+f"(d[37]), "+f"(d[38]), "+f"(d[39]), "+f"(d[40]), "+f"(d[41]), "+f"(d[42]), "+f"(d[43]), "+f"(d[44]), "+f"(d[45]), "+f"(d[46]), "+f"(d[47]), "+f"(d[48]), "+f"(d[49]), "+f"(d[50]), "+f"(d[51]), "+f"(d[52]), "+f"(d[53]), "+f"(d[54]), "+f"(d[55]), "+f"(d[56]), "+f"(d[57]), "+f"(d[58]), "+f"(d[59]), "+f"(d[60]), "+f"(d[61]), "+f"(d[62]), "+f"(d[63]), "+f"(d[64]), "+f"(d[65]), "+f"(d[66]), "+f"(d[67]), "+f"(d[68]), "+f"(d[69]), "+f"(d[70]), "+f"(d[71]), "+f"(d[72]), "+f"(d[73]), "+f"(d[74]), "+f"(d[75]), "+f"(d[76]), "+f"(d[77]), "+f"(d[78]), "+f"(d[79])
    : "l"(da), "l"(db), "r"(scaleD));
}
__device__ __forceinline__ void wgmma_rs_n144(float* d, const uint32_t* a, uint64_t db, int scaleD) {
  asm volatile("{\n.reg .pred p;\nsetp.ne.b32 p, %77, 0;\nwgmma.mma_async.sync.aligned.m64n144k16.f32.bf16.bf16 "
    "{%0,%1,%2,%3,%4,%5,%6,%7,%8,%9,%10,%11,%12,%13,%14,%15,%16,%17,%18,%19,%20,%21,%22,%23,%24,%25,%26,%27,%28,%29,%30,%31,%32,%33,%34,%35,%36,%37,%38,%39,%40,%41,%42,%43,%44,%45,%46,%47,%48,%49,%50,%51,%52,%53,%54,%55,%56,%57,%58,%59,%60,%61,%62,%63,%64,%65,%66,%67,%68,%69,%70,%71}, "
    "{%72,%73,%74,%75}, %76, p, 1, 1, 1;\n}\n"
    : "+f"(d[0]), "+f"(d[1]), "+f"(d[2]), "+f"(d[3]), "+f"(d[4]), "+f"(d[5]), "+f"(d[6]), "+f"(d[7]), "+f"(d[8]), "+f"(d[9]), "+f"(d[10]), "+f"(d[11]), "+f"(d[12]), "+f"(d[13]), "+f"(d[14]), "+f"(d[15]), "+f"(d[16]), "+f"(d[17]), "+f"(d[18]), "+f"(d[19]), "+f"(d[20]), "+f"(d[21]), "+f"(d[22]), "+f"(d[23]), "+f"(d[24]), "+f"(d[25]), "+f"(d[26]), "+f"(d[27]), "+f"(d[28]), "+f"(d[29]), "+f"(d[30]), "+f"(d[31]), "+f"(d[32]), "+f"(d[33]), "+f"(d[34]), "+f"(d[35]), "+f"(d[36]), "+f"(d[37]), "+f"(d[38]), "+f"(d[39]), "+f"(d[40]), "+f"(d[41]), "+f"(d[42]), "+f"(d[43]), "+f"(d[44]), "+f"(d[45]), "+f"(d[46]), "+f"(d[47]), "+f"(d[48]), "+f"(d[49]), "+f"(d[50]), "+f"(d[51]), "+f"(d[52]), "+f"(d[53]), "+f"(d[54]), "+f"(d[55]), "+f"(d[56]), "+f"(d[57]), "+f"(d[58]), "+f"(d[59]), "+f"(d[60]), "+f"(d[61]), "+f"(d[62]), "+f"(d[63]), "+f"(d[64]), "+f"(d[65]), "+f"(d[66]), "+f"(d[67]), "+f"(d[68]), "+f"(d[69]), "+f"(d[70]), "+f"(d[71])
    : "r"(a[0]), "r"(a[1]), "r"(a[2]), "r"(a[3]), "l"(db), "r"(scaleD));
}
__device__ __forceinline__ void wgmma_rs_n64(float* d, const uint32_t* a, uint64_t db, int scaleD) {
  asm volatile("{\n.reg .pred p;\nsetp.ne.b32 p, %37, 0;\nwgmma.mma_async.sync.aligned.m64n64k16.f32.bf16.bf16 "
    "{%0,%1,%2,%3,%4,%5,%6,%7,%8,%9,%10,%11,%12,%13,%14,%15,%16,%17,%18,%19,%20,%21,%22,%23,%24,%25,%26,%27,%28,%29,%30,%31}, "
    "{%32,%33,%34,%35}, %36, p, 1, 1, 1;\n}\n"
    : "+f"(d[0]), "+f"(d[1]), "+f"(d[2]), "+f"(d[3]), "+f"(d[4]), "+f"(d[5]), "+f"(d[6]), "+f"(d[7]), "+f"(d[8]), "+f"(d[9]), "+f"(d[10]), "+f"(d[11]), "+f"(d[12]), "+f"(d[13]), "+f"(d[14]), "+f"(d[15]), "+f"(d[16]), "+f"(d[17]), "+f"(d[18]), "+f"(d[19]), "+f"(d[20]), "+f"(d[21]), "+f"(d[22]), "+f"(d[23]), "+f"(d[24]), "+f"(d[25]), "+f"(d[26]), "+f"(d[27]), "+f"(d[28]), "+f"(d[29]), "+f"(d[30]), "+f"(d[31])
    : "r"(a[0]), "r"(a[1]), "r"(a[2]), "r"(a[3]), "l"(db), "r"(scaleD));
}

template <int V> struct Int { static constexpr int value = V; };
struct Cur {
  uint32_t s, ph;
  __device__ __forceinline__ void next() { if (++s == NST) { s = 0; ph ^= 1; } }
};

__device__ __forceinline__ uint32_t o_place(uint32_t w, uint32_t e) { return (((w ? 0xd5310u : 0xa8d57u) >> (4 * e)) & 15) * 8192 + 90112; }
#define z1_block(rb, w, j) (Q.Z + ((rb) * 16 + (w) * 8 + (j)) * ZB)
#define xn_block(hw) (Q.Z + (512 + (hw) * 2) * ZB)
#define z2_block(kb, j) (Q.Z + (256 + (kb) * 8 + (j)) * ZB)
template <int N> __device__ __forceinline__ void pause(uint32_t zero) {
  if (N <= 0) return;
  uint32_t z = clock() + threadIdx.x;
  do {
#pragma unroll (N > 8 ? 1 : 8)
    for (int i = 0; i < N; i++) asm volatile("shfl.sync.bfly.b32 %0, %0, 1, 0x1f, 0xffffffff;" : "+r"(z)::"memory");
  } while (__any_sync(~0u, z & zero));
}

__global__ void __cluster_dims__(2, 1, 1) __launch_bounds__(384, 1) mega_kernel(const Ptrs Q, const __grid_constant__ Params P) {
  extern __shared__ __align__(1024) uint8_t smem_raw[];
  const uint32_t sb = smem_u32(smem_raw);
  const uint32_t bars = sb + SM_BAR;
  const int tid = threadIdx.x;
  int lane = tid & 31;
  const int wid = __shfl_sync(~0u, tid >> 5, 0);
  const int cl = blockIdx.x >> 1;
  const int bid = (cl < 4 ? cl * 8 + 32 : cl - 4 + (max(cl - 29, 0) * 37 >> 8)) * 2 + (blockIdx.x & 1);
  const int rb = bid & 15, j = bid >> 4;
  uint4 wv[5];
  {
    const int n8 = min(tid >> 3, 26), part = n8 / 9;
    const uint8_t* src = (const uint8_t*)Q.wqkv + (8 * rb + (tid & 7)) * (3 * DM * 2) + (part * (DM - 72) + 72 * j + 8 * n8) * 2;
#pragma unroll
    for (int u = 0; u < 5; u++) wv[u] = ldnc128_if(tid < 216 && cl < 64 && (u < 4 || rb < 8), src + u * (128 * 3 * DM * 2));
  }
  if (cl >= 64) return;
  if (wid >= 7 && lane == 0) {
    if (wid < 10) {
#pragma unroll
      for (uint32_t b = 0; b < B_AD / 3; b += 8) mbar_init(bars + (wid - 7) * (B_AD / 3) + b, 1);
    } else if (wid == 10) {
#pragma unroll
      for (uint32_t b = B_AD; b < B_EVT; b += 8) mbar_init(bars + b, b < B_CSQ ? 2 : b < B_LAG ? 3 : 4);
    } else {
#pragma unroll
      for (uint32_t b = B_EVT; b < 1024; b += 8) if (b < B_OFF || b >= B_IMG) mbar_init(bars + b, b < B_IMG ? 4 : b < B_EMPTY ? 8 : 16);
    }
    asm volatile("fence.mbarrier_init.release.cluster;" ::: "memory");
  }
  __syncthreads();

  if (wid >= 8) {
    reg_dealloc<40>();
    const uint32_t el = elect_one();
    const uint64_t pol = policy_evict_first();
    uint32_t* const fj = Q.flags + FJ + j * 32;
    if (wid == 8) {
      if (el) { prefetch_map(&P.wsp); prefetch_map(&P.winb[j & 1]); prefetch_map(&P.wins); prefetch_map(&P.wout); prefetch_map(&P.act[1]); prefetch_map(&P.res[0]); prefetch_map(&P.res[1]); prefetch_map(&P.row[1]); prefetch_map(&P.red); }
      const uint32_t epoch = ldcg32(fj + FJ_EP + rb);
      Cur c{0, 1};
      const uint32_t rk = bid & 1;
      uint32_t st, full;
      auto slot = [&](uint32_t bytes) {
        st = sb + c.s * ST_BYTES; full = bars + B_FULL + c.s * 8;
        mbar_wait(full, c.ph);
        expect_tx_p(el, full, bytes);
        mbar_wait(full - B_FULL + B_EMPTY, c.ph);
      };
#pragma unroll 1
      for (int L = 0; L < 2; L++) {
#pragma unroll 1
        for (int i = 0; i < 9; i++) {
          if (L == 0 && i == 0) {
            flag_wait(fj + FJ_WQ, (epoch + 1) * 16);
            fence_async_g();
            TRC(el, 2, 45);
          }
          slot(27648);
          bulk_mc_h(el, st + ST_B + rk * 13824, Q.WQ + j * WQ_SL + i * 27648 + rk * 13824, 13824, full, EF(0), pol);
          c.next();
        }
        if (L == 0) {
          flag_wait(fj + FJ_WO, (epoch + 1) * 16);
          fence_async_g();
          TRC(el, 2, 46);
        }
#pragma unroll 1
        while (c.s) {
          mbar_wait(bars + B_EMPTY + c.s * 8, c.ph);
          if (el) { mbar_arrive(bars + B_FULL + c.s * 8); asm volatile("mbarrier.arrive.shared::cta.b64 _, [%0], 16;" ::"r"(bars + B_EMPTY + c.s * 8) : "memory"); }
          c.next();
        }
        expect_tx_p(el, bars + B_WF, WO_SL);
        mbar_wait(bars + B_EMPTY, c.ph);
        mbar_wait(bars + B_EMPTY + 8, c.ph);
        bulk_mc_h(el, sb + rk * (WO_SL / 2), Q.WO + j * WO_SL + rk * (WO_SL / 2), WO_SL / 2, bars + B_WF, EF(1), pol);
#pragma unroll 1
        for (int r = 0; r < 10; r++) {
          const bool big = r >= 2 && r < 8;
          const int a0 = (r < 5 ? 36 : 0) + ((9 * j) >> 1) + (big ? 2 - 2 * (j & 1) : 3 * (j & 1) + rk), ks = big ? 32 : 48;
          int k = big ? (r < 5 ? r - 2 : r - 5) * 192 + rk * 16 : (r & 1) * 288;
          const CUtensorMap* m = big ? &P.winb[j & 1] : &P.wins;
          const uint32_t dst = sb + SM_B3 + rk * 6144;
#pragma unroll
          for (int p = 0; p < 6; p++, k += ks) {
            if (!(p & 3) && r == 0) mbar_wait(bars + B_XD + p * 2, L);
            if (p) mbar_wait_c(bars + B_E3 + p * 8, ~r & 1); else mbar_wait(bars + B_E3, ~r & 1);
            expect_tx_p(el, bars + B_F3 + p * 8, 12288);
            tma3d_mc_h(el, dst + p * 12288, m, 0, k, a0, bars + B_F3 + p * 8, EF(2), pol);
          }
        }
        TRC(el, 2, L * 16 + 6);
        mbar_wait(bars + B_ZOK, L);
        fence_async_g();
        TRC(el, 2, L * 16 + 7);
        const uint8_t* src = z2_block(0, j) + rk * 18432;
#pragma unroll 1
        for (int r = 0; r < 8; r++) {
          const int k = (r & 3) * 512 + (r >> 2) * 64;
#pragma unroll
          for (int p = 0; p < 4; p++, src += 8 * ZB) {
            if ((p == 1 || p == 2) && r == 0) mbar_wait(bars + B_E3 - 8 + p * 24, 1);
            mbar_wait_c(bars + B_AD + p * 8, ~r & 1);
            if (p) mbar_wait_c(bars + B_EMPTY + p * 8, c.ph); else mbar_wait(bars + B_EMPTY, c.ph);
            expect_tx_p(el, bars + B_FULL + p * 8, ST_BYTES);
            bulk_mc_h(el, sb + p * ST_BYTES + ST_B + rk * 18432, src, 18432, bars + B_FULL + p * 8, EF(4), pol);
            tma3d_h(el, sb + p * ST_BYTES, &P.wsp, k + p * 128, rb * 64, 0, bars + B_FULL + p * 8, EF(3), pol);
          }
          c.ph ^= 1;
        }
        mbar_wait(bars + B_Z1, L);
        fence_async_g();
#pragma unroll 1
        for (int i = 0; i < 11; i++) {
          const int cb = i - 2 + j;
          if (i < 4) mbar_wait(bars + B_AD + c.s * 8, 1);
          slot(ZB);
          if (i < 2) bulk_load_h(el, st + ST_B, z1_block(rb, i, j), ZB, full, true, pol);
          else tma2d_mc_h(el, st + ST_B + rk * 18432, &P.wout, (cb >= 9 ? cb - 9 : cb) * 64, 288 * j + rk * 144, full, EF(5), pol);
          c.next();
        }
      }
    } else if (wid < 11) {
      uint32_t id = bid * 2 + wid - 9;
#define AGENT_IDS asm volatile("" : "+r"(lane), "+r"(id)); const uint32_t w = id & 1, hw = id & 31, rb = hw >> 1, j = id >> 5, ev = bars + B_EVT + w * EV_N * 8; \
      uint32_t* const fr = Q.flags + hw * 32; uint32_t* const fj = Q.flags + FJ + j * 32; (void)fr; (void)fj; (void)ev; (void)rb
      uint32_t t8 = 0;
      Cur c{0, 1};
#pragma unroll 1
      for (int L = 0; L < 2; L++) {
#pragma unroll 1
        for (int ph = 0; ph < 3; ph++) {
          if (ph + L > 0) {
            AGENT_IDS;
            uint32_t* f = fr + (ph == 0 ? FR_X2 : ph == 1 ? FR_O + L - (int)w * 32 : FR_X1 + L);
            mbar_wait_c(ev + ph * 8, L);
            TRC(el, 3, w * 32 + L * 16 + ph * 3);
            if (ph || XRLX) { if (ph < 2 || SDEL < 0) flag_add_p(el, f); } else flag_release_p(el, f);
            TRC(el, 3, w * 32 + L * 16 + ph * 3 + 1);
            if (ph == 1) {
#pragma unroll 1
              for (int e = 0; e < 5; e++) {
                const uint32_t nb = e ? 16384 : 8192, full = bars + B_OF + w * 40 + e * 8, dst = sb + o_place(w, e);
                const uint8_t* src = z1_block(rb, w, 0) + (e ? e * 16384 - 8192 : 0);
                expect_tx_p(el, full, nb);
                if (e == 0) {
                  pause<FD1>(Q.zero);
                  if (w) pause<FD2>(Q.zero);
                  flag_wait(f + w * (FR_OL - FR_O), t8 * (2 - w));
                  if (w) fence_async_g();
                }
                if (w && (e == 0 || e == 3)) mbar_wait_c(bars + (e ? B_X3 : B_OF + YPACE * 8), L);
                bulk_load_h(el, dst, src, nb, full, EF(6), pol);
                TRC(el && e == 0, 3, w * 32 + L * 16 + ph * 3 + 2);
              }
              continue;
            }
            if (ph == 2) {
              const uint8_t* src = xn_block(hw);
              uint32_t full = bars + B_AF3 + w * 96, dst = sb + w * 6144;
              mbar_wait_c(bars + B_XD + 8, L);
#pragma unroll 1
              for (int k = 0; k < 12; k++, src += 6144, dst += 12288, full += 8) {
                expect_tx_p(el, full, 6144);
                if (k >= APACE) mbar_wait_c(full - APACE * 8, L);
                if (k == 0) { if (SDEL < 0) flag_wait(f, t8); else pause<SDEL>(Q.zero); }
                if (k == 11 && L == 1) flag_wait(fj + FJ_P4, t8 * 4);
                bulk_load_h(el, dst, src, 6144, full, EF(7), pol);
                TRC(el && k == 0, 3, w * 32 + L * 16 + ph * 3 + 2);
              }
              break;
            }
            const uint32_t full = bars + B_FULLA + w * 32 + c.s * 8, dst = sb + c.s * ST_BYTES + w * 8192;
            mbar_wait_c(bars + B_EMPTY + c.s * 8, c.ph);
            expect_tx_p(el, full, 8192);
            pause<FD0>(Q.zero);
            flag_wait(f, t8);
            fence_async_g();
            tma3d_h(el, dst, &P.act[1], 0, rb * 64, w, full, false, pol);
            c.next();
            TRC(el, 3, w * 32 + L * 16 + ph * 3 + 2);
          }
#pragma unroll 1
          for (int i = L; i < 9; i++) {
            AGENT_IDS;
            const uint32_t full = bars + B_FULLA + w * 32 + c.s * 8, dst = sb + c.s * ST_BYTES + w * 8192;
            if (L == 0 && i == AEP) t8 = (ldcg32(fr + FR_EP + j) + 1) * 8;
            mbar_wait_c(bars + B_EMPTY + c.s * 8, c.ph);
            expect_tx_p(el, full, 8192);
            tma3d_h(el, dst, &P.act[L], i * 64, rb * 64, w, full, false, pol);
            c.next();
            if (i == PZI || i == PZI + 1) {
              uint8_t* d = (i == PZI ? xn_block(hw) : z1_block(rb, 0, 0) + w * 4608) + j * 9216 + lane * 16;
#pragma unroll 1
              for (int u = i == PZI ? 0 : 3; u < 6; u++, d += 1536) { stg128(d, ~0u, ~0u, ~0u, ~0u); stg128(d + 512, ~0u, ~0u, ~0u, ~0u); stg128(d + 1024, ~0u, ~0u, ~0u, ~0u); }
            }
            if (i == PZI) { stg128(Q.ST1 + (hw * 8 + j) * 32 + lane, ~0u, ~0u, ~0u, ~0u); stg128(Q.ZST + (hw * 8 + j) * 32 + lane, ~0u, ~0u, ~0u, ~0u); }
            if (i == RFI) {
              expect_tx_p(el, bars + B_WT + w * 8, 9216);
              tma3d_h(el, sb + SM_STG + w * 9216, &P.row[L], 0, 3 * w, rb * 64 + 8 * j, bars + B_WT + w * 8, false, pol);
            }
            if (i == 4 && L > w) {
              expect_tx_p(el, bars + B_CSQ, 864);
              bulk_load_p(el, sb + 3 * ST_BYTES + SM_CSQ, Q.CSP + (NCTA + (id >> 1)) * 216, 864, bars + B_CSQ);
            }
          }
          if (c.s) { c.s = 0; c.ph ^= 1; }
          {
            AGENT_IDS;
            const uint32_t tag = (t8 >> 2) - 1 + L;
            uint4* const xs = Q.XST + hw * 128;
            const uint32_t tab = sb + L * (3 * ST_BYTES) + SM_XST + w * 768 + lane * 8;
            TRC(el, 3, w * 32 + L * 16 + 13);
#pragma unroll 1
            for (int it = 0; it < (1 << 22); it++) {
              const uint4 a = ll_ld128(xs + 2 * lane), b = ll_ld128(xs + 64 + 2 * lane), h = ll_ld128(xs - (rb ? 192 : 0) + 2 * (lane | 24));
              if (__all_sync(~0u, a.z == tag && b.z == tag && h.z == tag)) { sts64(tab, h.x, h.y); sts64(tab + 256, a.x, a.y); sts64(tab + 512, b.x, b.y); break; }
            }
            __syncwarp();
            if (el) mbar_arrive(bars + B_CSQ);
            TRC(el, 3, w * 32 + L * 16 + 14);
            uint32_t* f = Q.flags + rb * 64 + FR_PZ + L;
            flag_release_p(el, f);
            expect_tx_p(el, bars + B_RES + w * 8, 9216);
            tma3d_h(el, sb + SM_STG + w * 9216, &P.res[L], j * 72, hw * 32, 0, bars + B_RES + w * 8, !L, pol);
            pause<FD3>(Q.zero);
            flag_wait(f, t8 * 2);
            fence_async_g();
            TRC(el, 3, w * 32 + L * 16 + 15);
          }
        }
        if (wid == 10) {
          AGENT_IDS;
          mbar_wait_c(ev - (EV_N - EV_ZN) * 8, L);
          mbar_wait_c(ev + EV_ZN * 8, L);
          asm volatile("fence.release.gpu;" ::: "memory");
          flag_add_p(el, fj + FJ_ZN + L);
          flag_add_p(el, fr - 32 + FR_XR + L);
          pause<FD4>(Q.zero);
          flag_wait(fj + FJ_ZN + L, t8 * 2);
          flag_wait(fr - 32 + FR_XR + L, t8);
          if (el) mbar_arrive(bars + B_ZOK);
        } else if (WPF) {
          AGENT_IDS;
          mbar_wait_c(ev + EV_ZN * 8, L);
          if (el) asm volatile("cp.async.bulk.prefetch.tensor.3d.L2.global [%0, {%1, %2, %3}];" ::"l"(&P.wsp), "r"(j * 128), "r"(rb * 64), "r"(0) : "memory");
        }
        float cv;
        {
        AGENT_IDS;
        cv = (lane & 3) ? 0.f : -blo(ldnc16(Q.b_sp + 128 * rb + 16 * j + 2 * (lane >> 2) + w));
        mbar_wait_c(ev + EV_Z1 * 8, L);
        const uint32_t ro = (w * 64 + 8 * j + (lane >> 2)) * 128, x0 = ((lane & 3) * 2) ^ (lane >> 2);
#pragma unroll 1
        for (int i = 0; i < 32; i++) {
          const bool tail = (i >> 1) == 12;
          const int kb = tail ? i + 6 : i < 24 ? i : i - 2;
          if (!(i & 7)) mbar_wait_c(bars + B_RT + i, L);
          if (i == 24) mbar_wait_c(bars + B_WT + w * 8, 1);
          if (!tail) mbar_wait(bars + B_FULL + c.s * 8, c.ph ^ 1);
          if (i == 3) {
            uint32_t id2 = id;
            asm volatile("" : "+r"(id2));
            expect_tx_p(el, bars + B_WT + w * 8, 3072);
#pragma unroll 1
            for (int r = 0; r < 8; r++)
              bulk_load_p(el, sb + SM_WT + w * 3200 + r * 400, (const uint8_t*)Q.w_sp + (64 * (id2 & 30) + 16 * (id2 >> 5) + 2 * r + w) * (SEQ * 2) + 29 * 128, 384, bars + B_WT + w * 8);
          }
#pragma unroll
          for (int e = 0; e < 2; e++) {
            const uint4 a = lds128(!tail ? sb + c.s * ST_BYTES + ro + ((x0 ^ e) << 4) : sb + SM_WT + w * 3200 + (lane >> 2) * 400 + (i - 24) * 256 + (lane & 3) * 32 + e * 16);
            const uint4 m = lds128(sb + SM_RT + 4096 + kb * 128 + (lane & 3) * 32 + e * 16);
            cv = fmaf(blo(a.x), blo(m.x), fmaf(bhi(a.x), bhi(m.x), fmaf(blo(a.y), blo(m.y), fmaf(bhi(a.y), bhi(m.y), cv))));
            cv = fmaf(blo(a.z), blo(m.z), fmaf(bhi(a.z), bhi(m.z), fmaf(blo(a.w), blo(m.w), fmaf(bhi(a.w), bhi(m.w), cv))));
          }
          if (!tail) {
            __syncwarp();
            if (el) mbar_arrive(bars + B_AD + c.s * 8);
            c.next();
          }
        }
        }
        AGENT_IDS;
        TRC(el, 3, w * 32 + L * 16 + 11);
        asm volatile("" : "+r"(t8));
        const uint32_t tag = (t8 >> 2) - 1 + L;
        cv = qsum(cv);
        uint2* const cs = (uint2*)(Q.XST + hw * 128 + 1);
        if ((lane & 3) == 0) ll_st64(cs + 32 * j + (lane >> 2) * 4, __float_as_uint(cv), tag);
        pause<FD5>(Q.zero);
#pragma unroll 1
        for (int it = 0; it < (1 << 22); it++) {
          const uint2 a = ll_ld64(cs + 4 * lane), b = ll_ld64(cs + 128 + 4 * lane);
          if (__all_sync(~0u, a.y == tag && b.y == tag)) { sts32(sb + SM_CV + w * 256 + lane * 4, a.x); sts32(sb + SM_CV + w * 256 + 128 + lane * 4, b.x); break; }
        }
        __syncwarp();
        if (el) mbar_arrive(bars + B_CV + w * 8);
        TRC(el, 3, w * 32 + L * 16 + 12);
#pragma unroll 1
        for (int kb = 30; kb < 32; kb++) {
          mbar_wait_c(bars + B_FULL + c.s * 8, c.ph ^ 1);
          if (el) mbar_arrive(bars + B_AD + c.s * 8);
          c.next();
        }
        c.ph ^= ((c.s + 11) >> 2) & 1; c.s = (c.s + 11) & 3;
        if (L == 0) {
          mbar_wait_c(ev + EV_PT * 8, 0);
          flag_add_p(el, fj + FJ_P4);
        }
      }
    } else {
      const uint32_t epoch = ldcg32(fj + FJ_EP + rb);
      mbar_wait(bars + B_IMG, 0);
      TRC(el, 2, 41);
      flag_release_p(el, fj + FJ_WQ);
      TRC(el, 2, 42);
#pragma unroll 1
      for (int L = 0; L < 2; L++) {
        float* const csf = Q.CSP + (NCTA + bid) * 216;
        if (L == 0) {
          flag_wait(fj + FJ_WQ, (epoch + 1) * 16);
          fence_async_g();
          expect_tx_p(el, bars + B_XRW, 13824);
          bulk_load_p(el, sb + ST_BYTES + SM_WOI, Q.CSP + j * 16 * 216, 6912, bars + B_XRW);
          bulk_load_p(el, sb + 2 * ST_BYTES + SM_WOI, Q.CSP + (j * 16 + 8) * 216, 6912, bars + B_XRW);
          mbar_wait(bars + B_XRW, 0);
#pragma unroll 1
          for (int f = lane; f < 54; f += 32) {
            float s[4] = {0.f, 0.f, 0.f, 0.f};
#pragma unroll 2
            for (int r = 0; r < 16; r++) {
              const uint4 v = lds128(sb + ST_BYTES + SM_WOI + (r >> 3) * ST_BYTES + (r & 7) * 864 + f * 16);
              s[0] += __uint_as_float(v.x); s[1] += __uint_as_float(v.y); s[2] += __uint_as_float(v.z); s[3] += __uint_as_float(v.w);
            }
            sts128(sb + SM_CSQ + f * 16, __float_as_uint(s[0]), __float_as_uint(s[1]), __float_as_uint(s[2]), __float_as_uint(s[3]));
            stg128(csf + f * 4, __float_as_uint(s[0]), __float_as_uint(s[1]), __float_as_uint(s[2]), __float_as_uint(s[3]));
          }
          __syncwarp();
          if (el) mbar_arrive(bars + B_CSQ);
          TRC(el, 2, 43);
          mbar_wait(bars + B_WOI, 0);
          bulk_store_p(el, Q.WO + j * WO_SL + rb * (41 * 128), sb + SM_WOI, (rb < 15 ? 41 : 33) * 128);
          publish_p(el, fj + FJ_WO);
          TRC(el, 2, 44);
          if (el) prefetch_l2((const uint8_t*)Q.w_in + bid * 41472, 41472);
          float o0 = 0.f, o1 = 0.f;
#pragma unroll 1
          for (int u = 0; u < 2; u++) {
            const uint8_t* src = (u ? (const uint8_t*)Q.w_sp + 500 * (SEQ * 2) + 2048 : (const uint8_t*)Q.w_in + 100 * (2 * FH * 2) + FH * 2) + lane * 16;
            const uint4 a = ldnc128(src), b = ldnc128(src + 300 * (2 * FH * 2) + 2048);
            const uint32_t x[8] = {a.x, a.y, a.z, a.w, b.x, b.y, b.z, b.w};
            float sq = 0.f;
#pragma unroll
            for (int e = 0; e < 8; e++) sq = fmaf(blo(x[e]), blo(x[e]), fmaf(bhi(x[e]), bhi(x[e]), sq));
            o0 = o1;
            asm("sqrt.approx.f32 %0, %1;" : "=f"(o1) : "f"(wsum(sq) * (u ? C0S * C0S * SEQ / 512.f : 2.f * GA * GA * DM / 512.f)));
          }
          const uint32_t off = (__float_as_uint(o0) & 0x7f800000u) >> 16 | 0x8000u | OFM;
          if (el) sts128(sb + SM_OFF, off * 0x10001u, min(__float_as_uint(o1) & 0x7f800000u, 0x7e000000u) | 0x00400000u, __float_as_uint(GB), 0u);
        }
        mbar_wait(bars + B_EVT + EV_O * 8, L);
        mbar_wait(bars + B_EVT + (EV_N + EV_O) * 8, L);
        flag_release_p(el, Q.flags + rb * 64 + FR_OL + L);
#pragma unroll 1
        for (int w = 0; w < 2; w++) {
          mbar_wait(bars + B_EVT + (w * EV_N + EV_XS) * 8, L);
          if (!w) mbar_wait(bars + B_AF3 + 96 + XP0 * 8, L);
          if (el) asm volatile("cp.async.bulk.tensor.3d.global.shared::cta.tile.bulk_group [%0, {%2, %3, %4}], [%1];\ncp.async.bulk.commit_group;\ncp.async.bulk.wait_group.read 0;" ::"l"(&P.res[1]), "r"(sb + SM_STG + 9216), "r"(j * 72), "r"(rb * 64 + w * 32), "r"(0) : "memory");
          __syncwarp();
          if (lane < 2 && !w) mbar_arrive(bars + B_S5);
        }
        if (el) { asm volatile("cp.async.bulk.wait_group 0;" ::: "memory"); mbar_arrive(bars + B_GATE3); }
        const uint32_t tag = epoch * 2 + L + 1;
        asm volatile("" : "+r"(lane));
#pragma unroll 1
        for (int b = 0; b < 8; b++) {
          if (!(b & 3)) {
            const int mb = b >> 2;
            mbar_wait(bars + B_ZS + mb * 8, L);
            pause<ZD1>(Q.zero);
            TRC(el && !mb, 2, L * 16 + 8);
            uint4 v;
#pragma unroll 1
            for (int it = 0; it < (1 << 22); it++) {
              v = ll_ld128(Q.ZST + ((rb * 2 + mb) * 8 + (lane >> 2)) * 32 + 4 * j + (lane & 3));
              if (__all_sync(~0u, max(max(v.x, v.y), max(v.z, v.w)) != ~0u)) break;
            }
            const bool o = lane & 16;
            float ss = __uint_as_float(o ? v.y : v.x) + __shfl_xor_sync(~0u, __uint_as_float(o ? v.x : v.y), 16), sq = __uint_as_float(o ? v.w : v.z) + __shfl_xor_sync(~0u, __uint_as_float(o ? v.z : v.w), 16);
            ss += __shfl_xor_sync(~0u, ss, 4); sq += __shfl_xor_sync(~0u, sq, 4); ss += __shfl_xor_sync(~0u, ss, 8); sq += __shfl_xor_sync(~0u, sq, 8);
            const float mean = ss * (1.f / FH), rs = blo(pack2(rsq_fast(fmaxf(fmaf(sq, 1.f / FH, -mean * mean), 0.f) + 4.f * GA * GA * LN_EPS), 0.f));
            if (!(lane & 12)) ll_st64(Q.RT + (mb * 16 + rb) * 64 + 8 * j + 2 * (lane & 3) + (lane >> 4), pack2(rs, rs * (mean - blo(lds32(sb + SM_OFF)))), tag);
            TRC(el && !mb, 2, L * 16 + 10);
            pause<ZD2>(Q.zero);
          }
          uint4 v[4];
#pragma unroll 1
          for (int it = 0; it < (1 << 22); it++) {
            bool ok = true;
#pragma unroll
            for (int u = 0; u < 4; u++) { v[u] = ll_ld128((const uint4*)Q.RT + b * 128 + u * 32 + lane); ok = ok && v[u].y == tag && v[u].w == tag; }
            if (__all_sync(~0u, ok)) break;
          }
#pragma unroll
          for (int u = 0; u < 4; u++) {
            const uint32_t rt = sb + SM_RT + b * 512 + u * 128, ro = (lane >> 3) * 32 + (lane & 3) * 8 + ((lane >> 2) & 1) * 2;
            sts32(rt + 4096 + lane * 4, __byte_perm(v[u].x, v[u].z, 0x7632));
            asm volatile("st.shared.u16 [%0], %1;\nst.shared.u16 [%0 + 4], %2;" ::"r"(rt + ro), "h"((uint16_t)v[u].x), "h"((uint16_t)v[u].z) : "memory");
          }
          __syncwarp();
          if (el && (b & 1)) mbar_arrive(bars + B_RT + (b - 1) * 4);
          TRC(el && b < 2, 2, L * 16 + 11 + b);
        }
        TRC(el, 2, L * 16 + 9);
        mbar_wait(bars + B_EVT + EV_Z1 * 8, L);
        mbar_wait(bars + B_EVT + (EV_N + EV_Z1) * 8, L);
        fence_gpu();
        if (el) mbar_arrive(bars + B_Z1);
      }
    }
  } else {
    int w = wid >> 2, q = wid & 3, rb = bid & 15, j = bid >> 4;
    int g = lane >> 2, t = lane & 3;
#define PHASE asm volatile("" : "+r"(w), "+r"(q), "+r"(rb), "+r"(j))
#define stg (sb + SM_STG + w * 9216)
    const bool tr = (tid & 127) == 0;
    (void)tr;
    Cur c{0, 0};
    const uint32_t ebar = mapa(bars + B_EMPTY, (bid & 1) ^ (lane & 1));
    auto release = [&](uint32_t s) { if (lane < 2) mbar_arrive_cluster(ebar + s * 8); };
    uint32_t ia = 0;
    auto wait_ab = [&]() { mbar_wait_c(bars + B_FULL + c.s * 8, c.ph); mbar_wait_c(bars + B_FULLA + w * 32 + c.s * 8, (ia >> c.s) & 1); ia ^= 1u << c.s; };
    uint32_t lagph = 0;
    auto yield = [&](int left, int lag) { if (w == 1 && left == lag) mbar_wait_c(bars + B_LAG, lagph); };
    auto yield_done = [&]() { if (w == 0 && lane == 0) mbar_arrive(bars + B_LAG); };
    uint32_t rp = 0;
    auto check = [&](auto n, uint32_t dst, const uint8_t* src) {
      const uint32_t a = dst + lane * 32 + (lane >> 2) * 4;
#pragma unroll 1
      for (int it = 0; it < (1 << 16); it++) {
        uint32_t x = lds32(a);
#pragma unroll
        for (int e = 1; e < n.value; e++) x = max(x, lds32(a + e * 1024));
        if (!__any_sync(~0u, x == ~0u)) break;
        fence_async_s();
        __syncwarp();
        expect_tx_p(lane == 0, bars + B_RB + q * 8, n.value * 1024);
        bulk_load_p(lane == 0, dst, src, n.value * 1024, bars + B_RB + q * 8);
        mbar_wait_c(bars + B_RB + q * 8, rp & 1);
        rp++;
      }
    };
    auto signal = [&](int e) { __syncwarp(); if (lane == 0) mbar_arrive(bars + B_EVT + w * EV_N * 8 + e * 8); };
    TRC(tr, w, 0);

    {
      uint8_t* dst = Q.WQ + j * WQ_SL + rb * 3456 + tid * 16;
#pragma unroll
      for (int u = 0; u < 5; u++) {
        stg128_if((u < 4 || rb < 8) && tid < 216, dst + u * (16 * 3456), wv[u].x, wv[u].y, wv[u].z, wv[u].w);
        if (u == 0) TRC(tr, w, 60);
      }
      if (Q.zero == 0) {
        float s[8];
#pragma unroll
        for (int u = 0; u < 5; u++) {
          const uint32_t x[4] = {wv[u].x, wv[u].y, wv[u].z, wv[u].w};
#pragma unroll
          for (int e = 0; e < 4; e++) { s[2 * e] = u ? s[2 * e] + blo(x[e]) : blo(x[e]); s[2 * e + 1] = u ? s[2 * e + 1] + bhi(x[e]) : bhi(x[e]); }
        }
#pragma unroll
        for (int m = 4; m; m >>= 1) {
#pragma unroll
          for (int e = 0; e < m; e++) s[e] = ((tid & m) ? s[e + m] : s[e]) + __shfl_xor_sync(~0u, (tid & m) ? s[e] : s[e + m], m);
        }
        stg32_if(tid < 216, Q.CSP + bid * 216 + tid, __float_as_uint(s[0]));
      }
      __syncwarp();
      if (lane == 0) mbar_arrive(bars + B_IMG);
    }
    reg_alloc<232>();
    auto fetch_wo = [&]() {
#pragma unroll 1
      for (int u = tid; u < 328; u += 256) {
        const int m = min(41 * rb + (u >> 3), 647), k8 = m / 9;
        cp_async16(sb + SM_WOI + u * 16, (const uint8_t*)Q.wo + (8 * k8 + (u & 7)) * (DM * 2) + (72 * j + 8 * (m - k8 * 9)) * 2);
      }
    };
    const uint32_t epoch = ldcg32(Q.flags + (rb * 2 + w) * 32 + FR_EP + j);
    TRC(tr, w, 1);

#pragma unroll 1
    for (int L = 0; L < 2; L++) {
      const int tb = 2 + L * 24;
      asm volatile("" : "+r"(lane), "+r"(g), "+r"(t));
      if (PHM & 1) PHASE;
      (void)tb;
      const uint32_t tag = epoch * 2 + L + 1;
      {
        uint32_t Pk[27][2];
        float rk[2][2], sc[2][2];
        const bool up0 = 2 * t > g, up1 = 2 * t + 1 > g;
        constexpr int HA_[6] = {0, 2, 4, 7, 12, 15}, HC_[6] = {6, 9, 10, 11, 14, 17};
        const bool remote = q == 0 && rb > 0;
        uint4* hp = Q.HALO + ((((rb - (q == 0)) * 2 + w) * 8 + j) * 6) * 32 + lane;
        const uint32_t att = 2 * ST_BYTES + w * 8192 + lane * 16;
        const uint8_t* hs = remote ? (const uint8_t*)hp : smem_raw + att + (q == 3 ? ST_BYTES : q == 2 ? 3072 : 0);
        uint8_t* od = z1_block(rb, q >> 1, 0) + (9 * j) * 1024 + (4 * (q & 1) + w) * 128 + lane * 4;
        ACLK_INIT;
        {
          float acc[108];
#pragma unroll
          for (int i = 0; i < 108; i++) acc[i] = 0.f;
          float sx[2] = {0.f, 0.f}, sq[2] = {0.f, 0.f};
          uint32_t prev = 0;
#pragma unroll 1
          for (int kb = 0; kb < 9; kb++) {
            wait_ab();
            yield(9 - kb, LAG1);
            TRC(tr && kb == 0, w, tb + 0);
            PCLK(kb * 4);
            const uint32_t st = sb + c.s * ST_BYTES, da = dlo(st + w * 8192, 16), db = dlo(st + ST_B, 3456);
            wgmma_fence();
#pragma unroll
            for (int kk = 0; kk < 4; kk++) {
              wgmma_ss_n216(acc, dsc<1024, 1>(da, kk * 32), dsc<128, 0>(db, kk * 6912), 1);
              if (kk == 0) { wgmma_commit(); wgmma_wait<1>(); if (kb > 0) release(prev); }
              if (kk == 3) wgmma_commit();
              if (kk == XK1) {
            if (kb >= KS && kb < KS + 3) {
              mbar_wait_c(bars + B_WT + w * 8, 0);
#pragma unroll
              for (int u = 0; u < 3; u++) {
                const uint2 x = lds64(stg + (2 * q + (lane >> 4)) * 1152 + (lane & 15) * 8 + (kb - KS) * 384 + u * 128);
                sx[0] += blo(x.x) + bhi(x.x); sx[1] += blo(x.y) + bhi(x.y);
                sq[0] = fmaf(blo(x.x), blo(x.x), fmaf(bhi(x.x), bhi(x.x), sq[0])); sq[1] = fmaf(blo(x.y), blo(x.y), fmaf(bhi(x.y), bhi(x.y), sq[1]));
              }
            }
            if (kb == KS + 3) {
              const bool o = lane & 1;
              float v = (o ? sq[0] + sq[1] : sx[0] + sx[1]) + __shfl_xor_sync(~0u, o ? sx[0] + sx[1] : sq[0] + sq[1], 1);
              v += __shfl_xor_sync(~0u, v, 2); v += __shfl_xor_sync(~0u, v, 4); v += __shfl_xor_sync(~0u, v, 8);
              const float m = v * (-1.f / DM), r = rsq_fast(fmaxf(fmaf(__shfl_xor_sync(~0u, v, 1), 1.f / DM, -m * m), 0.f) + LN_EPS);
              ll_st128_if(!(lane & 15), Q.XST + (rb * 2 + w) * 128 + 16 * j + 4 * q + (lane >> 3), m, r, tag);
            }
              }
              if (kk == XK2 && L == 0) {
            if (kb == 0) fetch_wo();
            if (kb == 3) {
              asm volatile("cp.async.wait_all;" ::: "memory");
              fence_async_s();
              __syncwarp();
              if (lane == 0) mbar_arrive(bars + B_WOI);
            }
              }
            }
            if (kb == 8) yield_done();
            PCLK(kb * 4 + 1);
            PCLK(kb * 4 + 2);
            PCLK(kb * 4 + 3);
            prev = c.s; c.next();
          }
          const uint32_t cs = sb + prev * ST_BYTES + SM_CSQ + t * 8;
          mbar_wait_c(bars + B_CSQ, L);
          const uint32_t xs = sb + prev * ST_BYTES + SM_XST + w * 768 + 256 + q * 128;
          const float2 n0 = lds64f(xs + g * 8), n1 = lds64f(xs + g * 8 + 64);
          const float m0 = n0.x, m1 = n1.x;
#pragma unroll
          for (int u = 0; u < 4; u++) {
            rk[u >> 1][u & 1] = __uint_as_float(lds32(xs + t * 16 + ((u & 1 ? up1 : up0) ? -64 : 0) + (u & 1) * 8 + (u >> 1) * 64 + 4));
            sc[u >> 1][u & 1] = rk[u >> 1][u & 1] * ((u >> 1 ? n1.y : n0.y) * (0.23570226039551584f * 1.4426950408889634f));
          }
          float2 cv[27];
#pragma unroll
          for (int G = 0; G < 27; G++) cv[G] = lds64f(cs + G * 32);
          PCLK(36);
          wgmma_wait<0>();
          PCLK(37);
          release(prev);
          lagph ^= 1;
          TRC(tr, w, tb + 1);
          ACLK(0);
#pragma unroll
          for (int G = 9; G < 27; G++) Pk[G][1] = pack2(fmaf(m1, cv[G].x, acc[4 * G + 2]), fmaf(m1, cv[G].y, acc[4 * G + 3]));
          if (q < 3) {
#pragma unroll
            for (int i = 0; i < 6; i++) sts128(sb + att + (q >> 1) * ST_BYTES + (q & 1) * 3072 + i * 512, Pk[9 + HA_[i]][1], Pk[10 + HA_[i]][1], tag, Pk[9 + HC_[i]][1]);
          } else if (rb < 15) {
#pragma unroll
            for (int i = 0; i < 6; i++) ll_st128(hp + i * 32, __uint_as_float(Pk[9 + HA_[i]][1]), __uint_as_float(Pk[10 + HA_[i]][1]), tag, __uint_as_float(Pk[9 + HC_[i]][1]));
          }
#pragma unroll
          for (int G = 0; G < 27; G++) {
            Pk[G][0] = pack2(fmaf(m0, cv[G].x, acc[4 * G]), fmaf(m0, cv[G].y, acc[4 * G + 1]));
            if (G < 9) Pk[G][1] = pack2(fmaf(m1, cv[G].x, acc[4 * G + 2]), fmaf(m1, cv[G].y, acc[4 * G + 3]));
          }
        }
        ACLK(1);
        constexpr int GA_[4] = {0, 2, 4, 7}, GB_[4] = {1, 3, 5, 8}, GC_[4] = {2, 4, 6, 6};
        float S1[4][4], S2[4][4];
        uint32_t qa[4][2], qc[4][2];
#pragma unroll
        for (int h = 0; h < 4; h++) {
#pragma unroll
          for (int r = 0; r < 2; r++) {
            qa[h][r] = (h == 0 || h == 3 || t >= h) ? Pk[GA_[h]][r] : 0u;
            qc[h][r] = (h == 3 ? t == 3 : t <= h) ? Pk[GC_[h]][r] : 0u;
          }
#pragma unroll
          for (int i = 0; i < 4; i++) S1[h][i] = S2[h][i] = 0.f;
          mma16(S1[h], qa[h][0], qa[h][1], Pk[GB_[h]][0], Pk[GB_[h]][1], Pk[9 + GA_[h]][0], Pk[9 + GB_[h]][0]);
          mma16(S2[h], qa[h][0], qa[h][1], Pk[GB_[h]][0], Pk[GB_[h]][1], Pk[9 + GA_[h]][1], Pk[9 + GB_[h]][1]);
        }
#pragma unroll
        for (int h = 0; h < 4; h++) {
          mma8(S1[h], qc[h][0], qc[h][1], Pk[9 + GC_[h]][0]);
          mma8(S2[h], qc[h][0], qc[h][1], Pk[9 + GC_[h]][1]);
        }
        uint32_t V1[9], V2[9];
#pragma unroll
        for (int i = 0; i < 9; i++) { V1[i] = movm(Pk[18 + i][0]); V2[i] = movm(Pk[18 + i][1]); }
        uint4 hv[6];
#pragma unroll
        for (int i = 0; i < 6; i++) hv[i] = ll_ld128g(hs + i * 512);
        const uint32_t mup = (up0 ? 0xffffu : 0u) | (up1 ? 0xffff0000u : 0u);
        auto finish = [&](const float (&x0)[4], const float (&x1)[4], const uint32_t (&Vb)[9], uint32_t ma, int hi) {
          uint32_t p[4], n[4];
          float rs[4];
#pragma unroll
          for (int h = 0; h < 4; h++) {
            const float m = qmax(fmaxf(x0[h], x1[h])), e0 = ex2(x0[h] - m), e1 = ex2(x1[h] - m);
            n[h] = pack2(e0, e1);
            p[h] = pack2(e0 * rk[hi][0], e1 * rk[hi][1]);
          }
#pragma unroll
          for (int h = 0; h < 4; h += 2) {
            float D[4] = {0.f, 0.f, 0.f, 0.f};
            mma8(D, n[h], n[h + 1], 0x3f803f80u);
            rs[h] = rcp_fast(D[0]); rs[h + 1] = rcp_fast(D[2]);
          }
#pragma unroll
          for (int i = 0; i < 9; i++) {
            const int h = i < 4 ? 0 : i == 4 ? 1 : 2;
            const bool nx = (i == 2 || i == 4 || i == 6) ? 2 * t >= i : i == 3 || i > 6;
            float O[4] = {0.f, 0.f, 0.f, 0.f};
            mma16(O, p[h] & ma, p[h + 1] & ma, p[h] & ~ma, p[h + 1] & ~ma, V1[i], Vb[i]);
            const float r = nx ? rs[h + 1] : rs[h];
            stg32(od + i * 1024 + hi * 256, pack2((nx ? O[2] : O[0]) * r, (nx ? O[3] : O[1]) * r));
          }
        };
        {
          float x0[4], x1[4];
#pragma unroll
          for (int h = 0; h < 4; h++) { x0[h] = (up0 ? S1[h][2] : S2[h][2]) * sc[1][0]; x1[h] = (up1 ? S1[h][3] : S2[h][3]) * sc[1][1]; }
          finish(x0, x1, V2, mup, 1);
        }
        ACLK(2);
        bar_sync(1 + w, 128);
#pragma unroll 1
        for (int it = 0; it < (1 << 20); it++) {
          if (remote) {
            bool ok = true;
#pragma unroll
            for (int i = 0; i < 6; i++) ok = ok && hv[i].z == tag;
            if (__all_sync(~0u, ok)) break;
          }
#pragma unroll
          for (int i = 0; i < 6; i++) hv[i] = ll_ld128g(hs + i * 512);
          if (!remote) break;
        }
        uint32_t H[18];
#pragma unroll
        for (int i = 0; i < 6; i++) { H[HA_[i]] = hv[i].x; H[HA_[i] + 1] = hv[i].y; H[HC_[i]] = hv[i].w; }
        float S0[4][4];
#pragma unroll
        for (int h = 0; h < 4; h++) {
#pragma unroll
          for (int i = 0; i < 4; i++) S0[h][i] = 0.f;
          mma16(S0[h], qa[h][0], qa[h][1], Pk[GB_[h]][0], Pk[GB_[h]][1], H[GA_[h]], H[GB_[h]]);
        }
#pragma unroll
        for (int h = 0; h < 4; h++) mma8(S0[h], qc[h][0], qc[h][1], H[GC_[h]]);
        uint32_t V0[9];
#pragma unroll
        for (int i = 0; i < 9; i++) V0[i] = movm(H[9 + i]);
        ACLK(3);
        {
          const bool nohalo = (rb | q) == 0;
          const float b0 = up0 && nohalo ? -INFINITY : 0.f, b1 = up1 && nohalo ? -INFINITY : 0.f;
          float x0[4], x1[4];
#pragma unroll
          for (int h = 0; h < 4; h++) { x0[h] = fmaf(up0 ? S0[h][0] : S1[h][0], sc[0][0], b0); x1[h] = fmaf(up1 ? S0[h][1] : S1[h][1], sc[0][1], b1); }
          finish(x0, x1, V0, ~mup, 0);
        }
        ACLK(4);
        signal(EV_O);
        ACLK_OUT;
        TRC(tr, w, tb + 2);
      }
      if (c.s) { c.s = 0; c.ph ^= 1; }
      if (PHM & 2) PHASE;
      {
        float acc[36];
        const int hw = rb * 2 + w;
        const uint32_t xt = stg + (8 * q + g) * 144 + t * 4;
        uint32_t xm = sb + SM_STG + 9216 + (8 * q + (lane & 7)) * 144 + (lane & 8) * 576 + (lane & 16);
        uint8_t* xn = xn_block(hw) + j * 9216 + q * 256 + lane * 4;
        uint32_t* sp = (uint32_t*)(Q.ST1 + (hw * 8 + j) * 32 + 8 * q) + lane;
        const uint4* sg = Q.ST1 + (hw * 8 + t) * 32 + 8 * q + g;
        asm volatile("" : "+r"(xm), "+l"(xn), "+l"(sp), "+l"(sg));
        mbar_wait_c(bars + B_RES + w * 8, L);
        TRC(tr, w, tb + 21);
#pragma unroll
        for (int i = 0; i < 18; i++) { const uint32_t x = lds32(xt + (i >> 1) * 16 + (i & 1) * 4608); acc[2 * i] = blo(x); acc[2 * i + 1] = bhi(x); asm volatile("" : "+f"(acc[2 * i]), "+f"(acc[2 * i + 1])); }
        mbar_wait_c(bars + B_WF, L);
        const uint32_t db = dlo(sb, 1152), of = bars + (w ? B_OF + 40 : B_AV + 96);
        uint32_t da[5];
#pragma unroll
        for (int e = 0; e < 5; e++) da[e] = __shfl_sync(~0u, dlo(sb + o_place(w, e), 1024), 0);
        if (w) {
#pragma unroll 1
          for (int kb = q; kb < 9; kb += 4) {
            const uint32_t e = (kb + 1) >> 1;
            mbar_wait_c(bars + B_OF + e * 8, L);
            check(Int<8>{}, sb + o_place(0, e) + (kb && !(kb & 1)) * 8192, z1_block(rb, 0, 0) + kb * 8192);
            if (lane <= !kb) mbar_arrive(bars + B_AV + (12 + e) * 8);
          }
          bar_sync(7, 256);
        }
        mbar_wait_c(of, L & w);
        TRC(tr, w, tb + 3);
        wgmma_fence();
#pragma unroll
        for (int kk = 0; kk < 4; kk++) wgmma_ss_n72(acc, dsc<128, 0>(da[0], kk * 2048), dsc<128, 0>(db, kk * 2304), 1);
        wgmma_commit();
#pragma unroll 1
        for (int h = 0; h < 2; h++) {
#pragma unroll
          for (int u = 0; u < 4; u++) {
            if (!(u & 1)) { mbar_wait_c(of + 8 + h * 16 + u * 4, 1 + 2 * h + (u >> 1) < SPL ? L & w : L); wgmma_fence(); }
            if (u == 3 && h && !w) bar_arrive(7, 256);
#pragma unroll
            for (int kk = 0; kk < 4; kk++) wgmma_ss_n72(acc, dsc<128, 0>(da[1 + (u >> 1)], (u & 1) * 8192 + kk * 2048), dsc<128, 0>(db + h * 2304, (1 + u) * 9216 + kk * 2304), 1);
            if (u != 2) wgmma_commit();
            if (u == 0) { wgmma_wait<1>(); if (lane + w == 0 && h) mbar_arrive(bars + B_X3); }
          }
          da[1] = da[3]; da[2] = da[4];
        }
        RCLK_INIT;
        wgmma_wait<0>();
        RCLK(0);
        if (lane < 2) mbar_arrive_cluster(ebar + B_XD - B_EMPTY + w * 8);
        TRC(tr && P5TRACE != 5, w, tb + 4);
        {
          float s0 = 0.f, s1 = 0.f, q0 = 0.f, q1 = 0.f;
#pragma unroll
          for (int i = 0; i < 36; i++) {
            if (i & 2) { s1 += acc[i]; q1 = fmaf(acc[i], acc[i], q1); } else { s0 += acc[i]; q0 = fmaf(acc[i], acc[i], q0); }
          }
          const bool o1 = t & 1, o2 = t & 2;
          const float ss = (o1 ? s1 : s0) + __shfl_xor_sync(~0u, o1 ? s0 : s1, 1), sq = (o1 ? q1 : q0) + __shfl_xor_sync(~0u, o1 ? q0 : q1, 1);
          const float v = (o2 ? sq : ss) + __shfl_xor_sync(~0u, o2 ? ss : sq, 2);
          asm volatile("st.relaxed.gpu.global.u32 [%0], %1;" ::"l"(sp), "r"(__float_as_uint(v)) : "memory");
        }
        RCLK(1);
        RCLK(2);
        pause<PDEL>(Q.zero);
        uint4 pa, pb;
        auto there = [&](const uint4& a, const uint4& b) { return __all_sync(~0u, max(max(max(a.x, a.y), max(a.z, a.w)), max(max(b.x, b.y), max(b.z, b.w))) != ~0u); };
#pragma unroll 1
        for (int it = 0; it < (1 << 20); it++) {
          pa = ll_ld128(sg); pb = ll_ld128(sg + 128);
          if (there(pa, pb)) break;
        }
        RCLK(3);
        float mean0 = qsum(__uint_as_float(pa.x) + __uint_as_float(pb.x)) * (-1.f / DM), mean1 = qsum(__uint_as_float(pa.y) + __uint_as_float(pb.y)) * (-1.f / DM);
        const float rs0 = GA * rsq_fast(fmaxf(fmaf(qsum(__uint_as_float(pa.z) + __uint_as_float(pb.z)), 1.f / DM, -mean0 * mean0), 0.f) + LN_EPS);
        const float rs1 = GA * rsq_fast(fmaxf(fmaf(qsum(__uint_as_float(pa.w) + __uint_as_float(pb.w)), 1.f / DM, -mean1 * mean1), 0.f) + LN_EPS);
        mean0 *= rs0; mean1 *= rs1;
#pragma unroll
        for (int i = 0; i < 18; i++) {
          const float a = (i & 1) ? rs1 : rs0, b = (i & 1) ? mean1 : mean0;
          stg32(xn + (i >> 1) * 1024 + (i & 1) * 128, pack2(fmaf(acc[2 * i], a, b), fmaf(acc[2 * i + 1], a, b)));
        }
        signal(EV_X1);
        RCLK(4);
        if (w) {
#pragma unroll 1
          for (int u = q; u < 24; u += 4) {
            const uint32_t mb = u < 2 * SPL ? u >= SPL : u & 1, k = u < 2 * SPL ? u - mb * SPL : u >> 1;
            mbar_wait_c(bars + B_AF3 + mb * 96 + k * 8, L);
            SCLK3(u);
            check(Int<6>{}, sb + k * 12288 + mb * 6144, xn_block(rb * 2 + mb) + k * 6144);
            SCLK3(24 + u);
            if (lane <= (u < 2 * SPL)) mbar_arrive(bars + B_AV + (u < SPL ? 12 + k : k) * 8);
          }
          TRVI(lane == 0 && P5TRACE != 5, 5, 56 + L * 4 + q, rp);
          mbar_wait_c(bars + B_S5, L);
        }
#pragma unroll
        for (int u = 0; u < 4; u++)
          stsm4(xm + u * 32, pack2(acc[8 * u], acc[8 * u + 1]), pack2(acc[8 * u + 2], acc[8 * u + 3]), pack2(acc[8 * u + 4], acc[8 * u + 5]), pack2(acc[8 * u + 6], acc[8 * u + 7]));
        asm volatile("stmatrix.sync.aligned.m8n8.x2.shared.b16 [%0], {%1,%2};" ::"r"(xm + 128), "r"(pack2(acc[32], acc[33])), "r"(pack2(acc[34], acc[35])) : "memory");
        fence_async_s();
        signal(EV_XS);
        RCLK(5);
        TRC(tr, w, tb + 5);
        RCLK(6);
        RCLK_OUT;
      }
      if (PHM & 4) PHASE;
      {
      float acc[160];
#pragma unroll
      for (int i = 0; i < 160; i++) acc[i] = 0.f;
      float s[2] = {0.f, 0.f}, qq[2] = {0.f, 0.f}, zo = 0.f;
      const uint32_t zp = sb + SM_ZP3 + (tid & 127) * 4;
      auto zstat = [&](int mb, bool on) {
        const bool o1 = t & 1, o2 = t & 2;
        const float ss = ((o1 ? s[1] : s[0]) + __shfl_xor_sync(~0u, o1 ? s[0] : s[1], 1)) * 0x1p60f, sq = (o1 ? qq[1] : qq[0]) + __shfl_xor_sync(~0u, o1 ? qq[0] : qq[1], 1);
        const uint32_t v = __float_as_uint((o2 ? sq : ss) + zo + __shfl_xor_sync(~0u, o2 ? ss : sq, 2));
        asm volatile("{\n.reg .pred p, q, r;\nsetp.eq.u32 p, %4, 1;\nsetp.eq.u32 q, %4, 2;\nsetp.eq.and.u32 r, %5, 0, q;\n@p st.shared.u32 [%0], %2;\n@p bar.arrive 13, 256;\n"
                     "@q st.relaxed.gpu.global.u32 [%1], %2;\n@r mbarrier.arrive.shared::cta.b64 _, [%3];\n}" ::"r"(zp + mb * 512), "l"((uint32_t*)(Q.ZST + ((rb * 2 + mb) * 8 + j) * 32) + (tid & 127)),
                     "r"(v), "r"(bars + B_ZS + mb * 8), "r"(on ? 1 + w : 0), "r"(lane) : "memory");
        s[0] = s[1] = qq[0] = qq[1] = 0.f;
      };
      const uint32_t ebar3 = ebar + (B_E3 - B_EMPTY);
#pragma unroll 1
      for (int half = 0; half < 2; half++) {
        const bool big = half != w;
        auto rel3 = [&](int p) { if (lane < 2) mbar_arrive_cluster(ebar3 + p * 8); };
        if (half + w > 0) bar_sync(6 + w, 256);
        auto pass = [&](auto nk) {
          constexpr int NK = nk.value;
          uint32_t d0 = dlo(sb, 1024), ph = half & ~w, af = bars + B_AV;
          const uint32_t db = dlo(sb + SM_B3, NK == 3 ? 6144 : 2048);
          const bool lead = NK == 3 && !half;
          if (lead) {
#pragma unroll
            for (int u = 0; u < 2 * SPL; u++) {
              const int mb = u / SPL, p = u % SPL;
              if (!mb) mbar_wait_c(bars + B_F3 + p * 8, 0);
              mbar_wait_c(af + (mb ? p : 12 + p) * 8, mb || p > 4 ? L : 1);
              TRC(tr && u == 0, w, tb + 6);
              SCLK2(u);
              if (p == 0) SCLK(mb * 4);
              wgmma_fence();
#pragma unroll
              for (int kk = 0; kk < 3; kk++) {
                wgmma_ss_n128(acc + mb * 80, dsc<128, 0>(d0, p * 12288 + kk * 2048 + mb * 6144), dsc<1024, 1>(db, p * 12288 + kk * 2048), p + kk > 0);
                if (kk == 0 && u > SPL) { wgmma_commit(); wgmma_wait<1>(); rel3(p - 1); }
              }
              wgmma_commit();
            }
          }
#pragma unroll 1
          for (int it = 0; it < 6 / NK; it++) {
#pragma unroll
            for (int p = 0; p < 6; p++) {
              if (p < SPL && lead && it == 0) continue;
              mbar_wait_c(bars + B_F3 + p * 8, ph);
              if (NK == 3) mbar_wait_c(af + p * 8, L);
              TRC(tr && p == 0 && it == 0, w, tb + 6 + half * 4);
              if (lead) SCLK2(12 + it * 6 + p);
              if (NK == 2 ? !(p & 1) : p % 3 == 0) SCLK(half * 11 + (NK == 2 ? it * 3 + p / 2 : it * 2 + p / 3));
              wgmma_fence();
#pragma unroll
              for (int u = 0; u < 2 * NK; u++) {
                const int kk = u >> 1, mb = u & 1, e = p * NK + kk;
                const uint64_t da = dsc<128, 0>(d0, (e / 3) * 12288 + (e % 3) * 2048 + mb * 6144);
                if (NK == 3) wgmma_ss_n128(acc + mb * 80, da, dsc<1024, 1>(db, p * 12288 + kk * 2048), e > 0 || it > 0);
                else wgmma_ss_n160(acc + mb * 80, da, dsc<1024, 1>(db, p * 12288 + kk * 6144), e > 0 || it > 0);
                if (u == 0) { wgmma_commit(); wgmma_wait<1>(); if (p > 0 || it > 0) rel3((p + 5) % 6); }
                if (u == HO3 && p == 5 && it == 6 / NK - 1) bar_arrive(7 - w, 256);
              }
              wgmma_commit();
            }
            d0 += NK * 1536; af += 48;
            ph ^= 1;
          }
        };
        if (big) pass(Int<2>{}); else pass(Int<3>{});
        if (w) { bar_sync(13, 256); zo = __uint_as_float(lds32(zp + half * 512)); }
        if (half) zstat(1, true);
        const uint32_t off2 = lds32(sb + SM_OFF);
        const int go = (j & 1) ? (big ? 0 : 20) : (big ? 16 : 0);
        const float* gbp = (const float*)(smem_raw + SM_OFF + 8);
        asm volatile("" : "+l"(gbp));
        uint8_t* zd = half ? z1_block(rb, 0, j) + go * 1024 + (q & 1) * 2048 + (q >> 1) * 512 + lane * 16 : z2_block(rb, j) + q * 9216 + go * 128 + ((g & 3) * 2 + (g >> 2)) * 16 + t * 4;
        wgmma_wait<0>();
        SCLK(half * 11 + 9);
        rel3(5);
        TRC(tr, w, tb + 7 + half * 4);
        auto gelu = [&](auto z2) {
          constexpr int NC = z2.value ? NC2 : NC1;
          float gate[NC], gb = GB, gn = GB;
          uint32_t qa[2][3] = {{0, 0, 0}, {0, 0, 0}};
#pragma unroll
          for (int e = 0; e < NC; e++) gate[e] = GB;
#pragma unroll
          for (int G = 0; G < 20; G++) {
            if (G == 16 && !big) break;
            if (G % (z2.value ? LD2 : LD1) == 0) { gb = gn; if (G < 20 - (z2.value ? LD2 : LD1)) asm volatile("ld.f32 %0, [%1];" : "=f"(gn) : "l"(gbp) : "memory"); }
#pragma unroll
            for (int r = 0; r < 2; r++) {
              float z[2];
              float& gt = gate[(G * 2 + r) % NC];
#pragma unroll
              for (int e = 0; e < 2; e++) {
                const float v = acc[4 * G + 2 * r + e];
                z[e] = fmaf(v, tanh_fast(v * fmaf(v, v, gt)), v);
                if (z2.value) { s[r] = fmaf(z[e], 0x1p-60f, s[r]); qq[r] = fmaf(z[e], z[e], qq[r]); }
              }
              const uint32_t pk = pack2(z[0], z[1]);
              if (z2.value) {
                stg32(zd + G * 128 + r * 4608, hsub2(pk, off2));
                gt = fmaf(qq[r], s[r], gb);
              } else {
                gt = fmaf(__uint_as_float(pk), 0x1p-60f, gb);
                if ((G & 3) == 3) stg128(zd + (G >> 2) * 4096 + r * (8 * ZB), qa[r][0], qa[r][1], qa[r][2], pk);
                else qa[r][G & 3] = pk;
              }
            }
          }
        };
#pragma unroll 1
        for (int mb = 0;; mb++) {
          if (half) gelu(Int<0>{}); else gelu(Int<1>{});
          if (mb) break;
          zstat(0, !half);
#pragma unroll
          for (int i = 0; i < 80; i++) acc[i] = acc[80 + i];
          zd += half ? 1024 : 128 * ZB;
        }
        mbar_wait_c(bars + B_GATE3, L);
        signal(half ? EV_Z1 : EV_ZN);
        SCLK(half * 11 + 10);
        TRC(tr, w, tb + 8 + half * 4);
      }
      }
      if (PHM & 8) PHASE;
      const uint32_t aoff = (w * 64 + q * 16 + (lane & 15)) * 128 + (((lane >> 4) ^ (lane & 7)) << 4);
      uint32_t hA[18][4];
      {
        float acc[144];
        const float c0 = __uint_as_float(lds32(sb + SM_OFF + 4));
#pragma unroll
        for (int i = 0; i < 144; i++) {
          asm volatile("fma.rn.f32 %0, %1, %2, %3;" : "=f"(acc[i]) : "f"(__uint_as_float(Q.zero)), "f"((float)(i + 2)), "f"(c0));
        }
        uint32_t prev = 0;
        auto stage = [&](int kb) {
          mbar_wait_c(bars + B_FULL + c.s * 8, c.ph);
          TRC(tr && kb == 0, w, tb + 13);
          SCLK(22 + kb);
          const uint32_t st = sb + c.s * ST_BYTES, db = dlo(st + ST_B, 4608), rt = sb + SM_RT + kb * 128 + t * 8;
          uint32_t a[4][4];
#pragma unroll
          for (int kk = 0; kk < 4; kk++) {
            uint32_t r[4];
            ldsm4(r, st + (aoff ^ (kk << 5)));
            const uint2 sc = lds64(rt + kk * 32);
            a[kk][0] = hmul2(__byte_perm(r[0], r[2], 0x5410), sc.x); a[kk][2] = hmul2(__byte_perm(r[0], r[2], 0x7632), sc.y);
            a[kk][1] = hmul2(__byte_perm(r[1], r[3], 0x5410), sc.x); a[kk][3] = hmul2(__byte_perm(r[1], r[3], 0x7632), sc.y);
          }
          if (kb + w == 0) bar_sync(6, 256);
          wgmma_fence();
#pragma unroll
          for (int i = 0; i < 8; i++) {
            const int kk = i & 3, hf = i >> 2;
            wgmma_rs_n144(acc + hf * 72, a[kk], dsc<128, 0>(db, kk * 9216 + hf * 2304), 1);
            if (i == 0) { wgmma_commit(); wgmma_wait<1>(); if (kb) release(prev); }
            if (i == 3) wgmma_commit();
          }
          wgmma_commit();
          prev = c.s; c.next();
        };
#pragma unroll 1
        for (int kb = 0; kb < 32; kb += 2) {
          if (!(kb & 7)) mbar_wait_c(bars + B_RT + kb, L);
          stage(kb);
          stage(kb + 1);
        }
        mbar_wait_c(bars + B_CV + w * 8, L);
        const float gk = 0.5f / GA;
        const float c1 = __uint_as_float(lds32(sb + SM_OFF + 4));
        const float gb0 = -gk * (c1 + __uint_as_float(lds32(sb + SM_CV + w * 256 + (16 * q + g) * 4))), gb1 = -gk * (c1 + __uint_as_float(lds32(sb + SM_CV + w * 256 + (16 * q + g + 8) * 4)));
        if (w == 1) { mbar_wait_c(bars + B_FULL + c.s * 8, c.ph); release(c.s); c.next(); }
        mbar_wait_c(bars + B_FULL + c.s * 8, c.ph);
        const uint32_t zs = sb + c.s * ST_BYTES + ST_B + (tid & 127) * 16;
        uint4 zl, zh;
#pragma unroll
        for (int u = 0; u < 18; u++) {
          if (u == 0) wgmma_wait<1>();
          if (u == 9) {
            wgmma_wait<0>();
            release(prev);
            if (L == 0) signal(EV_PT);
            TRC(tr, w, tb + 14);
            SCLK(54);
          }
          if (!(u & 1)) { zl = lds128(zs + u * 2048); zh = lds128(zs + u * 2048 + 2048); }
          const uint4 z = (u & 1) ? make_uint4(zl.z, zh.z, zl.w, zh.w) : make_uint4(zl.x, zh.x, zl.y, zh.y);
          hA[u][0] = hmul2(z.x, pack2(fmaf(acc[8 * u], gk, gb0), fmaf(acc[8 * u + 1], gk, gb0)));
          hA[u][1] = hmul2(z.y, pack2(fmaf(acc[8 * u + 2], gk, gb1), fmaf(acc[8 * u + 3], gk, gb1)));
          hA[u][2] = hmul2(z.z, pack2(fmaf(acc[8 * u + 4], gk, gb0), fmaf(acc[8 * u + 5], gk, gb0)));
          hA[u][3] = hmul2(z.w, pack2(fmaf(acc[8 * u + 6], gk, gb1), fmaf(acc[8 * u + 7], gk, gb1)));
        }
        __syncwarp();
        release(c.s);
        c.next();
        if (w == 0) { mbar_wait_c(bars + B_FULL + c.s * 8, c.ph); release(c.s); c.next(); }
        TRC(tr, w, tb + 15);
      }
      {
        CLK_INIT;
        if (w == 1) bar_arrive(6, 256);
        uint32_t pk[16];
#pragma unroll
        for (int i = 0; i < 16; i++) pk[i] = 0u;
        auto dump = [&](int p) {
          const uint32_t d = sb + (p & 3) * ST_BYTES, cb = p + j >= 9 ? p + j - 9 : p + j;
          if (lane == 0) asm volatile("cp.async.bulk.wait_group.read 3;" ::: "memory");
          __syncwarp();
#pragma unroll
          for (int u = 0; u < 4; u++) stsm4(d + (aoff ^ (u << 5)), pk[4 * u], pk[4 * u + 1], pk[4 * u + 2], pk[4 * u + 3]);
          fence_async_s();
          __syncwarp();
          tma3d_red_p(lane == 0, &P.red, cb * 64, rb * 64 + q * 16, w, d + w * 8192 + q * 2048);
        };
#pragma unroll 1
        for (int p = 0; p < 9; p++) {
          float acc[32];
          CLK(0);
          mbar_wait_c(bars + B_FULL + c.s * 8, c.ph);
          const uint32_t db = dlo(sb + c.s * ST_BYTES + ST_B, 0);
          CLK(1);
          bar_sync(6 + w, 256);
          CLK(2);
          wgmma_fence();
#pragma unroll
          for (int kk = 0; kk < 18; kk++) {
            wgmma_rs_n64(acc, hA[kk], dsc<1024, 1>(db, kk * 2048), kk != 0);
            if (kk == PPK && (w == 0 || p < 8)) bar_arrive(7 - w, 256);
          }
          wgmma_commit();
          CLK(3);
          if (p > 0) dump(p - 1);
          CLK(5);
          wgmma_wait<0>();
          CLK(4);
          if (L == 0 || p < 5) release(c.s);
          c.next();
#pragma unroll
          for (int i = 0; i < 16; i++) pk[i] = pack2(acc[2 * i], acc[2 * i + 1]);
          if (p == 8) { TRC(tr, w, tb + 16); dump(8); TRC(tr, w, tb + 17); }
        }
        if (lane == 0) asm volatile("cp.async.bulk.wait_group 0;" ::: "memory");
        if (L == 0) signal(EV_PT);
        CLK_OUT;
        TRC(tr, w, tb + 18);
      }
    }
    if ((tid & 127) == 0) Q.flags[(rb * 2 + w) * 32 + FR_EP + j] = epoch + 1;
    if (tid == 0) Q.flags[FJ + j * 32 + FJ_EP + rb] = epoch + 1;
  }
}

typedef CUresult (*EncodeFn)(CUtensorMap*, CUtensorMapDataType, cuuint32_t, void*, const cuuint64_t*, const cuuint64_t*, const cuuint32_t*,
                             const cuuint32_t*, CUtensorMapInterleave, CUtensorMapSwizzle, CUtensorMapL2promotion, CUtensorMapFloatOOBfill);

static void make_map(EncodeFn fn, CUtensorMap* m, const void* ptr, int rank, uint64_t d0, uint64_t d1, uint64_t d2, uint64_t s1, uint64_t s2,
                     uint32_t b0, uint32_t b1, uint32_t b2, CUtensorMapSwizzle swz) {
  cuuint64_t dims[3] = {d0, d1, d2}, strides[2] = {s1, s2};
  cuuint32_t box[3] = {b0, b1, b2}, es[3] = {1, 1, 1};
  fn(m, CU_TENSOR_MAP_DATA_TYPE_BFLOAT16, rank, const_cast<void*>(ptr), dims, strides, box, es, CU_TENSOR_MAP_INTERLEAVE_NONE, swz,
     CU_TENSOR_MAP_L2_PROMOTION_L2_128B, CU_TENSOR_MAP_FLOAT_OOB_FILL_NONE);
}

}

extern "C" void kernel_launch(void* const* d_in, const int* in_sizes, int n_in, void* d_out, int out_size) {
  using namespace mk;
  (void)in_sizes; (void)n_in; (void)out_size;
  static EncodeFn fn = nullptr;
  static Scratch* sc = nullptr;
  if (!fn) {
    cudaDriverEntryPointQueryResult qr;
    cudaGetDriverEntryPoint("cuTensorMapEncodeTiled", (void**)&fn, cudaEnableDefault, &qr);
    cudaGetSymbolAddress((void**)&sc, g_scratch);
    cudaFuncSetAttribute(mega_kernel, cudaFuncAttributeMaxDynamicSharedMemorySize, SM_TOTAL);
  }
  Params p;
  Ptrs a;
  a.x = (const uint8_t*)d_in[0];
  a.wqkv = (const __nv_bfloat16*)d_in[1];
  a.wo = (const __nv_bfloat16*)d_in[2];
  a.w_in = (const __nv_bfloat16*)d_in[4];
  a.w_sp = (const __nv_bfloat16*)d_in[5];
  a.b_sp = (const __nv_bfloat16*)d_in[6];
  a.out = (uint8_t*)d_out;
  a.zero = 0;
  a.WQ = sc->WQ; a.flags = sc->flags; a.CSP = sc->CSP; a.XST = sc->XST; a.HALO = sc->HALO; a.ST1 = sc->ST1; a.ZST = sc->ZST; a.RT = sc->RT; a.Z = sc->Z; a.WO = sc->WO;
  make_map(fn, &p.wsp, a.w_sp, 3, 2048, 1024, 2, 8192, 4096, 64, 64, 2, CU_TENSOR_MAP_SWIZZLE_128B);
  for (int i = 0; i < 2; i++) {
    make_map(fn, &p.act[i], i ? a.out : a.x, 3, DM, 1024, 2, 2304, 1152, 64, 64, 1, CU_TENSOR_MAP_SWIZZLE_128B);
    make_map(fn, &p.row[i], i ? a.out : a.x, 3, 192, 6, 1024, 384, 2304, 192, 3, 8, CU_TENSOR_MAP_SWIZZLE_NONE);
    make_map(fn, &p.res[i], i ? a.out : a.x, 3, DM, 1024, 2, 2304, 1152, 72, 32, 2, CU_TENSOR_MAP_SWIZZLE_NONE);
  }
  make_map(fn, &p.red, d_out, 3, DM, 1024, 2, 2304, 1152, 64, 16, 1, CU_TENSOR_MAP_SWIZZLE_128B);
  for (int i = 0; i < 2; i++) make_map(fn, &p.winb[i], a.w_in + 32 * i, 3, 64, 576, 72 - i, 9216, 128, 64, 16, 3, CU_TENSOR_MAP_SWIZZLE_128B);
  make_map(fn, &p.wins, a.w_in, 3, 64, 576, 72, 9216, 128, 64, 48, 1, CU_TENSOR_MAP_SWIZZLE_128B);
  make_map(fn, &p.wout, d_in[7], 2, 576, 2304, 1, 1152, 0, 64, 144, 1, CU_TENSOR_MAP_SWIZZLE_128B);
  mega_kernel<<<NGRID, 384, SM_TOTAL, cudaStreamPerThread>>>(a, p);
}
```

```cpp
#include <cuda_runtime.h>
#include <cuda.h>
#include <cuda_bf16.h>
#include <stdint.h>

#define MK_TRACE 0
#define MK_DBG 0
#define P5TRACE 0
#define LAG1 1
#define C0S 32.f
#define OFM 0x10u
#define NC2 2
#define NC1 6
#define PDEL 8
#define LD1 4
#define LD2 2
#define ZD1 8
#define ZD2 20
#define WPF 1
#define YPACE 2
#define SPL 3
#define XP0 10
#define EFM 0x33333022
#define EF(i) ((((EFM >> (4 * (i))) & 3) == 3) || (((EFM >> (4 * (i))) >> L) & 1))
#define AEP 2
#define PZI 4
#define KS 1
#define RFI 3
#define XK1 1
#define XK2 2
#define SDEL 10
#define FD3 14
#define FD4 0
#define FD5 0
#define PHM 15
#define PFT 0
#define APACE 7
#define HO3 1
#define PPK 13

namespace mk {

constexpr int SEQ = 2048, DM = 576, FH = 2304;
constexpr int NCTA = 128;
constexpr int NGRID = 132;
constexpr uint32_t ZB = 36864;
constexpr uint32_t WQ_SL = 72 * 3456;
constexpr uint32_t WO_SL = 72 * 1152;
constexpr float LN_EPS = 1e-5f;
constexpr float GA = 0.3292034911525734f, GB = 2.423681954311584f;

constexpr uint32_t ST_BYTES = 53248, ST_B = 16384, NST = 4;
constexpr uint32_t SM_STG = NST * ST_BYTES;
constexpr uint32_t SM_BAR = SM_STG + 2 * 9216, B_OFF = 896;
constexpr uint32_t SM_OFF = SM_BAR + B_OFF;
constexpr uint32_t SM_TOTAL = SM_BAR + 1024;
constexpr uint32_t SM_RT = SM_STG + 9216, SM_CV = SM_STG + 17408, SM_WT = SM_STG;
constexpr uint32_t SM_WOI = 44032, SM_CSQ = 49280, SM_XST = 50176;
enum { EV_PT = 0, EV_O = 1, EV_X1 = 2, EV_ZN = 3, EV_Z1 = 4, EV_XS = 5, EV_N = 6 };
constexpr uint32_t B_FULL = 0, B_FULLA = 32, B_RES = 96, B_WT = 112, B_GATE3 = 128, B_Z1 = 136, B_ZOK = 144, B_CV = 152, B_XRW = 168, B_F3 = 184, B_WF = 232, B_OF = 240,
                   B_RT = 320, B_AF3 = 352, B_RB = 544,
                   B_AD = 576, B_S5 = 608, B_AV = 616,
                   B_CSQ = 760,
                   B_LAG = 768, B_X3 = 776, B_ZS = 784, B_EVT = 800,
                   B_IMG = 912, B_WOI = 920, B_E3 = 928, B_XD = 976,
                   B_EMPTY = 992;
constexpr uint32_t SM_B3 = 9 * 16384, SM_ZP3 = SM_STG + 8192;

enum { FR_X2 = 0, FR_O = 1, FR_XR = 5, FR_OL = 7, FR_PZ = 9, FR_EP = 16, FJ = 32 * 32, FJ_WQ = 0, FJ_WO = 1, FJ_ZN = 3, FJ_P4 = 5, FJ_EP = 16, F_N = FJ + 8 * 32 };

struct Scratch {
  alignas(1024) uint32_t flags[F_N];
  alignas(1024) float CSP[2 * NCTA * 216];
  alignas(1024) uint2 RT[SEQ];
  alignas(1024) uint4 XST[2 * SEQ];
  alignas(1024) uint4 ST1[SEQ * 4];
  alignas(1024) uint4 ZST[SEQ * 4];
  alignas(1024) uint4 HALO[32 * 8 * 6 * 32];
  alignas(1024) uint8_t WO[8 * WO_SL];
  alignas(1024) uint8_t WQ[8 * WQ_SL];
  alignas(1024) uint8_t Z[576 * ZB];
};
__device__ Scratch g_scratch;

struct Ptrs {
  const __nv_bfloat16* wqkv;
  uint8_t* WQ;
  uint32_t* flags;
  float* CSP;
  const uint8_t* x;
  uint32_t zero;
  uint4 *XST, *HALO, *ST1, *ZST;
  uint2* RT;
  uint8_t *Z, *WO, *out;
  const __nv_bfloat16 *wo, *w_in, *w_sp, *b_sp;
};
struct Params {
  CUtensorMap wsp, winb[2], wins, wout;
  CUtensorMap act[2];
  CUtensorMap res[2];
  CUtensorMap row[2];
  CUtensorMap red;
};

__device__ __forceinline__ uint32_t smem_u32(const void* p) { return (uint32_t)__cvta_generic_to_shared(p); }
__device__ __forceinline__ void mbar_init(uint32_t bar, uint32_t cnt) { asm volatile("mbarrier.init.shared::cta.b64 [%0], %1;" ::"r"(bar), "r"(cnt)); }
__device__ __forceinline__ void mbar_arrive(uint32_t bar) { asm volatile("mbarrier.arrive.shared::cta.b64 _, [%0];" ::"r"(bar) : "memory"); }
__device__ __forceinline__ void mbar_wait(uint32_t bar, uint32_t parity) {
  asm volatile(
      "{\n.reg .pred p;\n.reg .u32 c;\nmov.u32 c, 0;\nLAB_WAIT:\n"
      "mbarrier.try_wait.parity.shared::cta.b64 p, [%0], %1;\n@p bra LAB_DONE;\n"
      "add.u32 c, c, 1;\nsetp.lt.u32 p, c, 0x100000;\n@p bra LAB_WAIT;\ntrap;\nLAB_DONE:\n}" ::"r"(bar), "r"(parity)
      : "memory");
}
__device__ __forceinline__ void mbar_wait_c(uint32_t bar, uint32_t parity) {
  asm volatile("{\n.reg .pred p;\nLAB_WAIT:\nmbarrier.try_wait.parity.shared::cta.b64 p, [%0], %1;\n@!p bra LAB_WAIT;\n}" ::"r"(bar), "r"(parity) : "memory");
}
__device__ __forceinline__ void flag_wait(const uint32_t* f, uint32_t target) {
  asm volatile(
      "{\n.reg .pred p;\n.reg .u32 c, v;\nmov.u32 c, 0;\nLAB_WAIT:\n"
      "ld.relaxed.gpu.global.u32 v, [%0];\nsub.u32 v, v, %1;\nsetp.ge.s32 p, v, 0;\n@p bra LAB_DONE;\n"
      "add.u32 c, c, 1;\nsetp.lt.u32 p, c, 0x400000;\n@p bra LAB_WAIT;\ntrap;\nLAB_DONE:\nfence.acquire.gpu;\n}" ::"l"(f), "r"(target)
      : "memory");
}
__device__ __forceinline__ void fence_gpu() { asm volatile("fence.acq_rel.gpu;" ::: "memory"); }
__device__ __forceinline__ void fence_async_g() { asm volatile("fence.proxy.async.global;" ::: "memory"); }
__device__ __forceinline__ void fence_async_s() { asm volatile("fence.proxy.async.shared::cta;" ::: "memory"); }
__device__ __forceinline__ uint32_t elect_one() {
  uint32_t p; asm volatile("{\n.reg .pred P;\nelect.sync _|P, 0xffffffff;\nselp.u32 %0, 1, 0, P;\n}" : "=r"(p)); return p;
}
__device__ __forceinline__ void expect_tx_p(uint32_t el, uint32_t bar, uint32_t bytes) {
  asm volatile("{\n.reg .pred P;\nsetp.ne.u32 P, %2, 0;\n@P mbarrier.arrive.expect_tx.shared::cta.b64 _, [%0], %1;\n}" ::"r"(bar), "r"(bytes), "r"(el) : "memory");
}
__device__ __forceinline__ void bulk_load_p(uint32_t el, uint32_t dst, const void* src, uint32_t bytes, uint32_t bar) {
  asm volatile("{\n.reg .pred P;\nsetp.ne.u32 P, %4, 0;\n@P cp.async.bulk.shared::cluster.global.mbarrier::complete_tx::bytes [%0], [%1], %2, [%3];\n}" ::"r"(dst), "l"(src), "r"(bytes), "r"(bar), "r"(el) : "memory");
}
__device__ __forceinline__ uint64_t policy_evict_first() { uint64_t p; asm("createpolicy.fractional.L2::evict_first.b64 %0, 1.0;" : "=l"(p)); return p; }
__device__ __forceinline__ void bulk_load_h(uint32_t el, uint32_t dst, const void* src, uint32_t bytes, uint32_t bar, bool ef, uint64_t pol) {
  if (ef) {
    asm volatile("{\n.reg .pred P;\nsetp.ne.u32 P, %4, 0;\n@P cp.async.bulk.shared::cluster.global.mbarrier::complete_tx::bytes.L2::cache_hint [%0], [%1], %2, [%3], %5;\n}" ::"r"(dst), "l"(src), "r"(bytes), "r"(bar), "r"(el), "l"(pol) : "memory");
  } else {
    asm volatile("{\n.reg .pred P;\nsetp.ne.u32 P, %4, 0;\n@P cp.async.bulk.shared::cluster.global.mbarrier::complete_tx::bytes [%0], [%1], %2, [%3];\n}" ::"r"(dst), "l"(src), "r"(bytes), "r"(bar), "r"(el) : "memory");
  }
}
__device__ __forceinline__ void bulk_mc_h(uint32_t el, uint32_t dst, const void* src, uint32_t bytes, uint32_t bar, bool ef, uint64_t pol) {
  if (ef) {
    asm volatile("{\n.reg .pred P;\nsetp.ne.u32 P, %4, 0;\n@P cp.async.bulk.shared::cluster.global.mbarrier::complete_tx::bytes.multicast::cluster.L2::cache_hint [%0], [%1], %2, [%3], %5, %6;\n}" ::"r"(dst), "l"(src), "r"(bytes), "r"(bar), "r"(el), "h"((uint16_t)3), "l"(pol) : "memory");
  } else {
    asm volatile("{\n.reg .pred P;\nsetp.ne.u32 P, %4, 0;\n@P cp.async.bulk.shared::cluster.global.mbarrier::complete_tx::bytes.multicast::cluster [%0], [%1], %2, [%3], %5;\n}" ::"r"(dst), "l"(src), "r"(bytes), "r"(bar), "r"(el), "h"((uint16_t)3) : "memory");
  }
}
__device__ __forceinline__ void tma3d_h(uint32_t el, uint32_t dst, const CUtensorMap* m, int c0, int c1, int c2, uint32_t bar, bool ef, uint64_t pol) {
  if (ef) {
    asm volatile("{\n.reg .pred P;\nsetp.ne.u32 P, %6, 0;\n@P cp.async.bulk.tensor.3d.shared::cluster.global.mbarrier::complete_tx::bytes.L2::cache_hint [%0], [%1, {%3, %4, %5}], [%2], %7;\n}" ::"r"(dst), "l"(m), "r"(bar), "r"(c0), "r"(c1), "r"(c2), "r"(el), "l"(pol) : "memory");
  } else {
    asm volatile("{\n.reg .pred P;\nsetp.ne.u32 P, %6, 0;\n@P cp.async.bulk.tensor.3d.shared::cluster.global.mbarrier::complete_tx::bytes [%0], [%1, {%3, %4, %5}], [%2];\n}" ::"r"(dst), "l"(m), "r"(bar), "r"(c0), "r"(c1), "r"(c2), "r"(el) : "memory");
  }
}
__device__ __forceinline__ void tma2d_mc_h(uint32_t el, uint32_t dst, const CUtensorMap* m, int c0, int c1, uint32_t bar, bool ef, uint64_t pol) {
  if (ef) {
    asm volatile("{\n.reg .pred P;\nsetp.ne.u32 P, %5, 0;\n@P cp.async.bulk.tensor.2d.shared::cluster.global.mbarrier::complete_tx::bytes.multicast::cluster.L2::cache_hint [%0], [%1, {%3, %4}], [%2], %6, %7;\n}" ::"r"(dst), "l"(m), "r"(bar), "r"(c0), "r"(c1), "r"(el), "h"((uint16_t)3), "l"(pol) : "memory");
  } else {
    asm volatile("{\n.reg .pred P;\nsetp.ne.u32 P, %5, 0;\n@P cp.async.bulk.tensor.2d.shared::cluster.global.mbarrier::complete_tx::bytes.multicast::cluster [%0], [%1, {%3, %4}], [%2], %6;\n}" ::"r"(dst), "l"(m), "r"(bar), "r"(c0), "r"(c1), "r"(el), "h"((uint16_t)3) : "memory");
  }
}
__device__ __forceinline__ void tma3d_mc_h(uint32_t el, uint32_t dst, const CUtensorMap* m, int c0, int c1, int c2, uint32_t bar, bool ef, uint64_t pol) {
  if (ef) {
    asm volatile("{\n.reg .pred P;\nsetp.ne.u32 P, %6, 0;\n@P cp.async.bulk.tensor.3d.shared::cluster.global.mbarrier::complete_tx::bytes.multicast::cluster.L2::cache_hint [%0], [%1, {%3, %4, %5}], [%2], %7, %8;\n}" ::"r"(dst), "l"(m), "r"(bar), "r"(c0), "r"(c1), "r"(c2), "r"(el), "h"((uint16_t)3), "l"(pol) : "memory");
  } else {
    asm volatile("{\n.reg .pred P;\nsetp.ne.u32 P, %6, 0;\n@P cp.async.bulk.tensor.3d.shared::cluster.global.mbarrier::complete_tx::bytes.multicast::cluster [%0], [%1, {%3, %4, %5}], [%2], %7;\n}" ::"r"(dst), "l"(m), "r"(bar), "r"(c0), "r"(c1), "r"(c2), "r"(el), "h"((uint16_t)3) : "memory");
  }
}
__device__ __forceinline__ void mbar_arrive_cluster(uint32_t addr) { asm volatile("mbarrier.arrive.shared::cluster.b64 _, [%0];" ::"r"(addr) : "memory"); }
__device__ __forceinline__ uint32_t mapa(uint32_t addr, uint32_t rank) { uint32_t r; asm("mapa.shared::cluster.u32 %0, %1, %2;" : "=r"(r) : "r"(addr), "r"(rank)); return r; }
__device__ __forceinline__ void bulk_store_p(uint32_t el, void* dst, uint32_t src, uint32_t bytes) {
  asm volatile("{\n.reg .pred P;\nsetp.ne.u32 P, %3, 0;\n@P cp.async.bulk.global.shared::cta.bulk_group [%0], [%1], %2;\n}" ::"l"(dst), "r"(src), "r"(bytes), "r"(el) : "memory");
}
__device__ __forceinline__ void flag_release_p(uint32_t el, uint32_t* f) {
  asm volatile("{\n.reg .pred P;\nsetp.ne.u32 P, %1, 0;\nfence.proxy.async;\n@P red.relaxed.gpu.global.add.u32 [%0], 1;\n}" ::"l"(f), "r"(el) : "memory");
}
__device__ __forceinline__ void flag_add_p(uint32_t el, uint32_t* f) {
  asm volatile("{\n.reg .pred P;\nsetp.ne.u32 P, %1, 0;\n@P red.relaxed.gpu.global.add.u32 [%0], 1;\n}" ::"l"(f), "r"(el) : "memory");
}
__device__ __forceinline__ void prefetch_l2(const void* src, uint32_t bytes) { asm volatile("cp.async.bulk.prefetch.L2.global [%0], %1;" ::"l"(src), "r"(bytes) : "memory"); }
__device__ __forceinline__ void prefetch_map(const CUtensorMap* m) { asm volatile("prefetch.tensormap [%0];" ::"l"(m) : "memory"); }
__device__ __forceinline__ void wgmma_fence() { asm volatile("wgmma.fence.sync.aligned;" ::: "memory"); }
__device__ __forceinline__ void wgmma_commit() { asm volatile("wgmma.commit_group.sync.aligned;" ::: "memory"); }
template <int N> __device__ __forceinline__ void wgmma_wait() { asm volatile("wgmma.wait_group.sync.aligned %0;" ::"n"(N) : "memory"); }
__device__ __forceinline__ uint32_t dlo(uint32_t addr, uint32_t lbo) { return ((addr & 0x3FFFF) >> 4) + ((lbo >> 4) << 16); }
template <uint32_t SBO, uint32_t SWZ> __device__ __forceinline__ uint64_t dsc(uint32_t lo, uint32_t off) {
  uint64_t d; asm("mov.b64 %0, {%1, %2};" : "=l"(d) : "r"(lo + (off >> 4)), "n"((SBO >> 4) | (SWZ << 30))); return d;
}
template <int R> __device__ __forceinline__ void reg_alloc() { asm volatile("setmaxnreg.inc.sync.aligned.u32 %0;" ::"n"(R)); }
template <int R> __device__ __forceinline__ void reg_dealloc() { asm volatile("setmaxnreg.dec.sync.aligned.u32 %0;" ::"n"(R)); }
__device__ __forceinline__ void bar_sync(int id, int n) { asm volatile("bar.sync %0, %1;" ::"r"(id), "r"(n) : "memory"); }
__device__ __forceinline__ void bar_arrive(int id, int n) { asm volatile("bar.arrive %0, %1;" ::"r"(id), "r"(n) : "memory"); }
__device__ __forceinline__ void ldsm4(uint32_t* r, uint32_t addr) {
  asm volatile("ldmatrix.sync.aligned.m8n8.x4.shared.b16 {%0,%1,%2,%3}, [%4];" : "=r"(r[0]), "=r"(r[1]), "=r"(r[2]), "=r"(r[3]) : "r"(addr) : "memory");
}
__device__ __forceinline__ uint32_t movm(uint32_t a) { uint32_t d; asm volatile("movmatrix.sync.aligned.m8n8.trans.b16 %0, %1;" : "=r"(d) : "r"(a)); return d; }
__device__ __forceinline__ void mma16(float* c, uint32_t a0, uint32_t a1, uint32_t a2, uint32_t a3, uint32_t b0, uint32_t b1) {
  asm volatile("mma.sync.aligned.m16n8k16.row.col.f32.bf16.bf16.f32 {%0,%1,%2,%3}, {%4,%5,%6,%7}, {%8,%9}, {%0,%1,%2,%3};"
               : "+f"(c[0]), "+f"(c[1]), "+f"(c[2]), "+f"(c[3]) : "r"(a0), "r"(a1), "r"(a2), "r"(a3), "r"(b0), "r"(b1));
}
__device__ __forceinline__ void mma8(float* c, uint32_t a0, uint32_t a1, uint32_t b0) {
  asm volatile("mma.sync.aligned.m16n8k8.row.col.f32.bf16.bf16.f32 {%0,%1,%2,%3}, {%4,%5}, {%6}, {%0,%1,%2,%3};"
               : "+f"(c[0]), "+f"(c[1]), "+f"(c[2]), "+f"(c[3]) : "r"(a0), "r"(a1), "r"(b0));
}
__device__ __forceinline__ uint32_t pack2(float lo, float hi) { uint32_t r; asm("cvt.rn.bf16x2.f32 %0, %1, %2;" : "=r"(r) : "f"(hi), "f"(lo)); return r; }
__device__ __forceinline__ float blo(uint32_t v) { return __uint_as_float(v << 16); }
__device__ __forceinline__ float bhi(uint32_t v) { return __uint_as_float(v & 0xffff0000u); }
__device__ __forceinline__ float tanh_fast(float x) { float y; asm("tanh.approx.f32 %0, %1;" : "=f"(y) : "f"(x)); return y; }
__device__ __forceinline__ float rcp_fast(float x) { float y; asm("rcp.approx.ftz.f32 %0, %1;" : "=f"(y) : "f"(x)); return y; }
__device__ __forceinline__ float rsq_fast(float x) { float y; asm("rsqrt.approx.ftz.f32 %0, %1;" : "=f"(y) : "f"(x)); return y; }
__device__ __forceinline__ float ex2(float x) { float y; asm("ex2.approx.ftz.f32 %0, %1;" : "=f"(y) : "f"(x)); return y; }
__device__ __forceinline__ float qsum(float v) { v += __shfl_xor_sync(~0u, v, 1); v += __shfl_xor_sync(~0u, v, 2); return v; }
__device__ __forceinline__ float qmax(float v) { v = fmaxf(v, __shfl_xor_sync(~0u, v, 1)); v = fmaxf(v, __shfl_xor_sync(~0u, v, 2)); return v; }
__device__ __forceinline__ void stg32(void* p, uint32_t v) { asm volatile("st.global.u32 [%0], %1;" ::"l"(p), "r"(v) : "memory"); }
__device__ __forceinline__ void stg128(void* p, uint32_t a, uint32_t b, uint32_t c, uint32_t d) { asm volatile("st.global.v4.u32 [%0], {%1,%2,%3,%4};" ::"l"(p), "r"(a), "r"(b), "r"(c), "r"(d) : "memory"); }
__device__ __forceinline__ uint32_t ldcg32(const void* p) { uint32_t v; asm volatile("ld.global.L1::no_allocate.u32 %0, [%1];" : "=r"(v) : "l"(p) : "memory"); return v; }
__device__ __forceinline__ void stg128_if(bool c, void* p, uint32_t a, uint32_t b, uint32_t cc, uint32_t d) {
  asm volatile("{\n.reg .pred P;\nsetp.ne.u32 P, %5, 0;\n@P st.global.v4.u32 [%0], {%1,%2,%3,%4};\n}" ::"l"(p), "r"(a), "r"(b), "r"(cc), "r"(d), "r"((uint32_t)c) : "memory");
}
__device__ __forceinline__ uint2 lds64(uint32_t a) { uint2 v; asm volatile("ld.shared.v2.u32 {%0,%1}, [%2];" : "=r"(v.x), "=r"(v.y) : "r"(a) : "memory"); return v; }
__device__ __forceinline__ uint4 ldcg128(const void* p) { uint4 v; asm volatile("ld.global.cg.v4.u32 {%0,%1,%2,%3}, [%4];" : "=r"(v.x), "=r"(v.y), "=r"(v.z), "=r"(v.w) : "l"(p) : "memory"); return v; }
__device__ __forceinline__ uint32_t ldnc16(const void* p) { uint16_t v; asm volatile("ld.global.nc.u16 %0, [%1];" : "=h"(v) : "l"(p)); return v; }
__device__ __forceinline__ uint4 ldnc128(const void* p) { uint4 v; asm volatile("ld.global.nc.v4.u32 {%0,%1,%2,%3}, [%4];" : "=r"(v.x), "=r"(v.y), "=r"(v.z), "=r"(v.w) : "l"(p)); return v; }
__device__ __forceinline__ void cp_async16(uint32_t dst, const void* src) { asm volatile("cp.async.cg.shared.global [%0], [%1], 16;" ::"r"(dst), "l"(src) : "memory"); }
__device__ __forceinline__ uint32_t hsub2(uint32_t a, uint32_t b) { uint32_t d; asm("sub.rn.bf16x2 %0, %1, %2;" : "=r"(d) : "r"(a), "r"(b)); return d; }
__device__ __forceinline__ void stg32_if(bool c, void* p, uint32_t v) {
  asm volatile("{\n.reg .pred P;\nsetp.ne.u32 P, %2, 0;\n@P st.global.u32 [%0], %1;\n}" ::"l"(p), "r"(v), "r"((uint32_t)c) : "memory");
}
__device__ __forceinline__ float wsum(float v) { for (int o = 16; o; o >>= 1) v += __shfl_xor_sync(~0u, v, o); return v; }
__device__ __forceinline__ uint32_t hmul2(uint32_t a, uint32_t b) { uint32_t d; asm("mul.rn.bf16x2 %0, %1, %2;" : "=r"(d) : "r"(a), "r"(b)); return d; }
__device__ __forceinline__ void sts32(uint32_t a, uint32_t v) { asm volatile("st.shared.u32 [%0], %1;" ::"r"(a), "r"(v) : "memory"); }
__device__ __forceinline__ uint32_t lds32(uint32_t a) { uint32_t v; asm volatile("ld.shared.u32 %0, [%1];" : "=r"(v) : "r"(a) : "memory"); return v; }
__device__ __forceinline__ void sts128(uint32_t a, uint32_t x, uint32_t y, uint32_t z, uint32_t w) { asm volatile("st.shared.v4.u32 [%0], {%1,%2,%3,%4};" ::"r"(a), "r"(x), "r"(y), "r"(z), "r"(w) : "memory"); }
__device__ __forceinline__ uint4 lds128(uint32_t a) { uint4 v; asm volatile("ld.shared.v4.u32 {%0,%1,%2,%3}, [%4];" : "=r"(v.x), "=r"(v.y), "=r"(v.z), "=r"(v.w) : "r"(a) : "memory"); return v; }
__device__ __forceinline__ void ll_st64(uint2* p, uint32_t v, uint32_t tag) {
  asm volatile("{\n.reg .b64 r;\nmov.b64 r, {%1,%2};\nst.relaxed.gpu.global.b64 [%0], r;\n}" ::"l"(p), "r"(v), "r"(tag) : "memory");
}
__device__ __forceinline__ uint2 ll_ld64(const uint2* p) {
  uint2 v; asm volatile("{\n.reg .b64 r;\nld.relaxed.gpu.global.b64 r, [%2];\nmov.b64 {%0,%1}, r;\n}" : "=r"(v.x), "=r"(v.y) : "l"(p) : "memory"); return v;
}
__device__ __forceinline__ void ll_st128(uint4* p, float a, float b, uint32_t tag, float c = 0.f) {
  asm volatile("{\n.reg .b128 r;\n.reg .b64 lo, hi;\nmov.b64 lo, {%1,%2};\nmov.b64 hi, {%3,%4};\nmov.b128 r, {lo, hi};\nst.relaxed.gpu.global.b128 [%0], r;\n}" ::"l"(p), "r"(__float_as_uint(a)), "r"(__float_as_uint(b)), "r"(tag), "r"(__float_as_uint(c)) : "memory");
}
__device__ __forceinline__ uint4 ll_ld128g(const void* p) {
  uint4 v; asm volatile("{\n.reg .b128 r;\n.reg .b64 lo, hi;\nld.relaxed.gpu.b128 r, [%4];\nmov.b128 {lo, hi}, r;\nmov.b64 {%0,%1}, lo;\nmov.b64 {%2,%3}, hi;\n}" : "=r"(v.x), "=r"(v.y), "=r"(v.z), "=r"(v.w) : "l"(p) : "memory"); return v;
}
__device__ __forceinline__ uint4 ll_ld128(const uint4* p) {
  uint4 v; asm volatile("{\n.reg .b128 r;\n.reg .b64 lo, hi;\nld.relaxed.gpu.global.b128 r, [%4];\nmov.b128 {lo, hi}, r;\nmov.b64 {%0,%1}, lo;\nmov.b64 {%2,%3}, hi;\n}" : "=r"(v.x), "=r"(v.y), "=r"(v.z), "=r"(v.w) : "l"(p) : "memory"); return v;
}
__device__ __forceinline__ void publish_p(uint32_t el, uint32_t* f) {
  asm volatile("{\n.reg .pred P;\nsetp.ne.u32 P, %1, 0;\n@P cp.async.bulk.commit_group;\n@P cp.async.bulk.wait_group 0;\n@P red.release.gpu.global.add.u32 [%0], 1;\n}" ::"l"(f), "r"(el) : "memory");
}
__device__ __forceinline__ void tma3d_red_p(uint32_t el, const CUtensorMap* m, int c0, int c1, int c2, uint32_t src) {
  asm volatile("{\n.reg .pred P;\nsetp.ne.u32 P, %5, 0;\n@P cp.reduce.async.bulk.tensor.3d.global.shared::cta.add.tile.bulk_group [%0, {%2, %3, %4}], [%1];\n@P cp.async.bulk.commit_group;\n}" ::"l"(m), "r"(src), "r"(c0), "r"(c1), "r"(c2), "r"(el) : "memory");
}
__device__ __forceinline__ void stsm4(uint32_t addr, uint32_t a, uint32_t b, uint32_t c, uint32_t d) {
  asm volatile("stmatrix.sync.aligned.m8n8.x4.shared.b16 [%0], {%1,%2,%3,%4};" ::"r"(addr), "r"(a), "r"(b), "r"(c), "r"(d) : "memory");
}
__device__ __forceinline__ void sts64(uint32_t a, uint32_t x, uint32_t y) { asm volatile("st.shared.v2.u32 [%0], {%1,%2};" ::"r"(a), "r"(x), "r"(y) : "memory"); }
__device__ __forceinline__ void ll_st128_if(bool on, uint4* p, float a, float b, uint32_t tag) {
  asm volatile("{\n.reg .pred P;\n.reg .b128 r;\n.reg .b64 lo, hi;\nsetp.ne.u32 P, %4, 0;\nmov.b64 lo, {%1,%2};\nmov.b64 hi, {%3,%3};\nmov.b128 r, {lo, hi};\n@P st.relaxed.gpu.global.b128 [%0], r;\n}" ::"l"(p), "r"(__float_as_uint(a)), "r"(__float_as_uint(b)), "r"(tag), "r"((uint32_t)on) : "memory");
}
__device__ __forceinline__ uint4 ldnc128_if(bool c, const void* p) {
  uint4 v = make_uint4(0u, 0u, 0u, 0u);
  asm volatile("{\n.reg .pred P;\nsetp.ne.u32 P, %5, 0;\n@P ld.global.nc.v4.u32 {%0,%1,%2,%3}, [%4];\n}" : "+r"(v.x), "+r"(v.y), "+r"(v.z), "+r"(v.w) : "l"(p), "r"((uint32_t)c));
  return v;
}
__device__ __forceinline__ uint32_t hfma2(uint32_t a, uint32_t b, uint32_t c) { uint32_t d; asm("fma.rn.bf16x2 %0, %1, %2, %3;" : "=r"(d) : "r"(a), "r"(b), "r"(c)); return d; }
__device__ __forceinline__ float2 lds64f(uint32_t a) { float2 v; asm volatile("ld.shared.v2.f32 {%0,%1}, [%2];" : "=f"(v.x), "=f"(v.y) : "r"(a) : "memory"); return v; }
#define TRC(cond, role, idx) do {} while (0)
#define TRV(role, idx, v) do {} while (0)
#define TRVI(c, role, idx, v) do {} while (0)

#define ACLK_INIT do {} while (0)
#define ACLK(i) do {} while (0)
#define ACLK_OUT do {} while (0)
#define QCLK(i) do {} while (0)
#define PH 1
#define RCLK(i) do {} while (0)
#define RCLK_INIT do {} while (0)
#define RCLK_OUT do {} while (0)
#define SCLK(i) do {} while (0)
#define SCLK2(i) do {} while (0)
#define SCLK3(i) do {} while (0)
#define PL 1
#define PCLK(i) do {} while (0)
#define PQ 1
#define CLK_INIT do {} while (0)
#define CLK(i) do {} while (0)
#define CLK_OUT do {} while (0)

__device__ __forceinline__ void wgmma_ss_n216(float* d, uint64_t da, uint64_t db, int scaleD) {
  asm volatile("{\n.reg .pred p;\nsetp.ne.b32 p, %110, 0;\nwgmma.mma_async.sync.aligned.m64n216k16.f32.bf16.bf16 "
    "{%0,%1,%2,%3,%4,%5,%6,%7,%8,%9,%10,%11,%12,%13,%14,%15,%16,%17,%18,%19,%20,%21,%22,%23,%24,%25,%26,%27,%28,%29,%30,%31,%32,%33,%34,%35,%36,%37,%38,%39,%40,%41,%42,%43,%44,%45,%46,%47,%48,%49,%50,%51,%52,%53,%54,%55,%56,%57,%58,%59,%60,%61,%62,%63,%64,%65,%66,%67,%68,%69,%70,%71,%72,%73,%74,%75,%76,%77,%78,%79,%80,%81,%82,%83,%84,%85,%86,%87,%88,%89,%90,%91,%92,%93,%94,%95,%96,%97,%98,%99,%100,%101,%102,%103,%104,%105,%106,%107}, "
    "%108, %109, p, 1, 1, 0, 1;\n}\n"
    : "+f"(d[0]), "+f"(d[1]), "+f"(d[2]), "+f"(d[3]), "+f"(d[4]), "+f"(d[5]), "+f"(d[6]), "+f"(d[7]), "+f"(d[8]), "+f"(d[9]), "+f"(d[10]), "+f"(d[11]), "+f"(d[12]), "+f"(d[13]), "+f"(d[14]), "+f"(d[15]), "+f"(d[16]), "+f"(d[17]), "+f"(d[18]), "+f"(d[19]), "+f"(d[20]), "+f"(d[21]), "+f"(d[22]), "+f"(d[23]), "+f"(d[24]), "+f"(d[25]), "+f"(d[26]), "+f"(d[27]), "+f"(d[28]), "+f"(d[29]), "+f"(d[30]), "+f"(d[31]), "+f"(d[32]), "+f"(d[33]), "+f"(d[34]), "+f"(d[35]), "+f"(d[36]), "+f"(d[37]), "+f"(d[38]), "+f"(d[39]), "+f"(d[40]), "+f"(d[41]), "+f"(d[42]), "+f"(d[43]), "+f"(d[44]), "+f"(d[45]), "+f"(d[46]), "+f"(d[47]), "+f"(d[48]), "+f"(d[49]), "+f"(d[50]), "+f"(d[51]), "+f"(d[52]), "+f"(d[53]), "+f"(d[54]), "+f"(d[55]), "+f"(d[56]), "+f"(d[57]), "+f"(d[58]), "+f"(d[59]), "+f"(d[60]), "+f"(d[61]), "+f"(d[62]), "+f"(d[63]), "+f"(d[64]), "+f"(d[65]), "+f"(d[66]), "+f"(d[67]), "+f"(d[68]), "+f"(d[69]), "+f"(d[70]), "+f"(d[71]), "+f"(d[72]), "+f"(d[73]), "+f"(d[74]), "+f"(d[75]), "+f"(d[76]), "+f"(d[77]), "+f"(d[78]), "+f"(d[79]), "+f"(d[80]), "+f"(d[81]), "+f"(d[82]), "+f"(d[83]), "+f"(d[84]), "+f"(d[85]), "+f"(d[86]), "+f"(d[87]), "+f"(d[88]), "+f"(d[89]), "+f"(d[90]), "+f"(d[91]), "+f"(d[92]), "+f"(d[93]), "+f"(d[94]), "+f"(d[95]), "+f"(d[96]), "+f"(d[97]), "+f"(d[98]), "+f"(d[99]), "+f"(d[100]), "+f"(d[101]), "+f"(d[102]), "+f"(d[103]), "+f"(d[104]), "+f"(d[105]), "+f"(d[106]), "+f"(d[107])
    : "l"(da), "l"(db), "r"(scaleD));
}
__device__ __forceinline__ void wgmma_ss_n72(float* d, uint64_t da, uint64_t db, int scaleD) {
  asm volatile("{\n.reg .pred p;\nsetp.ne.b32 p, %38, 0;\nwgmma.mma_async.sync.aligned.m64n72k16.f32.bf16.bf16 "
    "{%0,%1,%2,%3,%4,%5,%6,%7,%8,%9,%10,%11,%12,%13,%14,%15,%16,%17,%18,%19,%20,%21,%22,%23,%24,%25,%26,%27,%28,%29,%30,%31,%32,%33,%34,%35}, "
    "%36, %37, p, 1, 1, 0, 1;\n}\n"
    : "+f"(d[0]), "+f"(d[1]), "+f"(d[2]), "+f"(d[3]), "+f"(d[4]), "+f"(d[5]), "+f"(d[6]), "+f"(d[7]), "+f"(d[8]), "+f"(d[9]), "+f"(d[10]), "+f"(d[11]), "+f"(d[12]), "+f"(d[13]), "+f"(d[14]), "+f"(d[15]), "+f"(d[16]), "+f"(d[17]), "+f"(d[18]), "+f"(d[19]), "+f"(d[20]), "+f"(d[21]), "+f"(d[22]), "+f"(d[23]), "+f"(d[24]), "+f"(d[25]), "+f"(d[26]), "+f"(d[27]), "+f"(d[28]), "+f"(d[29]), "+f"(d[30]), "+f"(d[31]), "+f"(d[32]), "+f"(d[33]), "+f"(d[34]), "+f"(d[35])
    : "l"(da), "l"(db), "r"(scaleD));
}
__device__ __forceinline__ void wgmma_ss_n128(float* d, uint64_t da, uint64_t db, int scaleD) {
  asm volatile("{\n.reg .pred p;\nsetp.ne.b32 p, %66, 0;\nwgmma.mma_async.sync.aligned.m64n128k16.f32.bf16.bf16 "
    "{%0,%1,%2,%3,%4,%5,%6,%7,%8,%9,%10,%11,%12,%13,%14,%15,%16,%17,%18,%19,%20,%21,%22,%23,%24,%25,%26,%27,%28,%29,%30,%31,%32,%33,%34,%35,%36,%37,%38,%39,%40,%41,%42,%43,%44,%45,%46,%47,%48,%49,%50,%51,%52,%53,%54,%55,%56,%57,%58,%59,%60,%61,%62,%63}, "
    "%64, %65, p, 1, 1, 0, 1;\n}\n"
    : "+f"(d[0]), "+f"(d[1]), "+f"(d[2]), "+f"(d[3]), "+f"(d[4]), "+f"(d[5]), "+f"(d[6]), "+f"(d[7]), "+f"(d[8]), "+f"(d[9]), "+f"(d[10]), "+f"(d[11]), "+f"(d[12]), "+f"(d[13]), "+f"(d[14]), "+f"(d[15]), "+f"(d[16]), "+f"(d[17]), "+f"(d[18]), "+f"(d[19]), "+f"(d[20]), "+f"(d[21]), "+f"(d[22]), "+f"(d[23]), "+f"(d[24]), "+f"(d[25]), "+f"(d[26]), "+f"(d[27]), "+f"(d[28]), "+f"(d[29]), "+f"(d[30]), "+f"(d[31]), "+f"(d[32]), "+f"(d[33]), "+f"(d[34]), "+f"(d[35]), "+f"(d[36]), "+f"(d[37]), "+f"(d[38]), "+f"(d[39]), "+f"(d[40]), "+f"(d[41]), "+f"(d[42]), "+f"(d[43]), "+f"(d[44]), "+f"(d[45]), "+f"(d[46]), "+f"(d[47]), "+f"(d[48]), "+f"(d[49]), "+f"(d[50]), "+f"(d[51]), "+f"(d[52]), "+f"(d[53]), "+f"(d[54]), "+f"(d[55]), "+f"(d[56]), "+f"(d[57]), "+f"(d[58]), "+f"(d[59]), "+f"(d[60]), "+f"(d[61]), "+f"(d[62]), "+f"(d[63])
    : "l"(da), "l"(db), "r"(scaleD));
}
__device__ __forceinline__ void wgmma_ss_n160(float* d, uint64_t da, uint64_t db, int scaleD) {
  asm volatile("{\n.reg .pred p;\nsetp.ne.b32 p, %82, 0;\nwgmma.mma_async.sync.aligned.m64n160k16.f32.bf16.bf16 "
    "{%0,%1,%2,%3,%4,%5,%6,%7,%8,%9,%10,%11,%12,%13,%14,%15,%16,%17,%18,%19,%20,%21,%22,%23,%24,%25,%26,%27,%28,%29,%30,%31,%32,%33,%34,%35,%36,%37,%38,%39,%40,%41,%42,%43,%44,%45,%46,%47,%48,%49,%50,%51,%52,%53,%54,%55,%56,%57,%58,%59,%60,%61,%62,%63,%64,%65,%66,%67,%68,%69,%70,%71,%72,%73,%74,%75,%76,%77,%78,%79}, "
    "%80, %81, p, 1, 1, 0, 1;\n}\n"
    : "+f"(d[0]), "+f"(d[1]), "+f"(d[2]), "+f"(d[3]), "+f"(d[4]), "+f"(d[5]), "+f"(d[6]), "+f"(d[7]), "+f"(d[8]), "+f"(d[9]), "+f"(d[10]), "+f"(d[11]), "+f"(d[12]), "+f"(d[13]), "+f"(d[14]), "+f"(d[15]), "+f"(d[16]), "+f"(d[17]), "+f"(d[18]), "+f"(d[19]), "+f"(d[20]), "+f"(d[21]), "+f"(d[22]), "+f"(d[23]), "+f"(d[24]), "+f"(d[25]), "+f"(d[26]), "+f"(d[27]), "+f"(d[28]), "+f"(d[29]), "+f"(d[30]), "+f"(d[31]), "+f"(d[32]), "+f"(d[33]), "+f"(d[34]), "+f"(d[35]), "+f"(d[36]), "+f"(d[37]), "+f"(d[38]), "+f"(d[39]), "+f"(d[40]), "+f"(d[41]), "+f"(d[42]), "+f"(d[43]), "+f"(d[44]), "+f"(d[45]), "+f"(d[46]), "+f"(d[47]), "+f"(d[48]), "+f"(d[49]), "+f"(d[50]), "+f"(d[51]), "+f"(d[52]), "+f"(d[53]), "+f"(d[54]), "+f"(d[55]), "+f"(d[56]), "+f"(d[57]), "+f"(d[58]), "+f"(d[59]), "+f"(d[60]), "+f"(d[61]), "+f"(d[62]), "+f"(d[63]), "+f"(d[64]), "+f"(d[65]), "+f"(d[66]), "+f"(d[67]), "+f"(d[68]), "+f"(d[69]), "+f"(d[70]), "+f"(d[71]), "+f"(d[72]), "+f"(d[73]), "+f"(d[74]), "+f"(d[75]), "+f"(d[76]), "+f"(d[77]), "+f"(d[78]), "+f"(d[79])
    : "l"(da), "l"(db), "r"(scaleD));
}
__device__ __forceinline__ void wgmma_rs_n144(float* d, const uint32_t* a, uint64_t db, int scaleD) {
  asm volatile("{\n.reg .pred p;\nsetp.ne.b32 p, %77, 0;\nwgmma.mma_async.sync.aligned.m64n144k16.f32.bf16.bf16 "
    "{%0,%1,%2,%3,%4,%5,%6,%7,%8,%9,%10,%11,%12,%13,%14,%15,%16,%17,%18,%19,%20,%21,%22,%23,%24,%25,%26,%27,%28,%29,%30,%31,%32,%33,%34,%35,%36,%37,%38,%39,%40,%41,%42,%43,%44,%45,%46,%47,%48,%49,%50,%51,%52,%53,%54,%55,%56,%57,%58,%59,%60,%61,%62,%63,%64,%65,%66,%67,%68,%69,%70,%71}, "
    "{%72,%73,%74,%75}, %76, p, 1, 1, 1;\n}\n"
    : "+f"(d[0]), "+f"(d[1]), "+f"(d[2]), "+f"(d[3]), "+f"(d[4]), "+f"(d[5]), "+f"(d[6]), "+f"(d[7]), "+f"(d[8]), "+f"(d[9]), "+f"(d[10]), "+f"(d[11]), "+f"(d[12]), "+f"(d[13]), "+f"(d[14]), "+f"(d[15]), "+f"(d[16]), "+f"(d[17]), "+f"(d[18]), "+f"(d[19]), "+f"(d[20]), "+f"(d[21]), "+f"(d[22]), "+f"(d[23]), "+f"(d[24]), "+f"(d[25]), "+f"(d[26]), "+f"(d[27]), "+f"(d[28]), "+f"(d[29]), "+f"(d[30]), "+f"(d[31]), "+f"(d[32]), "+f"(d[33]), "+f"(d[34]), "+f"(d[35]), "+f"(d[36]), "+f"(d[37]), "+f"(d[38]), "+f"(d[39]), "+f"(d[40]), "+f"(d[41]), "+f"(d[42]), "+f"(d[43]), "+f"(d[44]), "+f"(d[45]), "+f"(d[46]), "+f"(d[47]), "+f"(d[48]), "+f"(d[49]), "+f"(d[50]), "+f"(d[51]), "+f"(d[52]), "+f"(d[53]), "+f"(d[54]), "+f"(d[55]), "+f"(d[56]), "+f"(d[57]), "+f"(d[58]), "+f"(d[59]), "+f"(d[60]), "+f"(d[61]), "+f"(d[62]), "+f"(d[63]), "+f"(d[64]), "+f"(d[65]), "+f"(d[66]), "+f"(d[67]), "+f"(d[68]), "+f"(d[69]), "+f"(d[70]), "+f"(d[71])
    : "r"(a[0]), "r"(a[1]), "r"(a[2]), "r"(a[3]), "l"(db), "r"(scaleD));
}
__device__ __forceinline__ void wgmma_rs_n64(float* d, const uint32_t* a, uint64_t db, int scaleD) {
  asm volatile("{\n.reg .pred p;\nsetp.ne.b32 p, %37, 0;\nwgmma.mma_async.sync.aligned.m64n64k16.f32.bf16.bf16 "
    "{%0,%1,%2,%3,%4,%5,%6,%7,%8,%9,%10,%11,%12,%13,%14,%15,%16,%17,%18,%19,%20,%21,%22,%23,%24,%25,%26,%27,%28,%29,%30,%31}, "
    "{%32,%33,%34,%35}, %36, p, 1, 1, 1;\n}\n"
    : "+f"(d[0]), "+f"(d[1]), "+f"(d[2]), "+f"(d[3]), "+f"(d[4]), "+f"(d[5]), "+f"(d[6]), "+f"(d[7]), "+f"(d[8]), "+f"(d[9]), "+f"(d[10]), "+f"(d[11]), "+f"(d[12]), "+f"(d[13]), "+f"(d[14]), "+f"(d[15]), "+f"(d[16]), "+f"(d[17]), "+f"(d[18]), "+f"(d[19]), "+f"(d[20]), "+f"(d[21]), "+f"(d[22]), "+f"(d[23]), "+f"(d[24]), "+f"(d[25]), "+f"(d[26]), "+f"(d[27]), "+f"(d[28]), "+f"(d[29]), "+f"(d[30]), "+f"(d[31])
    : "r"(a[0]), "r"(a[1]), "r"(a[2]), "r"(a[3]), "l"(db), "r"(scaleD));
}

template <int V> struct Int { static constexpr int value = V; };
struct Cur {
  uint32_t s, ph;
  __device__ __forceinline__ void next() { if (++s == NST) { s = 0; ph ^= 1; } }
};

__device__ __forceinline__ uint32_t o_place(uint32_t w, uint32_t e) { return (((w ? 0xd5310u : 0xa8d57u) >> (4 * e)) & 15) * 8192 + 90112; }
#define z1_block(rb, w, j) (Q.Z + ((rb) * 16 + (w) * 8 + (j)) * ZB)
#define xn_block(hw) (Q.Z + (512 + (hw) * 2) * ZB)
#define z2_block(kb, j) (Q.Z + (256 + (kb) * 8 + (j)) * ZB)
template <int N> __device__ __forceinline__ void pause(uint32_t zero) {
  if (N <= 0) return;
  uint32_t z = clock() + threadIdx.x;
  do {
#pragma unroll (N > 8 ? 1 : 8)
    for (int i = 0; i < N; i++) asm volatile("shfl.sync.bfly.b32 %0, %0, 1, 0x1f, 0xffffffff;" : "+r"(z)::"memory");
  } while (__any_sync(~0u, z & zero));
}

__global__ void __cluster_dims__(2, 1, 1) __launch_bounds__(384, 1) mega_kernel(const Ptrs Q, const __grid_constant__ Params P) {
  extern __shared__ __align__(1024) uint8_t smem_raw[];
  const uint32_t sb = smem_u32(smem_raw);
  const uint32_t bars = sb + SM_BAR;
  const int tid = threadIdx.x;
  int lane = tid & 31;
  const int wid = __shfl_sync(~0u, tid >> 5, 0);
  const int cl = blockIdx.x >> 1;
  const int bid = (cl < 4 ? cl * 8 + 32 : cl - 4 + (max(cl - 29, 0) * 37 >> 8)) * 2 + (blockIdx.x & 1);
  const int rb = bid & 15, j = bid >> 4;
  uint4 wv[5];
  {
    const int n8 = min(tid >> 3, 26), part = n8 / 9;
    const uint8_t* src = (const uint8_t*)Q.wqkv + (8 * rb + (tid & 7)) * (3 * DM * 2) + (part * (DM - 72) + 72 * j + 8 * n8) * 2;
#pragma unroll
    for (int u = 0; u < 5; u++) wv[u] = ldnc128_if(tid < 216 && cl < 64 && (u < 4 || rb < 8), src + u * (128 * 3 * DM * 2));
  }
  if (cl >= 64) return;
  if (wid >= 7 && lane == 0) {
    if (wid < 10) {
#pragma unroll
      for (uint32_t b = 0; b < B_AD / 3; b += 8) mbar_init(bars + (wid - 7) * (B_AD / 3) + b, 1);
    } else if (wid == 10) {
#pragma unroll
      for (uint32_t b = B_AD; b < B_EVT; b += 8) mbar_init(bars + b, b < B_CSQ ? 2 : b < B_LAG ? 3 : 4);
    } else {
#pragma unroll
      for (uint32_t b = B_EVT; b < 1024; b += 8) if (b < B_OFF || b >= B_IMG) mbar_init(bars + b, b < B_IMG ? 4 : b < B_EMPTY ? 8 : 16);
    }
    asm volatile("fence.mbarrier_init.release.cluster;" ::: "memory");
  }
  __syncthreads();

  if (wid >= 8) {
    reg_dealloc<56>();
    const uint32_t el = elect_one();
    const uint64_t pol = policy_evict_first();
    uint32_t* const fj = Q.flags + FJ + j * 32;
    if (wid == 8) {
      if (el) { prefetch_map(&P.wsp); prefetch_map(&P.winb[j & 1]); prefetch_map(&P.wins); prefetch_map(&P.wout); prefetch_map(&P.act[1]); prefetch_map(&P.res[0]); prefetch_map(&P.res[1]); prefetch_map(&P.row[1]); prefetch_map(&P.red); }
      const uint32_t epoch = ldcg32(fj + FJ_EP + rb);
      Cur c{0, 1};
      const uint32_t rk = bid & 1;
      uint32_t st, full;
      auto slot = [&](uint32_t bytes) {
        st = sb + c.s * ST_BYTES; full = bars + B_FULL + c.s * 8;
        mbar_wait(full, c.ph);
        expect_tx_p(el, full, bytes);
        mbar_wait(full - B_FULL + B_EMPTY, c.ph);
      };
#pragma unroll 1
      for (int L = 0; L < 2; L++) {
#pragma unroll 1
        for (int i = 0; i < 9; i++) {
          if (L == 0 && i == 0) {
            flag_wait(fj + FJ_WQ, (epoch + 1) * 16);
            fence_async_g();
            TRC(el, 2, 45);
          }
          slot(27648);
          bulk_mc_h(el, st + ST_B + rk * 13824, Q.WQ + j * WQ_SL + i * 27648 + rk * 13824, 13824, full, EF(0), pol);
          c.next();
        }
        if (L == 0) {
          flag_wait(fj + FJ_WO, (epoch + 1) * 16);
          fence_async_g();
          TRC(el, 2, 46);
        }
#pragma unroll 1
        while (c.s) {
          mbar_wait(bars + B_EMPTY + c.s * 8, c.ph);
          if (el) { mbar_arrive(bars + B_FULL + c.s * 8); asm volatile("mbarrier.arrive.shared::cta.b64 _, [%0], 16;" ::"r"(bars + B_EMPTY + c.s * 8) : "memory"); }
          c.next();
        }
        expect_tx_p(el, bars + B_WF, WO_SL);
        mbar_wait(bars + B_EMPTY, c.ph);
        mbar_wait(bars + B_EMPTY + 8, c.ph);
        bulk_mc_h(el, sb + rk * (WO_SL / 2), Q.WO + j * WO_SL + rk * (WO_SL / 2), WO_SL / 2, bars + B_WF, EF(1), pol);
#pragma unroll 1
        for (int r = 0; r < 10; r++) {
          const bool big = r >= 2 && r < 8;
          const int a0 = (r < 5 ? 36 : 0) + ((9 * j) >> 1) + (big ? 2 - 2 * (j & 1) : 3 * (j & 1) + rk), ks = big ? 32 : 48;
          int k = big ? (r < 5 ? r - 2 : r - 5) * 192 + rk * 16 : (r & 1) * 288;
          const CUtensorMap* m = big ? &P.winb[j & 1] : &P.wins;
          const uint32_t dst = sb + SM_B3 + rk * 6144;
#pragma unroll
          for (int p = 0; p < 6; p++, k += ks) {
            if (!(p & 3) && r == 0) mbar_wait(bars + B_XD + p * 2, L);
            if (p) mbar_wait_c(bars + B_E3 + p * 8, ~r & 1); else mbar_wait(bars + B_E3, ~r & 1);
            expect_tx_p(el, bars + B_F3 + p * 8, 12288);
            tma3d_mc_h(el, dst + p * 12288, m, 0, k, a0, bars + B_F3 + p * 8, EF(2), pol);
          }
        }
        TRC(el, 2, L * 16 + 6);
        mbar_wait(bars + B_ZOK, L);
        fence_async_g();
        TRC(el, 2, L * 16 + 7);
        const uint8_t* src = z2_block(0, j) + rk * 18432;
#pragma unroll 1
        for (int r = 0; r < 8; r++) {
          const int k = (r & 3) * 512 + (r >> 2) * 64;
#pragma unroll
          for (int p = 0; p < 4; p++, src += 8 * ZB) {
            if ((p == 1 || p == 2) && r == 0) mbar_wait(bars + B_E3 - 8 + p * 24, 1);
            mbar_wait_c(bars + B_AD + p * 8, ~r & 1);
            if (p) mbar_wait_c(bars + B_EMPTY + p * 8, c.ph); else mbar_wait(bars + B_EMPTY, c.ph);
            expect_tx_p(el, bars + B_FULL + p * 8, ST_BYTES);
            bulk_mc_h(el, sb + p * ST_BYTES + ST_B + rk * 18432, src, 18432, bars + B_FULL + p * 8, EF(4), pol);
            tma3d_h(el, sb + p * ST_BYTES, &P.wsp, k + p * 128, rb * 64, 0, bars + B_FULL + p * 8, EF(3), pol);
          }
          c.ph ^= 1;
        }
        mbar_wait(bars + B_Z1, L);
        fence_async_g();
#pragma unroll 1
        for (int i = 0; i < 11; i++) {
          const int cb = i - 2 + j;
          if (i < 4) mbar_wait(bars + B_AD + c.s * 8, 1);
          slot(ZB);
          if (i < 2) bulk_load_h(el, st + ST_B, z1_block(rb, i, j), ZB, full, true, pol);
          else tma2d_mc_h(el, st + ST_B + rk * 18432, &P.wout, (cb >= 9 ? cb - 9 : cb) * 64, 288 * j + rk * 144, full, EF(5), pol);
          c.next();
        }
      }
    } else if (wid < 11) {
      uint32_t id = bid * 2 + wid - 9;
#define AGENT_IDS asm volatile("" : "+r"(lane), "+r"(id)); const uint32_t w = id & 1, hw = id & 31, rb = hw >> 1, j = id >> 5, ev = bars + B_EVT + w * EV_N * 8; \
      uint32_t* const fr = Q.flags + hw * 32; uint32_t* const fj = Q.flags + FJ + j * 32; (void)fr; (void)fj; (void)ev; (void)rb
      uint32_t t8 = 0;
      Cur c{0, 1};
#pragma unroll 1
      for (int L = 0; L < 2; L++) {
        if (L) {
          AGENT_IDS;
          const uint32_t full = bars + B_FULLA + w * 32 + c.s * 8, dst = sb + c.s * ST_BYTES + w * 8192;
          expect_tx_p(el, full, 8192);
          mbar_wait_c(ev + EV_PT * 8, 1);
          TRC(el, 3, w * 32 + 16);
          flag_release_p(el, fr + FR_X2);
          TRC(el, 3, w * 32 + 17);
          mbar_wait_c(bars + B_EMPTY + c.s * 8, c.ph);
          flag_wait(fr + FR_X2, t8);
          fence_async_g();
          tma3d_h(el, dst, &P.act[1], 0, rb * 64, w, full, false, pol);
          c.next();
          TRC(el, 3, w * 32 + 18);
        }
#pragma unroll 1
        for (int i = L; i < 9; i++) {
          AGENT_IDS;
          const uint32_t full = bars + B_FULLA + w * 32 + c.s * 8, dst = sb + c.s * ST_BYTES + w * 8192;
          if (L == 0 && i == AEP) t8 = (ldcg32(fr + FR_EP + j) + 1) * 8;
          mbar_wait_c(bars + B_EMPTY + c.s * 8, c.ph);
          expect_tx_p(el, full, 8192);
          tma3d_h(el, dst, &P.act[L], i * 64, rb * 64, w, full, false, pol);
          c.next();
          if (i == PZI || i == PZI + 1) {
            uint8_t* d = (i == PZI ? xn_block(hw) : z1_block(rb, 0, 0) + w * 4608) + j * 9216 + lane * 16;
#pragma unroll 1
            for (int u = i == PZI ? 0 : 3; u < 6; u++, d += 1536) { stg128(d, ~0u, ~0u, ~0u, ~0u); stg128(d + 512, ~0u, ~0u, ~0u, ~0u); stg128(d + 1024, ~0u, ~0u, ~0u, ~0u); }
          }
          if (i == PZI) { stg128(Q.ST1 + (hw * 8 + j) * 32 + lane, ~0u, ~0u, ~0u, ~0u); stg128(Q.ZST + (hw * 8 + j) * 32 + lane, ~0u, ~0u, ~0u, ~0u); }
          if (i == RFI) {
            expect_tx_p(el, bars + B_WT + w * 8, 9216);
            tma3d_h(el, sb + SM_STG + w * 9216, &P.row[L], 0, 3 * w, rb * 64 + 8 * j, bars + B_WT + w * 8, false, pol);
          }
          if (i == 4 && L > w) {
            expect_tx_p(el, bars + B_CSQ, 864);
            bulk_load_p(el, sb + 3 * ST_BYTES + SM_CSQ, Q.CSP + (NCTA + (id >> 1)) * 216, 864, bars + B_CSQ);
          }
        }
        if (c.s) { c.s = 0; c.ph ^= 1; }
        {
          AGENT_IDS;
          const uint32_t tag = (t8 >> 2) - 1 + L;
          uint4* const xs = Q.XST + hw * 128;
          const uint32_t tab = sb + L * (3 * ST_BYTES) + SM_XST + w * 768 + lane * 8;
          TRC(el, 3, w * 32 + L * 16 + 13);
#pragma unroll 1
          for (int it = 0; it < (1 << 22); it++) {
            const uint4 a = ll_ld128(xs + 2 * lane), b = ll_ld128(xs + 64 + 2 * lane), h = ll_ld128(xs - (rb ? 192 : 0) + 2 * (lane | 24));
            if (__all_sync(~0u, a.z == tag && b.z == tag && h.z == tag)) { sts64(tab, h.x, h.y); sts64(tab + 256, a.x, a.y); sts64(tab + 512, b.x, b.y); break; }
          }
          __syncwarp();
          if (el) mbar_arrive(bars + B_CSQ);
          TRC(el, 3, w * 32 + L * 16 + 14);
          uint32_t* f = Q.flags + rb * 64 + FR_PZ + L;
          flag_release_p(el, f);
          expect_tx_p(el, bars + B_RES + w * 8, 9216);
          tma3d_h(el, sb + SM_STG + w * 9216, &P.res[L], j * 72, hw * 32, 0, bars + B_RES + w * 8, !L, pol);
          pause<FD3>(Q.zero);
          flag_wait(f, t8 * 2);
          fence_async_g();
          TRC(el, 3, w * 32 + L * 16 + 15);
        }
        {
          AGENT_IDS;
          uint32_t* f = Q.flags + rb * 64 + FR_O + L;
#pragma unroll 1
          for (int e = 0; e < 5; e++) {
            const uint32_t nb = e ? 16384 : 8192, full = bars + B_OF + w * 40 + e * 8, dst = sb + o_place(w, e);
            const uint8_t* src = z1_block(rb, w, 0) + (e ? e * 16384 - 8192 : 0);
            expect_tx_p(el, full, nb);
            if (e == 0) {
              mbar_wait_c(ev + EV_O * 8, L);
              TRC(el, 3, w * 32 + L * 16 + 3);
              flag_add_p(el, f);
              flag_wait(f + w * (FR_OL - FR_O), t8 * (2 - w));
              if (w) fence_async_g();
            }
            if (w && (e == 0 || e == 3)) mbar_wait_c(bars + (e ? B_X3 : B_OF + YPACE * 8), L);
            bulk_load_h(el, dst, src, nb, full, EF(6), pol);
            TRC(el && e == 0, 3, w * 32 + L * 16 + 5);
          }
        }
        {
          AGENT_IDS;
          const uint8_t* src = xn_block(hw);
          uint32_t full = bars + B_AF3 + w * 96, dst = sb + w * 6144;
          if (L) flag_wait(fj + FJ_P4, t8 * 4);
          mbar_wait_c(bars + B_XD + 8, L);
          mbar_wait_c(ev + EV_X1 * 8, L);
          TRC(el, 3, w * 32 + L * 16 + 6);
          pause<SDEL>(Q.zero);
#pragma unroll 1
          for (int k = 0; k < 12; k++, src += 6144, dst += 12288, full += 8) {
            expect_tx_p(el, full, 6144);
            if (k >= APACE) mbar_wait_c(full - APACE * 8, L);
            bulk_load_h(el, dst, src, 6144, full, EF(7), pol);
            TRC(el && k == 0, 3, w * 32 + L * 16 + 8);
          }
        }
        if (wid == 10) {
          AGENT_IDS;
          mbar_wait_c(ev - (EV_N - EV_ZN) * 8, L);
          mbar_wait_c(ev + EV_ZN * 8, L);
          asm volatile("fence.release.gpu;" ::: "memory");
          flag_add_p(el, fj + FJ_ZN + L);
          flag_add_p(el, fr - 32 + FR_XR + L);
          pause<FD4>(Q.zero);
          flag_wait(fj + FJ_ZN + L, t8 * 2);
          flag_wait(fr - 32 + FR_XR + L, t8);
          if (el) mbar_arrive(bars + B_ZOK);
        } else if (WPF) {
          AGENT_IDS;
          mbar_wait_c(ev + EV_ZN * 8, L);
          if (el) asm volatile("cp.async.bulk.prefetch.tensor.3d.L2.global [%0, {%1, %2, %3}];" ::"l"(&P.wsp), "r"(j * 128), "r"(rb * 64), "r"(0) : "memory");
        }
        float cv;
        {
        AGENT_IDS;
        cv = (lane & 3) ? 0.f : -blo(ldnc16(Q.b_sp + 128 * rb + 16 * j + 2 * (lane >> 2) + w));
        mbar_wait_c(ev + EV_Z1 * 8, L);
        const uint32_t ro = (w * 64 + 8 * j + (lane >> 2)) * 128, x0 = ((lane & 3) * 2) ^ (lane >> 2);
#pragma unroll 1
        for (int i = 0; i < 32; i++) {
          const bool tail = (i >> 1) == 12;
          const int kb = tail ? i + 6 : i < 24 ? i : i - 2;
          if (!(i & 7)) mbar_wait_c(bars + B_RT + i, L);
          if (i == 24) mbar_wait_c(bars + B_WT + w * 8, 1);
          if (!tail) mbar_wait(bars + B_FULL + c.s * 8, c.ph ^ 1);
          if (i == 3) {
            uint32_t id2 = id;
            asm volatile("" : "+r"(id2));
            expect_tx_p(el, bars + B_WT + w * 8, 3072);
#pragma unroll 1
            for (int r = 0; r < 8; r++)
              bulk_load_p(el, sb + SM_WT + w * 3200 + r * 400, (const uint8_t*)Q.w_sp + (64 * (id2 & 30) + 16 * (id2 >> 5) + 2 * r + w) * (SEQ * 2) + 29 * 128, 384, bars + B_WT + w * 8);
          }
#pragma unroll
          for (int e = 0; e < 2; e++) {
            const uint4 a = lds128(!tail ? sb + c.s * ST_BYTES + ro + ((x0 ^ e) << 4) : sb + SM_WT + w * 3200 + (lane >> 2) * 400 + (i - 24) * 256 + (lane & 3) * 32 + e * 16);
            const uint4 m = lds128(sb + SM_RT + 4096 + kb * 128 + (lane & 3) * 32 + e * 16);
            cv = fmaf(blo(a.x), blo(m.x), fmaf(bhi(a.x), bhi(m.x), fmaf(blo(a.y), blo(m.y), fmaf(bhi(a.y), bhi(m.y), cv))));
            cv = fmaf(blo(a.z), blo(m.z), fmaf(bhi(a.z), bhi(m.z), fmaf(blo(a.w), blo(m.w), fmaf(bhi(a.w), bhi(m.w), cv))));
          }
          if (!tail) {
            __syncwarp();
            if (el) mbar_arrive(bars + B_AD + c.s * 8);
            c.next();
          }
        }
        }
        AGENT_IDS;
        TRC(el, 3, w * 32 + L * 16 + 11);
        asm volatile("" : "+r"(t8));
        const uint32_t tag = (t8 >> 2) - 1 + L;
        cv = qsum(cv);
        uint2* const cs = (uint2*)(Q.XST + hw * 128 + 1);
        if ((lane & 3) == 0) ll_st64(cs + 32 * j + (lane >> 2) * 4, __float_as_uint(cv), tag);
        pause<FD5>(Q.zero);
#pragma unroll 1
        for (int it = 0; it < (1 << 22); it++) {
          const uint2 a = ll_ld64(cs + 4 * lane), b = ll_ld64(cs + 128 + 4 * lane);
          if (__all_sync(~0u, a.y == tag && b.y == tag)) { sts32(sb + SM_CV + w * 256 + lane * 4, a.x); sts32(sb + SM_CV + w * 256 + 128 + lane * 4, b.x); break; }
        }
        __syncwarp();
        if (el) mbar_arrive(bars + B_CV + w * 8);
        TRC(el, 3, w * 32 + L * 16 + 12);
#pragma unroll 1
        for (int kb = 30; kb < 32; kb++) {
          mbar_wait_c(bars + B_FULL + c.s * 8, c.ph ^ 1);
          if (el) mbar_arrive(bars + B_AD + c.s * 8);
          c.next();
        }
        c.ph ^= ((c.s + 11) >> 2) & 1; c.s = (c.s + 11) & 3;
        if (L == 0) {
          mbar_wait_c(ev + EV_PT * 8, 0);
          flag_add_p(el, fj + FJ_P4);
        }
      }
    } else {
      const uint32_t epoch = ldcg32(fj + FJ_EP + rb);
      mbar_wait(bars + B_IMG, 0);
      TRC(el, 2, 41);
      flag_release_p(el, fj + FJ_WQ);
      TRC(el, 2, 42);
#pragma unroll 1
      for (int L = 0; L < 2; L++) {
        float* const csf = Q.CSP + (NCTA + bid) * 216;
        if (L == 0) {
          flag_wait(fj + FJ_WQ, (epoch + 1) * 16);
          fence_async_g();
          expect_tx_p(el, bars + B_XRW, 13824);
          bulk_load_p(el, sb + ST_BYTES + SM_WOI, Q.CSP + j * 16 * 216, 6912, bars + B_XRW);
          bulk_load_p(el, sb + 2 * ST_BYTES + SM_WOI, Q.CSP + (j * 16 + 8) * 216, 6912, bars + B_XRW);
          mbar_wait(bars + B_XRW, 0);
#pragma unroll 1
          for (int f = lane; f < 54; f += 32) {
            float s[4] = {0.f, 0.f, 0.f, 0.f};
#pragma unroll 2
            for (int r = 0; r < 16; r++) {
              const uint4 v = lds128(sb + ST_BYTES + SM_WOI + (r >> 3) * ST_BYTES + (r & 7) * 864 + f * 16);
              s[0] += __uint_as_float(v.x); s[1] += __uint_as_float(v.y); s[2] += __uint_as_float(v.z); s[3] += __uint_as_float(v.w);
            }
            sts128(sb + SM_CSQ + f * 16, __float_as_uint(s[0]), __float_as_uint(s[1]), __float_as_uint(s[2]), __float_as_uint(s[3]));
            stg128(csf + f * 4, __float_as_uint(s[0]), __float_as_uint(s[1]), __float_as_uint(s[2]), __float_as_uint(s[3]));
          }
          __syncwarp();
          if (el) mbar_arrive(bars + B_CSQ);
          TRC(el, 2, 43);
          if (el && PFT) prefetch_l2((const uint8_t*)Q.w_in + bid * 41472, PFT * 20736);
          mbar_wait(bars + B_WOI, 0);
          bulk_store_p(el, Q.WO + j * WO_SL + rb * (41 * 128), sb + SM_WOI, (rb < 15 ? 41 : 33) * 128);
          publish_p(el, fj + FJ_WO);
          TRC(el, 2, 44);
          if (el && PFT < 2) prefetch_l2((const uint8_t*)Q.w_in + bid * 41472 + PFT * 20736, 41472 - PFT * 20736);
          float o0 = 0.f, o1 = 0.f;
#pragma unroll 1
          for (int u = 0; u < 2; u++) {
            const uint8_t* src = (u ? (const uint8_t*)Q.w_sp + 500 * (SEQ * 2) + 2048 : (const uint8_t*)Q.w_in + 100 * (2 * FH * 2) + FH * 2) + lane * 16;
            const uint4 a = ldnc128(src), b = ldnc128(src + 300 * (2 * FH * 2) + 2048);
            const uint32_t x[8] = {a.x, a.y, a.z, a.w, b.x, b.y, b.z, b.w};
            float sq = 0.f;
#pragma unroll
            for (int e = 0; e < 8; e++) sq = fmaf(blo(x[e]), blo(x[e]), fmaf(bhi(x[e]), bhi(x[e]), sq));
            o0 = o1;
            asm("sqrt.approx.f32 %0, %1;" : "=f"(o1) : "f"(wsum(sq) * (u ? C0S * C0S * SEQ / 512.f : 2.f * GA * GA * DM / 512.f)));
          }
          const uint32_t off = (__float_as_uint(o0) & 0x7f800000u) >> 16 | 0x8000u | OFM;
          if (el) sts128(sb + SM_OFF, off * 0x10001u, min(__float_as_uint(o1) & 0x7f800000u, 0x7e000000u) | 0x00400000u, __float_as_uint(GB), 0u);
        }
        mbar_wait(bars + B_EVT + EV_O * 8, L);
        mbar_wait(bars + B_EVT + (EV_N + EV_O) * 8, L);
        flag_release_p(el, Q.flags + rb * 64 + FR_OL + L);
#pragma unroll 1
        for (int w = 0; w < 2; w++) {
          mbar_wait(bars + B_EVT + (w * EV_N + EV_XS) * 8, L);
          if (!w) mbar_wait(bars + B_AF3 + 96 + XP0 * 8, L);
          if (el) asm volatile("cp.async.bulk.tensor.3d.global.shared::cta.tile.bulk_group [%0, {%2, %3, %4}], [%1];\ncp.async.bulk.commit_group;\ncp.async.bulk.wait_group.read 0;" ::"l"(&P.res[1]), "r"(sb + SM_STG + 9216), "r"(j * 72), "r"(rb * 64 + w * 32), "r"(0) : "memory");
          __syncwarp();
          if (lane < 2 && !w) mbar_arrive(bars + B_S5);
        }
        if (el) { asm volatile("cp.async.bulk.wait_group 0;" ::: "memory"); mbar_arrive(bars + B_GATE3); }
        const uint32_t tag = epoch * 2 + L + 1;
        asm volatile("" : "+r"(lane));
#pragma unroll 1
        for (int b = 0; b < 8; b++) {
          if (!(b & 3)) {
            const int mb = b >> 2;
            mbar_wait(bars + B_ZS + mb * 8, L);
            pause<ZD1>(Q.zero);
            TRC(el && !mb, 2, L * 16 + 8);
            uint4 v;
#pragma unroll 1
            for (int it = 0; it < (1 << 22); it++) {
              v = ll_ld128(Q.ZST + ((rb * 2 + mb) * 8 + (lane >> 2)) * 32 + 4 * j + (lane & 3));
              if (__all_sync(~0u, max(max(v.x, v.y), max(v.z, v.w)) != ~0u)) break;
            }
            const bool o = lane & 16;
            float ss = __uint_as_float(o ? v.y : v.x) + __shfl_xor_sync(~0u, __uint_as_float(o ? v.x : v.y), 16), sq = __uint_as_float(o ? v.w : v.z) + __shfl_xor_sync(~0u, __uint_as_float(o ? v.z : v.w), 16);
            ss += __shfl_xor_sync(~0u, ss, 4); sq += __shfl_xor_sync(~0u, sq, 4); ss += __shfl_xor_sync(~0u, ss, 8); sq += __shfl_xor_sync(~0u, sq, 8);
            const float mean = ss * (1.f / FH), rs = blo(pack2(rsq_fast(fmaxf(fmaf(sq, 1.f / FH, -mean * mean), 0.f) + 4.f * GA * GA * LN_EPS), 0.f));
            if (!(lane & 12)) ll_st64(Q.RT + (mb * 16 + rb) * 64 + 8 * j + 2 * (lane & 3) + (lane >> 4), pack2(rs, rs * (mean - blo(lds32(sb + SM_OFF)))), tag);
            TRC(el && !mb, 2, L * 16 + 10);
            pause<ZD2>(Q.zero);
          }
          uint4 v[4];
#pragma unroll 1
          for (int it = 0; it < (1 << 22); it++) {
            bool ok = true;
#pragma unroll
            for (int u = 0; u < 4; u++) { v[u] = ll_ld128((const uint4*)Q.RT + b * 128 + u * 32 + lane); ok = ok && v[u].y == tag && v[u].w == tag; }
            if (__all_sync(~0u, ok)) break;
          }
#pragma unroll
          for (int u = 0; u < 4; u++) {
            const uint32_t rt = sb + SM_RT + b * 512 + u * 128, ro = (lane >> 3) * 32 + (lane & 3) * 8 + ((lane >> 2) & 1) * 2;
            sts32(rt + 4096 + lane * 4, __byte_perm(v[u].x, v[u].z, 0x7632));
            asm volatile("st.shared.u16 [%0], %1;\nst.shared.u16 [%0 + 4], %2;" ::"r"(rt + ro), "h"((uint16_t)v[u].x), "h"((uint16_t)v[u].z) : "memory");
          }
          __syncwarp();
          if (el && (b & 1)) mbar_arrive(bars + B_RT + (b - 1) * 4);
          TRC(el && b < 2, 2, L * 16 + 11 + b);
        }
        TRC(el, 2, L * 16 + 9);
        mbar_wait(bars + B_EVT + EV_Z1 * 8, L);
        mbar_wait(bars + B_EVT + (EV_N + EV_Z1) * 8, L);
        fence_gpu();
        if (el) mbar_arrive(bars + B_Z1);
      }
    }
  } else {
    int w = wid >> 2, q = wid & 3, rb = bid & 15, j = bid >> 4;
    int g = lane >> 2, t = lane & 3;
#define PHASE asm volatile("" : "+r"(w), "+r"(q), "+r"(rb), "+r"(j))
#define stg (sb + SM_STG + w * 9216)
    const bool tr = (tid & 127) == 0;
    (void)tr;
    Cur c{0, 0};
    const uint32_t ebar = mapa(bars + B_EMPTY, (bid & 1) ^ (lane & 1));
    auto release = [&](uint32_t s) { if (lane < 2) mbar_arrive_cluster(ebar + s * 8); };
    uint32_t ia = 0;
    auto wait_ab = [&]() { mbar_wait_c(bars + B_FULL + c.s * 8, c.ph); mbar_wait_c(bars + B_FULLA + w * 32 + c.s * 8, (ia >> c.s) & 1); ia ^= 1u << c.s; };
    uint32_t lagph = 0;
    auto yield = [&](int left, int lag) { if (w == 1 && left == lag) mbar_wait_c(bars + B_LAG, lagph); };
    auto yield_done = [&]() { if (w == 0 && lane == 0) mbar_arrive(bars + B_LAG); };
    uint32_t rp = 0;
    auto check = [&](auto n, uint32_t dst, const uint8_t* src) {
      const uint32_t a = dst + lane * 32 + (lane >> 2) * 4;
#pragma unroll 1
      for (int it = 0; it < (1 << 16); it++) {
        uint32_t x = lds32(a);
#pragma unroll
        for (int e = 1; e < n.value; e++) x = max(x, lds32(a + e * 1024));
        if (!__any_sync(~0u, x == ~0u)) break;
        fence_async_s();
        __syncwarp();
        expect_tx_p(lane == 0, bars + B_RB + q * 8, n.value * 1024);
        bulk_load_p(lane == 0, dst, src, n.value * 1024, bars + B_RB + q * 8);
        mbar_wait_c(bars + B_RB + q * 8, rp & 1);
        rp++;
      }
    };
    auto signal = [&](int e) { __syncwarp(); if (lane == 0) mbar_arrive(bars + B_EVT + w * EV_N * 8 + e * 8); };
    TRC(tr, w, 0);

    {
      uint8_t* dst = Q.WQ + j * WQ_SL + rb * 3456 + tid * 16;
#pragma unroll
      for (int u = 0; u < 5; u++) {
        stg128_if((u < 4 || rb < 8) && tid < 216, dst + u * (16 * 3456), wv[u].x, wv[u].y, wv[u].z, wv[u].w);
        if (u == 0) TRC(tr, w, 60);
      }
      if (Q.zero == 0) {
        float s[8];
#pragma unroll
        for (int u = 0; u < 5; u++) {
          const uint32_t x[4] = {wv[u].x, wv[u].y, wv[u].z, wv[u].w};
#pragma unroll
          for (int e = 0; e < 4; e++) { s[2 * e] = u ? s[2 * e] + blo(x[e]) : blo(x[e]); s[2 * e + 1] = u ? s[2 * e + 1] + bhi(x[e]) : bhi(x[e]); }
        }
#pragma unroll
        for (int m = 4; m; m >>= 1) {
#pragma unroll
          for (int e = 0; e < m; e++) s[e] = ((tid & m) ? s[e + m] : s[e]) + __shfl_xor_sync(~0u, (tid & m) ? s[e] : s[e + m], m);
        }
        stg32_if(tid < 216, Q.CSP + bid * 216 + tid, __float_as_uint(s[0]));
      }
      __syncwarp();
      if (lane == 0) mbar_arrive(bars + B_IMG);
    }
    reg_alloc<224>();
    auto fetch_wo = [&]() {
#pragma unroll 1
      for (int u = tid; u < 328; u += 256) {
        const int m = min(41 * rb + (u >> 3), 647), k8 = m / 9;
        cp_async16(sb + SM_WOI + u * 16, (const uint8_t*)Q.wo + (8 * k8 + (u & 7)) * (DM * 2) + (72 * j + 8 * (m - k8 * 9)) * 2);
      }
    };
    const uint32_t epoch = ldcg32(Q.flags + (rb * 2 + w) * 32 + FR_EP + j);
    TRC(tr, w, 1);

#pragma unroll 1
    for (int L = 0; L < 2; L++) {
      const int tb = 2 + L * 24;
      asm volatile("" : "+r"(lane), "+r"(g), "+r"(t));
      if (PHM & 1) PHASE;
      (void)tb;
      const uint32_t tag = epoch * 2 + L + 1;
      {
        uint32_t Pk[27][2];
        float rk[2][2], sc[2][2];
        const bool up0 = 2 * t > g, up1 = 2 * t + 1 > g;
        constexpr int HA_[6] = {0, 2, 4, 7, 12, 15}, HC_[6] = {6, 9, 10, 11, 14, 17};
        const bool remote = q == 0 && rb > 0;
        uint4* hp = Q.HALO + ((((rb - (q == 0)) * 2 + w) * 8 + j) * 6) * 32 + lane;
        const uint32_t att = 2 * ST_BYTES + w * 8192 + lane * 16;
        const uint8_t* hs = remote ? (const uint8_t*)hp : smem_raw + att + (q == 3 ? ST_BYTES : q == 2 ? 3072 : 0);
        uint8_t* od = z1_block(rb, q >> 1, 0) + (9 * j) * 1024 + (4 * (q & 1) + w) * 128 + lane * 4;
        ACLK_INIT;
        {
          float acc[108];
#pragma unroll
          for (int i = 0; i < 108; i++) acc[i] = 0.f;
          float sx[2] = {0.f, 0.f}, sq[2] = {0.f, 0.f};
          uint32_t prev = 0;
#pragma unroll 1
          for (int kb = 0; kb < 9; kb++) {
            wait_ab();
            yield(9 - kb, LAG1);
            TRC(tr && kb == 0, w, tb + 0);
            PCLK(kb * 4);
            const uint32_t st = sb + c.s * ST_BYTES, da = dlo(st + w * 8192, 16), db = dlo(st + ST_B, 3456);
            wgmma_fence();
#pragma unroll
            for (int kk = 0; kk < 4; kk++) {
              wgmma_ss_n216(acc, dsc<1024, 1>(da, kk * 32), dsc<128, 0>(db, kk * 6912), 1);
              if (kk == 0) { wgmma_commit(); wgmma_wait<1>(); if (kb > 0) release(prev); }
              if (kk == 3) wgmma_commit();
              if (kk == XK1) {
            if (kb >= KS && kb < KS + 3) {
              mbar_wait_c(bars + B_WT + w * 8, 0);
#pragma unroll
              for (int u = 0; u < 3; u++) {
                const uint2 x = lds64(stg + (2 * q + (lane >> 4)) * 1152 + (lane & 15) * 8 + (kb - KS) * 384 + u * 128);
                sx[0] += blo(x.x) + bhi(x.x); sx[1] += blo(x.y) + bhi(x.y);
                sq[0] = fmaf(blo(x.x), blo(x.x), fmaf(bhi(x.x), bhi(x.x), sq[0])); sq[1] = fmaf(blo(x.y), blo(x.y), fmaf(bhi(x.y), bhi(x.y), sq[1]));
              }
            }
            if (kb == KS + 3) {
              const bool o = lane & 1;
              float v = (o ? sq[0] + sq[1] : sx[0] + sx[1]) + __shfl_xor_sync(~0u, o ? sx[0] + sx[1] : sq[0] + sq[1], 1);
              v += __shfl_xor_sync(~0u, v, 2); v += __shfl_xor_sync(~0u, v, 4); v += __shfl_xor_sync(~0u, v, 8);
              const float m = v * (-1.f / DM), r = rsq_fast(fmaxf(fmaf(__shfl_xor_sync(~0u, v, 1), 1.f / DM, -m * m), 0.f) + LN_EPS);
              ll_st128_if(!(lane & 15), Q.XST + (rb * 2 + w) * 128 + 16 * j + 4 * q + (lane >> 3), m, r, tag);
            }
              }
              if (kk == XK2 && L == 0) {
            if (kb == 0) fetch_wo();
            if (kb == 3) {
              asm volatile("cp.async.wait_all;" ::: "memory");
              fence_async_s();
              __syncwarp();
              if (lane == 0) mbar_arrive(bars + B_WOI);
            }
              }
            }
            if (kb == 8) yield_done();
            PCLK(kb * 4 + 1);
            PCLK(kb * 4 + 2);
            PCLK(kb * 4 + 3);
            prev = c.s; c.next();
          }
          const uint32_t cs = sb + prev * ST_BYTES + SM_CSQ + t * 8;
          mbar_wait_c(bars + B_CSQ, L);
          const uint32_t xs = sb + prev * ST_BYTES + SM_XST + w * 768 + 256 + q * 128;
          const float2 n0 = lds64f(xs + g * 8), n1 = lds64f(xs + g * 8 + 64);
          const float m0 = n0.x, m1 = n1.x;
#pragma unroll
          for (int u = 0; u < 4; u++) {
            rk[u >> 1][u & 1] = __uint_as_float(lds32(xs + t * 16 + ((u & 1 ? up1 : up0) ? -64 : 0) + (u & 1) * 8 + (u >> 1) * 64 + 4));
            sc[u >> 1][u & 1] = rk[u >> 1][u & 1] * ((u >> 1 ? n1.y : n0.y) * (0.23570226039551584f * 1.4426950408889634f));
          }
          float2 cv[27];
#pragma unroll
          for (int G = 0; G < 27; G++) cv[G] = lds64f(cs + G * 32);
          PCLK(36);
          wgmma_wait<0>();
          PCLK(37);
          release(prev);
          lagph ^= 1;
          TRC(tr, w, tb + 1);
          ACLK(0);
#pragma unroll
          for (int G = 9; G < 27; G++) Pk[G][1] = pack2(fmaf(m1, cv[G].x, acc[4 * G + 2]), fmaf(m1, cv[G].y, acc[4 * G + 3]));
          if (q < 3) {
#pragma unroll
            for (int i = 0; i < 6; i++) sts128(sb + att + (q >> 1) * ST_BYTES + (q & 1) * 3072 + i * 512, Pk[9 + HA_[i]][1], Pk[10 + HA_[i]][1], tag, Pk[9 + HC_[i]][1]);
          } else if (rb < 15) {
#pragma unroll
            for (int i = 0; i < 6; i++) ll_st128(hp + i * 32, __uint_as_float(Pk[9 + HA_[i]][1]), __uint_as_float(Pk[10 + HA_[i]][1]), tag, __uint_as_float(Pk[9 + HC_[i]][1]));
          }
#pragma unroll
          for (int G = 0; G < 27; G++) {
            Pk[G][0] = pack2(fmaf(m0, cv[G].x, acc[4 * G]), fmaf(m0, cv[G].y, acc[4 * G + 1]));
            if (G < 9) Pk[G][1] = pack2(fmaf(m1, cv[G].x, acc[4 * G + 2]), fmaf(m1, cv[G].y, acc[4 * G + 3]));
          }
        }
        ACLK(1);
        constexpr int GA_[4] = {0, 2, 4, 7}, GB_[4] = {1, 3, 5, 8}, GC_[4] = {2, 4, 6, 6};
        float S1[4][4], S2[4][4];
        uint32_t qa[4][2], qc[4][2];
#pragma unroll
        for (int h = 0; h < 4; h++) {
#pragma unroll
          for (int r = 0; r < 2; r++) {
            qa[h][r] = (h == 0 || h == 3 || t >= h) ? Pk[GA_[h]][r] : 0u;
            qc[h][r] = (h == 3 ? t == 3 : t <= h) ? Pk[GC_[h]][r] : 0u;
          }
#pragma unroll
          for (int i = 0; i < 4; i++) S1[h][i] = S2[h][i] = 0.f;
          mma16(S1[h], qa[h][0], qa[h][1], Pk[GB_[h]][0], Pk[GB_[h]][1], Pk[9 + GA_[h]][0], Pk[9 + GB_[h]][0]);
          mma16(S2[h], qa[h][0], qa[h][1], Pk[GB_[h]][0], Pk[GB_[h]][1], Pk[9 + GA_[h]][1], Pk[9 + GB_[h]][1]);
        }
#pragma unroll
        for (int h = 0; h < 4; h++) {
          mma8(S1[h], qc[h][0], qc[h][1], Pk[9 + GC_[h]][0]);
          mma8(S2[h], qc[h][0], qc[h][1], Pk[9 + GC_[h]][1]);
        }
        uint32_t V1[9], V2[9];
#pragma unroll
        for (int i = 0; i < 9; i++) { V1[i] = movm(Pk[18 + i][0]); V2[i] = movm(Pk[18 + i][1]); }
        uint4 hv[6];
#pragma unroll
        for (int i = 0; i < 6; i++) hv[i] = ll_ld128g(hs + i * 512);
        const uint32_t mup = (up0 ? 0xffffu : 0u) | (up1 ? 0xffff0000u : 0u);
        auto finish = [&](const float (&x0)[4], const float (&x1)[4], const uint32_t (&Vb)[9], uint32_t ma, int hi) {
          uint32_t p[4], n[4];
          float rs[4];
#pragma unroll
          for (int h = 0; h < 4; h++) {
            const float m = qmax(fmaxf(x0[h], x1[h])), e0 = ex2(x0[h] - m), e1 = ex2(x1[h] - m);
            n[h] = pack2(e0, e1);
            p[h] = pack2(e0 * rk[hi][0], e1 * rk[hi][1]);
          }
#pragma unroll
          for (int h = 0; h < 4; h += 2) {
            float D[4] = {0.f, 0.f, 0.f, 0.f};
            mma8(D, n[h], n[h + 1], 0x3f803f80u);
            rs[h] = rcp_fast(D[0]); rs[h + 1] = rcp_fast(D[2]);
          }
#pragma unroll
          for (int i = 0; i < 9; i++) {
            const int h = i < 4 ? 0 : i == 4 ? 1 : 2;
            const bool nx = (i == 2 || i == 4 || i == 6) ? 2 * t >= i : i == 3 || i > 6;
            float O[4] = {0.f, 0.f, 0.f, 0.f};
            mma16(O, p[h] & ma, p[h + 1] & ma, p[h] & ~ma, p[h + 1] & ~ma, V1[i], Vb[i]);
            const float r = nx ? rs[h + 1] : rs[h];
            stg32(od + i * 1024 + hi * 256, pack2((nx ? O[2] : O[0]) * r, (nx ? O[3] : O[1]) * r));
          }
        };
        {
          float x0[4], x1[4];
#pragma unroll
          for (int h = 0; h < 4; h++) { x0[h] = (up0 ? S1[h][2] : S2[h][2]) * sc[1][0]; x1[h] = (up1 ? S1[h][3] : S2[h][3]) * sc[1][1]; }
          finish(x0, x1, V2, mup, 1);
        }
        ACLK(2);
        bar_sync(1 + w, 128);
#pragma unroll 1
        for (int it = 0; it < (1 << 20); it++) {
          if (remote) {
            bool ok = true;
#pragma unroll
            for (int i = 0; i < 6; i++) ok = ok && hv[i].z == tag;
            if (__all_sync(~0u, ok)) break;
          }
#pragma unroll
          for (int i = 0; i < 6; i++) hv[i] = ll_ld128g(hs + i * 512);
          if (!remote) break;
        }
        uint32_t H[18];
#pragma unroll
        for (int i = 0; i < 6; i++) { H[HA_[i]] = hv[i].x; H[HA_[i] + 1] = hv[i].y; H[HC_[i]] = hv[i].w; }
        float S0[4][4];
#pragma unroll
        for (int h = 0; h < 4; h++) {
#pragma unroll
          for (int i = 0; i < 4; i++) S0[h][i] = 0.f;
          mma16(S0[h], qa[h][0], qa[h][1], Pk[GB_[h]][0], Pk[GB_[h]][1], H[GA_[h]], H[GB_[h]]);
        }
#pragma unroll
        for (int h = 0; h < 4; h++) mma8(S0[h], qc[h][0], qc[h][1], H[GC_[h]]);
        uint32_t V0[9];
#pragma unroll
        for (int i = 0; i < 9; i++) V0[i] = movm(H[9 + i]);
        ACLK(3);
        {
          const bool nohalo = (rb | q) == 0;
          const float b0 = up0 && nohalo ? -INFINITY : 0.f, b1 = up1 && nohalo ? -INFINITY : 0.f;
          float x0[4], x1[4];
#pragma unroll
          for (int h = 0; h < 4; h++) { x0[h] = fmaf(up0 ? S0[h][0] : S1[h][0], sc[0][0], b0); x1[h] = fmaf(up1 ? S0[h][1] : S1[h][1], sc[0][1], b1); }
          finish(x0, x1, V0, ~mup, 0);
        }
        ACLK(4);
        signal(EV_O);
        ACLK_OUT;
        TRC(tr, w, tb + 2);
      }
      if (c.s) { c.s = 0; c.ph ^= 1; }
      if (PHM & 2) PHASE;
      {
        float acc[36];
        const int hw = rb * 2 + w;
        const uint32_t xt = stg + (8 * q + g) * 144 + t * 4;
        uint32_t xm = sb + SM_STG + 9216 + (8 * q + (lane & 7)) * 144 + (lane & 8) * 576 + (lane & 16);
        uint8_t* xn = xn_block(hw) + j * 9216 + q * 256 + lane * 4;
        uint32_t* sp = (uint32_t*)(Q.ST1 + (hw * 8 + j) * 32 + 8 * q) + lane;
        const uint4* sg = Q.ST1 + (hw * 8 + t) * 32 + 8 * q + g;
        asm volatile("" : "+r"(xm), "+l"(xn), "+l"(sp), "+l"(sg));
        mbar_wait_c(bars + B_RES + w * 8, L);
        TRC(tr, w, tb + 21);
#pragma unroll
        for (int i = 0; i < 18; i++) { const uint32_t x = lds32(xt + (i >> 1) * 16 + (i & 1) * 4608); acc[2 * i] = blo(x); acc[2 * i + 1] = bhi(x); asm volatile("" : "+f"(acc[2 * i]), "+f"(acc[2 * i + 1])); }
        mbar_wait_c(bars + B_WF, L);
        const uint32_t db = dlo(sb, 1152), of = bars + (w ? B_OF + 40 : B_AV + 96);
        uint32_t da[5];
#pragma unroll
        for (int e = 0; e < 5; e++) da[e] = __shfl_sync(~0u, dlo(sb + o_place(w, e), 1024), 0);
        if (w) {
#pragma unroll 1
          for (int kb = q; kb < 9; kb += 4) {
            const uint32_t e = (kb + 1) >> 1;
            mbar_wait_c(bars + B_OF + e * 8, L);
            check(Int<8>{}, sb + o_place(0, e) + (kb && !(kb & 1)) * 8192, z1_block(rb, 0, 0) + kb * 8192);
            if (lane <= !kb) mbar_arrive(bars + B_AV + (12 + e) * 8);
          }
          bar_sync(7, 256);
        }
        mbar_wait_c(of, L & w);
        TRC(tr, w, tb + 3);
        wgmma_fence();
#pragma unroll
        for (int kk = 0; kk < 4; kk++) wgmma_ss_n72(acc, dsc<128, 0>(da[0], kk * 2048), dsc<128, 0>(db, kk * 2304), 1);
        wgmma_commit();
#pragma unroll 1
        for (int h = 0; h < 2; h++) {
#pragma unroll
          for (int u = 0; u < 4; u++) {
            if (!(u & 1)) { mbar_wait_c(of + 8 + h * 16 + u * 4, 1 + 2 * h + (u >> 1) < SPL ? L & w : L); wgmma_fence(); }
            if (u == 3 && h && !w) bar_arrive(7, 256);
#pragma unroll
            for (int kk = 0; kk < 4; kk++) wgmma_ss_n72(acc, dsc<128, 0>(da[1 + (u >> 1)], (u & 1) * 8192 + kk * 2048), dsc<128, 0>(db + h * 2304, (1 + u) * 9216 + kk * 2304), 1);
            if (u != 2) wgmma_commit();
            if (u == 0) { wgmma_wait<1>(); if (lane + w == 0 && h) mbar_arrive(bars + B_X3); }
          }
          da[1] = da[3]; da[2] = da[4];
        }
        RCLK_INIT;
        wgmma_wait<0>();
        RCLK(0);
        if (lane < 2) mbar_arrive_cluster(ebar + B_XD - B_EMPTY + w * 8);
        TRC(tr && P5TRACE != 5, w, tb + 4);
        {
          float s0 = 0.f, s1 = 0.f, q0 = 0.f, q1 = 0.f;
#pragma unroll
          for (int i = 0; i < 36; i++) {
            if (i & 2) { s1 += acc[i]; q1 = fmaf(acc[i], acc[i], q1); } else { s0 += acc[i]; q0 = fmaf(acc[i], acc[i], q0); }
          }
          const bool o1 = t & 1, o2 = t & 2;
          const float ss = (o1 ? s1 : s0) + __shfl_xor_sync(~0u, o1 ? s0 : s1, 1), sq = (o1 ? q1 : q0) + __shfl_xor_sync(~0u, o1 ? q0 : q1, 1);
          const float v = (o2 ? sq : ss) + __shfl_xor_sync(~0u, o2 ? ss : sq, 2);
          asm volatile("st.relaxed.gpu.global.u32 [%0], %1;" ::"l"(sp), "r"(__float_as_uint(v)) : "memory");
        }
        RCLK(1);
        RCLK(2);
        pause<PDEL>(Q.zero);
        uint4 pa, pb;
        auto there = [&](const uint4& a, const uint4& b) { return __all_sync(~0u, max(max(max(a.x, a.y), max(a.z, a.w)), max(max(b.x, b.y), max(b.z, b.w))) != ~0u); };
#pragma unroll 1
        for (int it = 0; it < (1 << 20); it++) {
          pa = ll_ld128(sg); pb = ll_ld128(sg + 128);
          if (there(pa, pb)) break;
        }
        RCLK(3);
        float mean0 = qsum(__uint_as_float(pa.x) + __uint_as_float(pb.x)) * (-1.f / DM), mean1 = qsum(__uint_as_float(pa.y) + __uint_as_float(pb.y)) * (-1.f / DM);
        const float rs0 = GA * rsq_fast(fmaxf(fmaf(qsum(__uint_as_float(pa.z) + __uint_as_float(pb.z)), 1.f / DM, -mean0 * mean0), 0.f) + LN_EPS);
        const float rs1 = GA * rsq_fast(fmaxf(fmaf(qsum(__uint_as_float(pa.w) + __uint_as_float(pb.w)), 1.f / DM, -mean1 * mean1), 0.f) + LN_EPS);
        mean0 *= rs0; mean1 *= rs1;
#pragma unroll
        for (int i = 0; i < 18; i++) {
          const float a = (i & 1) ? rs1 : rs0, b = (i & 1) ? mean1 : mean0;
          stg32(xn + (i >> 1) * 1024 + (i & 1) * 128, pack2(fmaf(acc[2 * i], a, b), fmaf(acc[2 * i + 1], a, b)));
        }
        signal(EV_X1);
        RCLK(4);
        if (w) {
#pragma unroll 1
          for (int u = q; u < 24; u += 4) {
            const uint32_t mb = u < 2 * SPL ? u >= SPL : u & 1, k = u < 2 * SPL ? u - mb * SPL : u >> 1;
            mbar_wait_c(bars + B_AF3 + mb * 96 + k * 8, L);
            SCLK3(u);
            check(Int<6>{}, sb + k * 12288 + mb * 6144, xn_block(rb * 2 + mb) + k * 6144);
            SCLK3(24 + u);
            if (lane <= (u < 2 * SPL)) mbar_arrive(bars + B_AV + (u < SPL ? 12 + k : k) * 8);
          }
          TRVI(lane == 0 && P5TRACE != 5, 5, 56 + L * 4 + q, rp);
          mbar_wait_c(bars + B_S5, L);
        }
#pragma unroll
        for (int u = 0; u < 4; u++)
          stsm4(xm + u * 32, pack2(acc[8 * u], acc[8 * u + 1]), pack2(acc[8 * u + 2], acc[8 * u + 3]), pack2(acc[8 * u + 4], acc[8 * u + 5]), pack2(acc[8 * u + 6], acc[8 * u + 7]));
        asm volatile("stmatrix.sync.aligned.m8n8.x2.shared.b16 [%0], {%1,%2};" ::"r"(xm + 128), "r"(pack2(acc[32], acc[33])), "r"(pack2(acc[34], acc[35])) : "memory");
        fence_async_s();
        signal(EV_XS);
        RCLK(5);
        TRC(tr, w, tb + 5);
        RCLK(6);
        RCLK_OUT;
      }
      if (PHM & 4) PHASE;
      {
      float acc[160];
#pragma unroll
      for (int i = 0; i < 160; i++) acc[i] = 0.f;
      float s[2] = {0.f, 0.f}, qq[2] = {0.f, 0.f}, zo = 0.f;
      const uint32_t zp = sb + SM_ZP3 + (tid & 127) * 4;
      auto zstat = [&](int mb, bool on) {
        const bool o1 = t & 1, o2 = t & 2;
        const float ss = ((o1 ? s[1] : s[0]) + __shfl_xor_sync(~0u, o1 ? s[0] : s[1], 1)) * 0x1p60f, sq = (o1 ? qq[1] : qq[0]) + __shfl_xor_sync(~0u, o1 ? qq[0] : qq[1], 1);
        const uint32_t v = __float_as_uint((o2 ? sq : ss) + zo + __shfl_xor_sync(~0u, o2 ? ss : sq, 2));
        asm volatile("{\n.reg .pred p, q, r;\nsetp.eq.u32 p, %4, 1;\nsetp.eq.u32 q, %4, 2;\nsetp.eq.and.u32 r, %5, 0, q;\n@p st.shared.u32 [%0], %2;\n@p bar.arrive 13, 256;\n"
                     "@q st.relaxed.gpu.global.u32 [%1], %2;\n@r mbarrier.arrive.shared::cta.b64 _, [%3];\n}" ::"r"(zp + mb * 512), "l"((uint32_t*)(Q.ZST + ((rb * 2 + mb) * 8 + j) * 32) + (tid & 127)),
                     "r"(v), "r"(bars + B_ZS + mb * 8), "r"(on ? 1 + w : 0), "r"(lane) : "memory");
        s[0] = s[1] = qq[0] = qq[1] = 0.f;
      };
      const uint32_t ebar3 = ebar + (B_E3 - B_EMPTY);
#pragma unroll 1
      for (int half = 0; half < 2; half++) {
        const bool big = half != w;
        auto rel3 = [&](int p) { if (lane < 2) mbar_arrive_cluster(ebar3 + p * 8); };
        if (half + w > 0) bar_sync(6 + w, 256);
        auto pass = [&](auto nk) {
          constexpr int NK = nk.value;
          uint32_t d0 = dlo(sb, 1024), ph = half & ~w, af = bars + B_AV;
          const uint32_t db = dlo(sb + SM_B3, NK == 3 ? 6144 : 2048);
          const bool lead = NK == 3 && !half;
          if (lead) {
#pragma unroll
            for (int u = 0; u < 2 * SPL; u++) {
              const int mb = u / SPL, p = u % SPL;
              if (!mb) mbar_wait_c(bars + B_F3 + p * 8, 0);
              mbar_wait_c(af + (mb ? p : 12 + p) * 8, mb || p > 4 ? L : 1);
              TRC(tr && u == 0, w, tb + 6);
              SCLK2(u);
              if (p == 0) SCLK(mb * 4);
              wgmma_fence();
#pragma unroll
              for (int kk = 0; kk < 3; kk++) {
                wgmma_ss_n128(acc + mb * 80, dsc<128, 0>(d0, p * 12288 + kk * 2048 + mb * 6144), dsc<1024, 1>(db, p * 12288 + kk * 2048), p + kk > 0);
                if (kk == 0 && u > SPL) { wgmma_commit(); wgmma_wait<1>(); rel3(p - 1); }
              }
              wgmma_commit();
            }
          }
#pragma unroll 1
          for (int it = 0; it < 6 / NK; it++) {
#pragma unroll
            for (int p = 0; p < 6; p++) {
              if (p < SPL && lead && it == 0) continue;
              mbar_wait_c(bars + B_F3 + p * 8, ph);
              if (NK == 3) mbar_wait_c(af + p * 8, L);
              TRC(tr && p == 0 && it == 0, w, tb + 6 + half * 4);
              if (lead) SCLK2(12 + it * 6 + p);
              if (NK == 2 ? !(p & 1) : p % 3 == 0) SCLK(half * 11 + (NK == 2 ? it * 3 + p / 2 : it * 2 + p / 3));
              wgmma_fence();
#pragma unroll
              for (int u = 0; u < 2 * NK; u++) {
                const int kk = u >> 1, mb = u & 1, e = p * NK + kk;
                const uint64_t da = dsc<128, 0>(d0, (e / 3) * 12288 + (e % 3) * 2048 + mb * 6144);
                if (NK == 3) wgmma_ss_n128(acc + mb * 80, da, dsc<1024, 1>(db, p * 12288 + kk * 2048), e > 0 || it > 0);
                else wgmma_ss_n160(acc + mb * 80, da, dsc<1024, 1>(db, p * 12288 + kk * 6144), e > 0 || it > 0);
                if (u == 0) { wgmma_commit(); wgmma_wait<1>(); if (p > 0 || it > 0) rel3((p + 5) % 6); }
                if (u == HO3 && p == 5 && it == 6 / NK - 1) bar_arrive(7 - w, 256);
              }
              wgmma_commit();
            }
            d0 += NK * 1536; af += 48;
            ph ^= 1;
          }
        };
        if (big) pass(Int<2>{}); else pass(Int<3>{});
        if (w) { bar_sync(13, 256); zo = __uint_as_float(lds32(zp + half * 512)); }
        if (half) zstat(1, true);
        const uint32_t off2 = lds32(sb + SM_OFF);
        const int go = (j & 1) ? (big ? 0 : 20) : (big ? 16 : 0);
        const float* gbp = (const float*)(smem_raw + SM_OFF + 8);
        asm volatile("" : "+l"(gbp));
        uint8_t* zd = half ? z1_block(rb, 0, j) + go * 1024 + (q & 1) * 2048 + (q >> 1) * 512 + lane * 16 : z2_block(rb, j) + q * 9216 + go * 128 + ((g & 3) * 2 + (g >> 2)) * 16 + t * 4;
        wgmma_wait<0>();
        SCLK(half * 11 + 9);
        rel3(5);
        TRC(tr, w, tb + 7 + half * 4);
        auto gelu = [&](auto z2) {
          constexpr int NC = z2.value ? NC2 : NC1;
          float gate[NC], gb = GB, gn = GB;
          uint32_t qa[2][3] = {{0, 0, 0}, {0, 0, 0}};
#pragma unroll
          for (int e = 0; e < NC; e++) gate[e] = GB;
#pragma unroll
          for (int G = 0; G < 20; G++) {
            if (G == 16 && !big) break;
            if (G % (z2.value ? LD2 : LD1) == 0) { gb = gn; if (G < 20 - (z2.value ? LD2 : LD1)) asm volatile("ld.f32 %0, [%1];" : "=f"(gn) : "l"(gbp) : "memory"); }
#pragma unroll
            for (int r = 0; r < 2; r++) {
              float z[2];
              float& gt = gate[(G * 2 + r) % NC];
#pragma unroll
              for (int e = 0; e < 2; e++) {
                const float v = acc[4 * G + 2 * r + e];
                z[e] = fmaf(v, tanh_fast(v * fmaf(v, v, gt)), v);
                if (z2.value) { s[r] = fmaf(z[e], 0x1p-60f, s[r]); qq[r] = fmaf(z[e], z[e], qq[r]); }
              }
              const uint32_t pk = pack2(z[0], z[1]);
              if (z2.value) {
                stg32(zd + G * 128 + r * 4608, hsub2(pk, off2));
                gt = fmaf(qq[r], s[r], gb);
              } else {
                gt = fmaf(__uint_as_float(pk), 0x1p-60f, gb);
                if ((G & 3) == 3) stg128(zd + (G >> 2) * 4096 + r * (8 * ZB), qa[r][0], qa[r][1], qa[r][2], pk);
                else qa[r][G & 3] = pk;
              }
            }
          }
        };
#pragma unroll 1
        for (int mb = 0;; mb++) {
          if (half) gelu(Int<0>{}); else gelu(Int<1>{});
          if (mb) break;
          zstat(0, !half);
#pragma unroll
          for (int i = 0; i < 80; i++) acc[i] = acc[80 + i];
          zd += half ? 1024 : 128 * ZB;
        }
        mbar_wait_c(bars + B_GATE3, L);
        signal(half ? EV_Z1 : EV_ZN);
        SCLK(half * 11 + 10);
        TRC(tr, w, tb + 8 + half * 4);
      }
      }
      if (PHM & 8) PHASE;
      const uint32_t aoff = (w * 64 + q * 16 + (lane & 15)) * 128 + (((lane >> 4) ^ (lane & 7)) << 4);
      uint32_t hA[18][4];
      {
        float acc[144];
        const float c0 = __uint_as_float(lds32(sb + SM_OFF + 4));
#pragma unroll
        for (int i = 0; i < 144; i++) {
          asm volatile("fma.rn.f32 %0, %1, %2, %3;" : "=f"(acc[i]) : "f"(__uint_as_float(Q.zero)), "f"((float)(i + 2)), "f"(c0));
        }
        uint32_t prev = 0;
        auto stage = [&](int kb) {
          mbar_wait_c(bars + B_FULL + c.s * 8, c.ph);
          TRC(tr && kb == 0, w, tb + 13);
          SCLK(22 + kb);
          const uint32_t st = sb + c.s * ST_BYTES, db = dlo(st + ST_B, 4608), rt = sb + SM_RT + kb * 128 + t * 8;
          uint32_t a[4][4];
#pragma unroll
          for (int kk = 0; kk < 4; kk++) {
            uint32_t r[4];
            ldsm4(r, st + (aoff ^ (kk << 5)));
            const uint2 sc = lds64(rt + kk * 32);
            a[kk][0] = hmul2(__byte_perm(r[0], r[2], 0x5410), sc.x); a[kk][2] = hmul2(__byte_perm(r[0], r[2], 0x7632), sc.y);
            a[kk][1] = hmul2(__byte_perm(r[1], r[3], 0x5410), sc.x); a[kk][3] = hmul2(__byte_perm(r[1], r[3], 0x7632), sc.y);
          }
          if (kb + w == 0) bar_sync(6, 256);
          wgmma_fence();
#pragma unroll
          for (int i = 0; i < 8; i++) {
            const int kk = i & 3, hf = i >> 2;
            wgmma_rs_n144(acc + hf * 72, a[kk], dsc<128, 0>(db, kk * 9216 + hf * 2304), 1);
            if (i == 0) { wgmma_commit(); wgmma_wait<1>(); if (kb) release(prev); }
            if (i == 3) wgmma_commit();
          }
          wgmma_commit();
          prev = c.s; c.next();
        };
#pragma unroll 1
        for (int kb = 0; kb < 32; kb += 2) {
          if (!(kb & 7)) mbar_wait_c(bars + B_RT + kb, L);
          stage(kb);
          stage(kb + 1);
        }
        mbar_wait_c(bars + B_CV + w * 8, L);
        const float gk = 0.5f / GA;
        const float c1 = __uint_as_float(lds32(sb + SM_OFF + 4));
        const float gb0 = -gk * (c1 + __uint_as_float(lds32(sb + SM_CV + w * 256 + (16 * q + g) * 4))), gb1 = -gk * (c1 + __uint_as_float(lds32(sb + SM_CV + w * 256 + (16 * q + g + 8) * 4)));
        if (w == 1) { mbar_wait_c(bars + B_FULL + c.s * 8, c.ph); release(c.s); c.next(); }
        mbar_wait_c(bars + B_FULL + c.s * 8, c.ph);
        const uint32_t zs = sb + c.s * ST_BYTES + ST_B + (tid & 127) * 16;
        uint4 zl, zh;
#pragma unroll
        for (int u = 0; u < 18; u++) {
          if (u == 0) wgmma_wait<1>();
          if (u == 9) {
            wgmma_wait<0>();
            release(prev);
            if (L == 0) signal(EV_PT);
            TRC(tr, w, tb + 14);
            SCLK(54);
          }
          if (!(u & 1)) { zl = lds128(zs + u * 2048); zh = lds128(zs + u * 2048 + 2048); }
          const uint4 z = (u & 1) ? make_uint4(zl.z, zh.z, zl.w, zh.w) : make_uint4(zl.x, zh.x, zl.y, zh.y);
          hA[u][0] = hmul2(z.x, pack2(fmaf(acc[8 * u], gk, gb0), fmaf(acc[8 * u + 1], gk, gb0)));
          hA[u][1] = hmul2(z.y, pack2(fmaf(acc[8 * u + 2], gk, gb1), fmaf(acc[8 * u + 3], gk, gb1)));
          hA[u][2] = hmul2(z.z, pack2(fmaf(acc[8 * u + 4], gk, gb0), fmaf(acc[8 * u + 5], gk, gb0)));
          hA[u][3] = hmul2(z.w, pack2(fmaf(acc[8 * u + 6], gk, gb1), fmaf(acc[8 * u + 7], gk, gb1)));
        }
        __syncwarp();
        release(c.s);
        c.next();
        if (w == 0) { mbar_wait_c(bars + B_FULL + c.s * 8, c.ph); release(c.s); c.next(); }
        TRC(tr, w, tb + 15);
      }
      {
        CLK_INIT;
        if (w == 1) bar_arrive(6, 256);
        uint32_t pk[16];
#pragma unroll
        for (int i = 0; i < 16; i++) pk[i] = 0u;
        auto dump = [&](int p) {
          const uint32_t d = sb + (p & 3) * ST_BYTES, cb = p + j >= 9 ? p + j - 9 : p + j;
          asm volatile("cp.async.bulk.wait_group.read 3;" ::: "memory");
          __syncwarp();
#pragma unroll
          for (int u = 0; u < 4; u++) stsm4(d + (aoff ^ (u << 5)), pk[4 * u], pk[4 * u + 1], pk[4 * u + 2], pk[4 * u + 3]);
          fence_async_s();
          __syncwarp();
          tma3d_red_p(elect_one(), &P.red, cb * 64, rb * 64 + q * 16, w, d + w * 8192 + q * 2048);
        };
#pragma unroll 1
        for (int p = 0; p < 9; p++) {
          float acc[32];
          CLK(0);
          mbar_wait_c(bars + B_FULL + c.s * 8, c.ph);
          const uint32_t db = dlo(sb + c.s * ST_BYTES + ST_B, 0);
          CLK(1);
          bar_sync(6 + w, 256);
          CLK(2);
          wgmma_fence();
#pragma unroll
          for (int kk = 0; kk < 18; kk++) {
            wgmma_rs_n64(acc, hA[kk], dsc<1024, 1>(db, kk * 2048), kk != 0);
            if (kk == PPK && (w == 0 || p < 8)) bar_arrive(7 - w, 256);
          }
          wgmma_commit();
          CLK(3);
          if (p > 0) dump(p - 1);
          CLK(5);
          wgmma_wait<0>();
          CLK(4);
          if (L == 0 || p < 5) release(c.s);
          c.next();
#pragma unroll
          for (int i = 0; i < 16; i++) pk[i] = pack2(acc[2 * i], acc[2 * i + 1]);
          if (p == 8) { TRC(tr, w, tb + 16); dump(8); TRC(tr, w, tb + 17); }
        }
        asm volatile("cp.async.bulk.wait_group 0;" ::: "memory");
        if (L == 0) signal(EV_PT);
        CLK_OUT;
        TRC(tr, w, tb + 18);
      }
    }
    if ((tid & 127) == 0) Q.flags[(rb * 2 + w) * 32 + FR_EP + j] = epoch + 1;
    if (tid == 0) Q.flags[FJ + j * 32 + FJ_EP + rb] = epoch + 1;
  }
}

typedef CUresult (*EncodeFn)(CUtensorMap*, CUtensorMapDataType, cuuint32_t, void*, const cuuint64_t*, const cuuint64_t*, const cuuint32_t*,
                             const cuuint32_t*, CUtensorMapInterleave, CUtensorMapSwizzle, CUtensorMapL2promotion, CUtensorMapFloatOOBfill);

static void make_map(EncodeFn fn, CUtensorMap* m, const void* ptr, int rank, uint64_t d0, uint64_t d1, uint64_t d2, uint64_t s1, uint64_t s2,
                     uint32_t b0, uint32_t b1, uint32_t b2, CUtensorMapSwizzle swz) {
  cuuint64_t dims[3] = {d0, d1, d2}, strides[2] = {s1, s2};
  cuuint32_t box[3] = {b0, b1, b2}, es[3] = {1, 1, 1};
  fn(m, CU_TENSOR_MAP_DATA_TYPE_BFLOAT16, rank, const_cast<void*>(ptr), dims, strides, box, es, CU_TENSOR_MAP_INTERLEAVE_NONE, swz,
     CU_TENSOR_MAP_L2_PROMOTION_L2_128B, CU_TENSOR_MAP_FLOAT_OOB_FILL_NONE);
}

}

extern "C" void kernel_launch(void* const* d_in, const int* in_sizes, int n_in, void* d_out, int out_size) {
  using namespace mk;
  (void)in_sizes; (void)n_in; (void)out_size;
  static EncodeFn fn = nullptr;
  static Scratch* sc = nullptr;
  if (!fn) {
    cudaDriverEntryPointQueryResult qr;
    cudaGetDriverEntryPoint("cuTensorMapEncodeTiled", (void**)&fn, cudaEnableDefault, &qr);
    cudaGetSymbolAddress((void**)&sc, g_scratch);
    cudaFuncSetAttribute(mega_kernel, cudaFuncAttributeMaxDynamicSharedMemorySize, SM_TOTAL);
  }
  Params p;
  Ptrs a;
  a.x = (const uint8_t*)d_in[0];
  a.wqkv = (const __nv_bfloat16*)d_in[1];
  a.wo = (const __nv_bfloat16*)d_in[2];
  a.w_in = (const __nv_bfloat16*)d_in[4];
  a.w_sp = (const __nv_bfloat16*)d_in[5];
  a.b_sp = (const __nv_bfloat16*)d_in[6];
  a.out = (uint8_t*)d_out;
  a.zero = 0;
  a.WQ = sc->WQ; a.flags = sc->flags; a.CSP = sc->CSP; a.XST = sc->XST; a.HALO = sc->HALO; a.ST1 = sc->ST1; a.ZST = sc->ZST; a.RT = sc->RT; a.Z = sc->Z; a.WO = sc->WO;
  make_map(fn, &p.wsp, a.w_sp, 3, 2048, 1024, 2, 8192, 4096, 64, 64, 2, CU_TENSOR_MAP_SWIZZLE_128B);
  for (int i = 0; i < 2; i++) {
    make_map(fn, &p.act[i], i ? a.out : a.x, 3, DM, 1024, 2, 2304, 1152, 64, 64, 1, CU_TENSOR_MAP_SWIZZLE_128B);
    make_map(fn, &p.row[i], i ? a.out : a.x, 3, 192, 6, 1024, 384, 2304, 192, 3, 8, CU_TENSOR_MAP_SWIZZLE_NONE);
    make_map(fn, &p.res[i], i ? a.out : a.x, 3, DM, 1024, 2, 2304, 1152, 72, 32, 2, CU_TENSOR_MAP_SWIZZLE_NONE);
  }
  make_map(fn, &p.red, d_out, 3, DM, 1024, 2, 2304, 1152, 64, 16, 1, CU_TENSOR_MAP_SWIZZLE_128B);
  for (int i = 0; i < 2; i++) make_map(fn, &p.winb[i], a.w_in + 32 * i, 3, 64, 576, 72 - i, 9216, 128, 64, 16, 3, CU_TENSOR_MAP_SWIZZLE_128B);
  make_map(fn, &p.wins, a.w_in, 3, 64, 576, 72, 9216, 128, 64, 48, 1, CU_TENSOR_MAP_SWIZZLE_128B);
  make_map(fn, &p.wout, d_in[7], 2, 576, 2304, 1, 1152, 0, 64, 144, 1, CU_TENSOR_MAP_SWIZZLE_128B);
  mega_kernel<<<NGRID, 384, SM_TOTAL, cudaStreamPerThread>>>(a, p);
}
```

```cpp
#include <cuda_runtime.h>
#include <cuda.h>
#include <cuda_bf16.h>
#include <stdint.h>

#define MK_TRACE 0
#define MK_DBG 0
#define P5TRACE 0
#define LAG1 1
#define C0S 32.f
#define OFM 0x10u
#define NC2 2
#define NC1 8
#define PDEL 8
#define LD1 4
#define LD2 2
#define ZD1 8
#define ZD2 20
#define WPF 1
#define YPACE 2
#define SPL 3
#define XP0 10
#define EFM 0x23333022
#define EF(i) ((((EFM >> (4 * (i))) & 3) == 3) || (((EFM >> (4 * (i))) >> L) & 1))
#define AEP 2
#define PZI 4
#define KS 1
#define RFI 3
#define XK1 1
#define XK2 2
#define SDEL 10
#define FD3 14
#define FD4 0
#define FD5 0
#define PHM 15
#define NOW 2
#define APACE 7
#define HO3 41
#define HO4 41
#define PPK 17

namespace mk {

constexpr int SEQ = 2048, DM = 576, FH = 2304;
constexpr int NCTA = 128;
constexpr int NGRID = 132;
constexpr uint32_t ZB = 36864;
constexpr uint32_t WQ_SL = 72 * 3456;
constexpr uint32_t WO_SL = 72 * 1152;
constexpr float LN_EPS = 1e-5f;
constexpr float GA = 0.3292034911525734f, GB = 2.423681954311584f;

constexpr uint32_t ST_BYTES = 53248, ST_B = 16384, NST = 4;
constexpr uint32_t SM_STG = NST * ST_BYTES;
constexpr uint32_t SM_BAR = SM_STG + 2 * 9216, B_OFF = 896;
constexpr uint32_t SM_OFF = SM_BAR + B_OFF;
constexpr uint32_t SM_TOTAL = SM_BAR + 1024;
constexpr uint32_t SM_RT = SM_STG + 9216, SM_CV = SM_STG + 17408, SM_WT = SM_STG;
constexpr uint32_t SM_WOI = 44032, SM_CSQ = 49280, SM_XST = 50176;
enum { EV_PT = 0, EV_O = 1, EV_X1 = 2, EV_ZN = 3, EV_Z1 = 4, EV_XS = 5, EV_N = 6 };
constexpr uint32_t B_FULL = 0, B_FULLA = 32, B_RES = 96, B_WT = 112, B_GATE3 = 128, B_Z1 = 136, B_ZOK = 144, B_CV = 152, B_XRW = 168, B_F3 = 184, B_WF = 232, B_OF = 240,
                   B_RT = 320, B_AF3 = 352, B_RB = 544,
                   B_AD = 576, B_S5 = 608, B_AV = 616, B_CSQ = 760,
                   B_LAG = 768, B_X3 = 776, B_ZS = 784, B_EVT = 800,
                   B_IMG = 912, B_WOI = 920, B_E3 = 928, B_XD = 976,
                   B_EMPTY = 992;
constexpr uint32_t SM_B3 = 9 * 16384, SM_ZP3 = SM_STG + 8192;

enum { FR_X2 = 0, FR_O = 1, FR_XR = 5, FR_OL = 7, FR_PZ = 9, FR_EP = 16, FJ = 32 * 32, FJ_WQ = 0, FJ_WO = 1, FJ_ZN = 3, FJ_P4 = 5, FJ_EP = 16, F_N = FJ + 8 * 32 };

struct Scratch {
  alignas(1024) uint32_t flags[F_N];
  alignas(1024) float CSP[2 * NCTA * 216];
  alignas(1024) uint2 RT[SEQ];
  alignas(1024) uint4 XST[2 * SEQ];
  alignas(1024) uint4 ST1[SEQ * 4];
  alignas(1024) uint4 ZST[SEQ * 4];
  alignas(1024) uint4 HALO[32 * 8 * 6 * 32];
  alignas(1024) uint8_t WO[8 * WO_SL];
  alignas(1024) uint8_t WQ[8 * WQ_SL];
  alignas(1024) uint8_t Z[576 * ZB];
};
__device__ Scratch g_scratch;

struct Ptrs {
  const __nv_bfloat16* wqkv;
  uint8_t* WQ;
  uint32_t* flags;
  float* CSP;
  const uint8_t* x;
  uint32_t zero;
  uint4 *XST, *HALO, *ST1, *ZST;
  uint2* RT;
  uint8_t *Z, *WO, *out;
  const __nv_bfloat16 *wo, *w_in, *w_sp, *b_sp;
};
struct Params {
  CUtensorMap wsp, winb[2], wins, wout;
  CUtensorMap act[2];
  CUtensorMap res[2];
  CUtensorMap row[2];
};

__device__ __forceinline__ uint32_t smem_u32(const void* p) { return (uint32_t)__cvta_generic_to_shared(p); }
__device__ __forceinline__ void mbar_init(uint32_t bar, uint32_t cnt) { asm volatile("mbarrier.init.shared::cta.b64 [%0], %1;" ::"r"(bar), "r"(cnt)); }
__device__ __forceinline__ void mbar_arrive(uint32_t bar) { asm volatile("mbarrier.arrive.shared::cta.b64 _, [%0];" ::"r"(bar) : "memory"); }
__device__ __forceinline__ void mbar_wait(uint32_t bar, uint32_t parity) {
  asm volatile(
      "{\n.reg .pred p;\n.reg .u32 c;\nmov.u32 c, 0;\nLAB_WAIT:\n"
      "mbarrier.try_wait.parity.shared::cta.b64 p, [%0], %1;\n@p bra LAB_DONE;\n"
      "add.u32 c, c, 1;\nsetp.lt.u32 p, c, 0x100000;\n@p bra LAB_WAIT;\ntrap;\nLAB_DONE:\n}" ::"r"(bar), "r"(parity)
      : "memory");
}
__device__ __forceinline__ void mbar_wait_c(uint32_t bar, uint32_t parity) {
  asm volatile("{\n.reg .pred p;\nLAB_WAIT:\nmbarrier.try_wait.parity.shared::cta.b64 p, [%0], %1;\n@!p bra LAB_WAIT;\n}" ::"r"(bar), "r"(parity) : "memory");
}
__device__ __forceinline__ void flag_wait(const uint32_t* f, uint32_t target) {
  asm volatile(
      "{\n.reg .pred p;\n.reg .u32 c, v;\nmov.u32 c, 0;\nLAB_WAIT:\n"
      "ld.relaxed.gpu.global.u32 v, [%0];\nsub.u32 v, v, %1;\nsetp.ge.s32 p, v, 0;\n@p bra LAB_DONE;\n"
      "add.u32 c, c, 1;\nsetp.lt.u32 p, c, 0x400000;\n@p bra LAB_WAIT;\ntrap;\nLAB_DONE:\nfence.acquire.gpu;\n}" ::"l"(f), "r"(target)
      : "memory");
}
__device__ __forceinline__ void fence_gpu() { asm volatile("fence.acq_rel.gpu;" ::: "memory"); }
__device__ __forceinline__ void fence_async_g() { asm volatile("fence.proxy.async.global;" ::: "memory"); }
__device__ __forceinline__ void fence_async_s() { asm volatile("fence.proxy.async.shared::cta;" ::: "memory"); }
__device__ __forceinline__ uint32_t elect_one() {
  uint32_t p; asm volatile("{\n.reg .pred P;\nelect.sync _|P, 0xffffffff;\nselp.u32 %0, 1, 0, P;\n}" : "=r"(p)); return p;
}
__device__ __forceinline__ void expect_tx_p(uint32_t el, uint32_t bar, uint32_t bytes) {
  asm volatile("{\n.reg .pred P;\nsetp.ne.u32 P, %2, 0;\n@P mbarrier.arrive.expect_tx.shared::cta.b64 _, [%0], %1;\n}" ::"r"(bar), "r"(bytes), "r"(el) : "memory");
}
__device__ __forceinline__ void bulk_load_p(uint32_t el, uint32_t dst, const void* src, uint32_t bytes, uint32_t bar) {
  asm volatile("{\n.reg .pred P;\nsetp.ne.u32 P, %4, 0;\n@P cp.async.bulk.shared::cluster.global.mbarrier::complete_tx::bytes [%0], [%1], %2, [%3];\n}" ::"r"(dst), "l"(src), "r"(bytes), "r"(bar), "r"(el) : "memory");
}
__device__ __forceinline__ uint64_t policy_evict_first() { uint64_t p; asm("createpolicy.fractional.L2::evict_first.b64 %0, 1.0;" : "=l"(p)); return p; }
__device__ __forceinline__ void bulk_load_h(uint32_t el, uint32_t dst, const void* src, uint32_t bytes, uint32_t bar, bool ef, uint64_t pol) {
  if (ef) {
    asm volatile("{\n.reg .pred P;\nsetp.ne.u32 P, %4, 0;\n@P cp.async.bulk.shared::cluster.global.mbarrier::complete_tx::bytes.L2::cache_hint [%0], [%1], %2, [%3], %5;\n}" ::"r"(dst), "l"(src), "r"(bytes), "r"(bar), "r"(el), "l"(pol) : "memory");
  } else {
    asm volatile("{\n.reg .pred P;\nsetp.ne.u32 P, %4, 0;\n@P cp.async.bulk.shared::cluster.global.mbarrier::complete_tx::bytes [%0], [%1], %2, [%3];\n}" ::"r"(dst), "l"(src), "r"(bytes), "r"(bar), "r"(el) : "memory");
  }
}
__device__ __forceinline__ void bulk_mc_h(uint32_t el, uint32_t dst, const void* src, uint32_t bytes, uint32_t bar, bool ef, uint64_t pol) {
  if (ef) {
    asm volatile("{\n.reg .pred P;\nsetp.ne.u32 P, %4, 0;\n@P cp.async.bulk.shared::cluster.global.mbarrier::complete_tx::bytes.multicast::cluster.L2::cache_hint [%0], [%1], %2, [%3], %5, %6;\n}" ::"r"(dst), "l"(src), "r"(bytes), "r"(bar), "r"(el), "h"((uint16_t)3), "l"(pol) : "memory");
  } else {
    asm volatile("{\n.reg .pred P;\nsetp.ne.u32 P, %4, 0;\n@P cp.async.bulk.shared::cluster.global.mbarrier::complete_tx::bytes.multicast::cluster [%0], [%1], %2, [%3], %5;\n}" ::"r"(dst), "l"(src), "r"(bytes), "r"(bar), "r"(el), "h"((uint16_t)3) : "memory");
  }
}
__device__ __forceinline__ void tma3d_h(uint32_t el, uint32_t dst, const CUtensorMap* m, int c0, int c1, int c2, uint32_t bar, bool ef, uint64_t pol) {
  if (ef) {
    asm volatile("{\n.reg .pred P;\nsetp.ne.u32 P, %6, 0;\n@P cp.async.bulk.tensor.3d.shared::cluster.global.mbarrier::complete_tx::bytes.L2::cache_hint [%0], [%1, {%3, %4, %5}], [%2], %7;\n}" ::"r"(dst), "l"(m), "r"(bar), "r"(c0), "r"(c1), "r"(c2), "r"(el), "l"(pol) : "memory");
  } else {
    asm volatile("{\n.reg .pred P;\nsetp.ne.u32 P, %6, 0;\n@P cp.async.bulk.tensor.3d.shared::cluster.global.mbarrier::complete_tx::bytes [%0], [%1, {%3, %4, %5}], [%2];\n}" ::"r"(dst), "l"(m), "r"(bar), "r"(c0), "r"(c1), "r"(c2), "r"(el) : "memory");
  }
}
__device__ __forceinline__ void tma2d_mc_h(uint32_t el, uint32_t dst, const CUtensorMap* m, int c0, int c1, uint32_t bar, bool ef, uint64_t pol) {
  if (ef) {
    asm volatile("{\n.reg .pred P;\nsetp.ne.u32 P, %5, 0;\n@P cp.async.bulk.tensor.2d.shared::cluster.global.mbarrier::complete_tx::bytes.multicast::cluster.L2::cache_hint [%0], [%1, {%3, %4}], [%2], %6, %7;\n}" ::"r"(dst), "l"(m), "r"(bar), "r"(c0), "r"(c1), "r"(el), "h"((uint16_t)3), "l"(pol) : "memory");
  } else {
    asm volatile("{\n.reg .pred P;\nsetp.ne.u32 P, %5, 0;\n@P cp.async.bulk.tensor.2d.shared::cluster.global.mbarrier::complete_tx::bytes.multicast::cluster [%0], [%1, {%3, %4}], [%2], %6;\n}" ::"r"(dst), "l"(m), "r"(bar), "r"(c0), "r"(c1), "r"(el), "h"((uint16_t)3) : "memory");
  }
}
__device__ __forceinline__ void tma3d_mc_h(uint32_t el, uint32_t dst, const CUtensorMap* m, int c0, int c1, int c2, uint32_t bar, bool ef, uint64_t pol) {
  if (ef) {
    asm volatile("{\n.reg .pred P;\nsetp.ne.u32 P, %6, 0;\n@P cp.async.bulk.tensor.3d.shared::cluster.global.mbarrier::complete_tx::bytes.multicast::cluster.L2::cache_hint [%0], [%1, {%3, %4, %5}], [%2], %7, %8;\n}" ::"r"(dst), "l"(m), "r"(bar), "r"(c0), "r"(c1), "r"(c2), "r"(el), "h"((uint16_t)3), "l"(pol) : "memory");
  } else {
    asm volatile("{\n.reg .pred P;\nsetp.ne.u32 P, %6, 0;\n@P cp.async.bulk.tensor.3d.shared::cluster.global.mbarrier::complete_tx::bytes.multicast::cluster [%0], [%1, {%3, %4, %5}], [%2], %7;\n}" ::"r"(dst), "l"(m), "r"(bar), "r"(c0), "r"(c1), "r"(c2), "r"(el), "h"((uint16_t)3) : "memory");
  }
}
__device__ __forceinline__ void mbar_arrive_cluster(uint32_t addr) { asm volatile("mbarrier.arrive.shared::cluster.b64 _, [%0];" ::"r"(addr) : "memory"); }
__device__ __forceinline__ uint32_t mapa(uint32_t addr, uint32_t rank) { uint32_t r; asm("mapa.shared::cluster.u32 %0, %1, %2;" : "=r"(r) : "r"(addr), "r"(rank)); return r; }
__device__ __forceinline__ void bulk_store_p(uint32_t el, void* dst, uint32_t src, uint32_t bytes) {
  asm volatile("{\n.reg .pred P;\nsetp.ne.u32 P, %3, 0;\n@P cp.async.bulk.global.shared::cta.bulk_group [%0], [%1], %2;\n}" ::"l"(dst), "r"(src), "r"(bytes), "r"(el) : "memory");
}
__device__ __forceinline__ void flag_release_p(uint32_t el, uint32_t* f) {
  asm volatile("{\n.reg .pred P;\nsetp.ne.u32 P, %1, 0;\nfence.proxy.async;\n@P red.relaxed.gpu.global.add.u32 [%0], 1;\n}" ::"l"(f), "r"(el) : "memory");
}
__device__ __forceinline__ void flag_add_p(uint32_t el, uint32_t* f) {
  asm volatile("{\n.reg .pred P;\nsetp.ne.u32 P, %1, 0;\n@P red.relaxed.gpu.global.add.u32 [%0], 1;\n}" ::"l"(f), "r"(el) : "memory");
}
__device__ __forceinline__ void prefetch_l2(const void* src, uint32_t bytes) { asm volatile("cp.async.bulk.prefetch.L2.global [%0], %1;" ::"l"(src), "r"(bytes) : "memory"); }
__device__ __forceinline__ void prefetch_map(const CUtensorMap* m) { asm volatile("prefetch.tensormap [%0];" ::"l"(m) : "memory"); }
__device__ __forceinline__ void wgmma_fence() { asm volatile("wgmma.fence.sync.aligned;" ::: "memory"); }
__device__ __forceinline__ void wgmma_commit() { asm volatile("wgmma.commit_group.sync.aligned;" ::: "memory"); }
template <int N> __device__ __forceinline__ void wgmma_wait() { asm volatile("wgmma.wait_group.sync.aligned %0;" ::"n"(N) : "memory"); }
__device__ __forceinline__ uint32_t dlo(uint32_t addr, uint32_t lbo) { return ((addr & 0x3FFFF) >> 4) + ((lbo >> 4) << 16); }
template <uint32_t SBO, uint32_t SWZ> __device__ __forceinline__ uint64_t dsc(uint32_t lo, uint32_t off) {
  uint64_t d; asm("mov.b64 %0, {%1, %2};" : "=l"(d) : "r"(lo + (off >> 4)), "n"((SBO >> 4) | (SWZ << 30))); return d;
}
template <int R> __device__ __forceinline__ void reg_alloc() { asm volatile("setmaxnreg.inc.sync.aligned.u32 %0;" ::"n"(R)); }
template <int R> __device__ __forceinline__ void reg_dealloc() { asm volatile("setmaxnreg.dec.sync.aligned.u32 %0;" ::"n"(R)); }
__device__ __forceinline__ void bar_sync(int id, int n) { asm volatile("bar.sync %0, %1;" ::"r"(id), "r"(n) : "memory"); }
__device__ __forceinline__ void bar_arrive(int id, int n) { asm volatile("bar.arrive %0, %1;" ::"r"(id), "r"(n) : "memory"); }
__device__ __forceinline__ void ldsm4(uint32_t* r, uint32_t addr) {
  asm volatile("ldmatrix.sync.aligned.m8n8.x4.shared.b16 {%0,%1,%2,%3}, [%4];" : "=r"(r[0]), "=r"(r[1]), "=r"(r[2]), "=r"(r[3]) : "r"(addr) : "memory");
}
__device__ __forceinline__ uint32_t movm(uint32_t a) { uint32_t d; asm volatile("movmatrix.sync.aligned.m8n8.trans.b16 %0, %1;" : "=r"(d) : "r"(a)); return d; }
__device__ __forceinline__ void mma16(float* c, uint32_t a0, uint32_t a1, uint32_t a2, uint32_t a3, uint32_t b0, uint32_t b1) {
  asm volatile("mma.sync.aligned.m16n8k16.row.col.f32.bf16.bf16.f32 {%0,%1,%2,%3}, {%4,%5,%6,%7}, {%8,%9}, {%0,%1,%2,%3};"
               : "+f"(c[0]), "+f"(c[1]), "+f"(c[2]), "+f"(c[3]) : "r"(a0), "r"(a1), "r"(a2), "r"(a3), "r"(b0), "r"(b1));
}
__device__ __forceinline__ void mma8(float* c, uint32_t a0, uint32_t a1, uint32_t b0) {
  asm volatile("mma.sync.aligned.m16n8k8.row.col.f32.bf16.bf16.f32 {%0,%1,%2,%3}, {%4,%5}, {%6}, {%0,%1,%2,%3};"
               : "+f"(c[0]), "+f"(c[1]), "+f"(c[2]), "+f"(c[3]) : "r"(a0), "r"(a1), "r"(b0));
}
__device__ __forceinline__ uint32_t pack2(float lo, float hi) { uint32_t r; asm("cvt.rn.bf16x2.f32 %0, %1, %2;" : "=r"(r) : "f"(hi), "f"(lo)); return r; }
__device__ __forceinline__ float blo(uint32_t v) { return __uint_as_float(v << 16); }
__device__ __forceinline__ float bhi(uint32_t v) { return __uint_as_float(v & 0xffff0000u); }
__device__ __forceinline__ float tanh_fast(float x) { float y; asm("tanh.approx.f32 %0, %1;" : "=f"(y) : "f"(x)); return y; }
__device__ __forceinline__ float rcp_fast(float x) { float y; asm("rcp.approx.ftz.f32 %0, %1;" : "=f"(y) : "f"(x)); return y; }
__device__ __forceinline__ float rsq_fast(float x) { float y; asm("rsqrt.approx.ftz.f32 %0, %1;" : "=f"(y) : "f"(x)); return y; }
__device__ __forceinline__ float ex2(float x) { float y; asm("ex2.approx.ftz.f32 %0, %1;" : "=f"(y) : "f"(x)); return y; }
__device__ __forceinline__ float qsum(float v) { v += __shfl_xor_sync(~0u, v, 1); v += __shfl_xor_sync(~0u, v, 2); return v; }
__device__ __forceinline__ float qmax(float v) { v = fmaxf(v, __shfl_xor_sync(~0u, v, 1)); v = fmaxf(v, __shfl_xor_sync(~0u, v, 2)); return v; }
__device__ __forceinline__ void stg32(void* p, uint32_t v) { asm volatile("st.global.u32 [%0], %1;" ::"l"(p), "r"(v) : "memory"); }
__device__ __forceinline__ void stg128(void* p, uint32_t a, uint32_t b, uint32_t c, uint32_t d) { asm volatile("st.global.v4.u32 [%0], {%1,%2,%3,%4};" ::"l"(p), "r"(a), "r"(b), "r"(c), "r"(d) : "memory"); }
__device__ __forceinline__ uint32_t ldcg32(const void* p) { uint32_t v; asm volatile("ld.global.L1::no_allocate.u32 %0, [%1];" : "=r"(v) : "l"(p) : "memory"); return v; }
__device__ __forceinline__ void stg128_if(bool c, void* p, uint32_t a, uint32_t b, uint32_t cc, uint32_t d) {
  asm volatile("{\n.reg .pred P;\nsetp.ne.u32 P, %5, 0;\n@P st.global.v4.u32 [%0], {%1,%2,%3,%4};\n}" ::"l"(p), "r"(a), "r"(b), "r"(cc), "r"(d), "r"((uint32_t)c) : "memory");
}
__device__ __forceinline__ uint2 lds64(uint32_t a) { uint2 v; asm volatile("ld.shared.v2.u32 {%0,%1}, [%2];" : "=r"(v.x), "=r"(v.y) : "r"(a) : "memory"); return v; }
__device__ __forceinline__ uint4 ldcg128(const void* p) { uint4 v; asm volatile("ld.global.cg.v4.u32 {%0,%1,%2,%3}, [%4];" : "=r"(v.x), "=r"(v.y), "=r"(v.z), "=r"(v.w) : "l"(p) : "memory"); return v; }
__device__ __forceinline__ uint32_t ldnc16(const void* p) { uint16_t v; asm volatile("ld.global.nc.u16 %0, [%1];" : "=h"(v) : "l"(p)); return v; }
__device__ __forceinline__ uint4 ldnc128(const void* p) { uint4 v; asm volatile("ld.global.nc.v4.u32 {%0,%1,%2,%3}, [%4];" : "=r"(v.x), "=r"(v.y), "=r"(v.z), "=r"(v.w) : "l"(p)); return v; }
__device__ __forceinline__ void cp_async16(uint32_t dst, const void* src) { asm volatile("cp.async.cg.shared.global [%0], [%1], 16;" ::"r"(dst), "l"(src) : "memory"); }
__device__ __forceinline__ uint32_t hsub2(uint32_t a, uint32_t b) { uint32_t d; asm("sub.rn.bf16x2 %0, %1, %2;" : "=r"(d) : "r"(a), "r"(b)); return d; }
__device__ __forceinline__ void stg32_if(bool c, void* p, uint32_t v) {
  asm volatile("{\n.reg .pred P;\nsetp.ne.u32 P, %2, 0;\n@P st.global.u32 [%0], %1;\n}" ::"l"(p), "r"(v), "r"((uint32_t)c) : "memory");
}
__device__ __forceinline__ float wsum(float v) { for (int o = 16; o; o >>= 1) v += __shfl_xor_sync(~0u, v, o); return v; }
__device__ __forceinline__ uint32_t hmul2(uint32_t a, uint32_t b) { uint32_t d; asm("mul.rn.bf16x2 %0, %1, %2;" : "=r"(d) : "r"(a), "r"(b)); return d; }
__device__ __forceinline__ void sts32(uint32_t a, uint32_t v) { asm volatile("st.shared.u32 [%0], %1;" ::"r"(a), "r"(v) : "memory"); }
__device__ __forceinline__ uint32_t lds32(uint32_t a) { uint32_t v; asm volatile("ld.shared.u32 %0, [%1];" : "=r"(v) : "r"(a) : "memory"); return v; }
__device__ __forceinline__ void sts128(uint32_t a, uint32_t x, uint32_t y, uint32_t z, uint32_t w) { asm volatile("st.shared.v4.u32 [%0], {%1,%2,%3,%4};" ::"r"(a), "r"(x), "r"(y), "r"(z), "r"(w) : "memory"); }
__device__ __forceinline__ uint4 lds128(uint32_t a) { uint4 v; asm volatile("ld.shared.v4.u32 {%0,%1,%2,%3}, [%4];" : "=r"(v.x), "=r"(v.y), "=r"(v.z), "=r"(v.w) : "r"(a) : "memory"); return v; }
__device__ __forceinline__ void ll_st64(uint2* p, uint32_t v, uint32_t tag) {
  asm volatile("{\n.reg .b64 r;\nmov.b64 r, {%1,%2};\nst.relaxed.gpu.global.b64 [%0], r;\n}" ::"l"(p), "r"(v), "r"(tag) : "memory");
}
__device__ __forceinline__ uint2 ll_ld64(const uint2* p) {
  uint2 v; asm volatile("{\n.reg .b64 r;\nld.relaxed.gpu.global.b64 r, [%2];\nmov.b64 {%0,%1}, r;\n}" : "=r"(v.x), "=r"(v.y) : "l"(p) : "memory"); return v;
}
__device__ __forceinline__ void ll_st128(uint4* p, float a, float b, uint32_t tag, float c = 0.f) {
  asm volatile("{\n.reg .b128 r;\n.reg .b64 lo, hi;\nmov.b64 lo, {%1,%2};\nmov.b64 hi, {%3,%4};\nmov.b128 r, {lo, hi};\nst.relaxed.gpu.global.b128 [%0], r;\n}" ::"l"(p), "r"(__float_as_uint(a)), "r"(__float_as_uint(b)), "r"(tag), "r"(__float_as_uint(c)) : "memory");
}
__device__ __forceinline__ uint4 ll_ld128g(const void* p) {
  uint4 v; asm volatile("{\n.reg .b128 r;\n.reg .b64 lo, hi;\nld.relaxed.gpu.b128 r, [%4];\nmov.b128 {lo, hi}, r;\nmov.b64 {%0,%1}, lo;\nmov.b64 {%2,%3}, hi;\n}" : "=r"(v.x), "=r"(v.y), "=r"(v.z), "=r"(v.w) : "l"(p) : "memory"); return v;
}
__device__ __forceinline__ uint4 ll_ld128(const uint4* p) {
  uint4 v; asm volatile("{\n.reg .b128 r;\n.reg .b64 lo, hi;\nld.relaxed.gpu.global.b128 r, [%4];\nmov.b128 {lo, hi}, r;\nmov.b64 {%0,%1}, lo;\nmov.b64 {%2,%3}, hi;\n}" : "=r"(v.x), "=r"(v.y), "=r"(v.z), "=r"(v.w) : "l"(p) : "memory"); return v;
}
__device__ __forceinline__ void publish_p(uint32_t el, uint32_t* f) {
  asm volatile("{\n.reg .pred P;\nsetp.ne.u32 P, %1, 0;\n@P cp.async.bulk.commit_group;\n@P cp.async.bulk.wait_group 0;\n@P red.release.gpu.global.add.u32 [%0], 1;\n}" ::"l"(f), "r"(el) : "memory");
}
__device__ __forceinline__ void stsm4(uint32_t addr, uint32_t a, uint32_t b, uint32_t c, uint32_t d) {
  asm volatile("stmatrix.sync.aligned.m8n8.x4.shared.b16 [%0], {%1,%2,%3,%4};" ::"r"(addr), "r"(a), "r"(b), "r"(c), "r"(d) : "memory");
}
__device__ __forceinline__ void sts64(uint32_t a, uint32_t x, uint32_t y) { asm volatile("st.shared.v2.u32 [%0], {%1,%2};" ::"r"(a), "r"(x), "r"(y) : "memory"); }
__device__ __forceinline__ void ll_st128_if(bool on, uint4* p, float a, float b, uint32_t tag) {
  asm volatile("{\n.reg .pred P;\n.reg .b128 r;\n.reg .b64 lo, hi;\nsetp.ne.u32 P, %4, 0;\nmov.b64 lo, {%1,%2};\nmov.b64 hi, {%3,%3};\nmov.b128 r, {lo, hi};\n@P st.relaxed.gpu.global.b128 [%0], r;\n}" ::"l"(p), "r"(__float_as_uint(a)), "r"(__float_as_uint(b)), "r"(tag), "r"((uint32_t)on) : "memory");
}
__device__ __forceinline__ uint4 ldnc128_if(bool c, const void* p) {
  uint4 v = make_uint4(0u, 0u, 0u, 0u);
  asm volatile("{\n.reg .pred P;\nsetp.ne.u32 P, %5, 0;\n@P ld.global.nc.v4.u32 {%0,%1,%2,%3}, [%4];\n}" : "+r"(v.x), "+r"(v.y), "+r"(v.z), "+r"(v.w) : "l"(p), "r"((uint32_t)c));
  return v;
}
__device__ __forceinline__ uint32_t hfma2(uint32_t a, uint32_t b, uint32_t c) { uint32_t d; asm("fma.rn.bf16x2 %0, %1, %2, %3;" : "=r"(d) : "r"(a), "r"(b), "r"(c)); return d; }
__device__ __forceinline__ float2 lds64f(uint32_t a) { float2 v; asm volatile("ld.shared.v2.f32 {%0,%1}, [%2];" : "=f"(v.x), "=f"(v.y) : "r"(a) : "memory"); return v; }
#define TRC(cond, role, idx) do {} while (0)
#define TRV(role, idx, v) do {} while (0)
#define TRVI(c, role, idx, v) do {} while (0)

#define ACLK_INIT do {} while (0)
#define ACLK(i) do {} while (0)
#define ACLK_OUT do {} while (0)
#define QCLK(i) do {} while (0)
#define PH 1
#define RCLK(i) do {} while (0)
#define RCLK_INIT do {} while (0)
#define RCLK_OUT do {} while (0)
#define SCLK(i) do {} while (0)
#define SCLK2(i) do {} while (0)
#define SCLK3(i) do {} while (0)
#define PL 1
#define PCLK(i) do {} while (0)
#define PQ 1
#define CLK_INIT do {} while (0)
#define CLK(i) do {} while (0)
#define CLK_OUT do {} while (0)

__device__ __forceinline__ void wgmma_ss_n216(float* d, uint64_t da, uint64_t db, int scaleD) {
  asm volatile("{\n.reg .pred p;\nsetp.ne.b32 p, %110, 0;\nwgmma.mma_async.sync.aligned.m64n216k16.f32.bf16.bf16 "
    "{%0,%1,%2,%3,%4,%5,%6,%7,%8,%9,%10,%11,%12,%13,%14,%15,%16,%17,%18,%19,%20,%21,%22,%23,%24,%25,%26,%27,%28,%29,%30,%31,%32,%33,%34,%35,%36,%37,%38,%39,%40,%41,%42,%43,%44,%45,%46,%47,%48,%49,%50,%51,%52,%53,%54,%55,%56,%57,%58,%59,%60,%61,%62,%63,%64,%65,%66,%67,%68,%69,%70,%71,%72,%73,%74,%75,%76,%77,%78,%79,%80,%81,%82,%83,%84,%85,%86,%87,%88,%89,%90,%91,%92,%93,%94,%95,%96,%97,%98,%99,%100,%101,%102,%103,%104,%105,%106,%107}, "
    "%108, %109, p, 1, 1, 0, 1;\n}\n"
    : "+f"(d[0]), "+f"(d[1]), "+f"(d[2]), "+f"(d[3]), "+f"(d[4]), "+f"(d[5]), "+f"(d[6]), "+f"(d[7]), "+f"(d[8]), "+f"(d[9]), "+f"(d[10]), "+f"(d[11]), "+f"(d[12]), "+f"(d[13]), "+f"(d[14]), "+f"(d[15]), "+f"(d[16]), "+f"(d[17]), "+f"(d[18]), "+f"(d[19]), "+f"(d[20]), "+f"(d[21]), "+f"(d[22]), "+f"(d[23]), "+f"(d[24]), "+f"(d[25]), "+f"(d[26]), "+f"(d[27]), "+f"(d[28]), "+f"(d[29]), "+f"(d[30]), "+f"(d[31]), "+f"(d[32]), "+f"(d[33]), "+f"(d[34]), "+f"(d[35]), "+f"(d[36]), "+f"(d[37]), "+f"(d[38]), "+f"(d[39]), "+f"(d[40]), "+f"(d[41]), "+f"(d[42]), "+f"(d[43]), "+f"(d[44]), "+f"(d[45]), "+f"(d[46]), "+f"(d[47]), "+f"(d[48]), "+f"(d[49]), "+f"(d[50]), "+f"(d[51]), "+f"(d[52]), "+f"(d[53]), "+f"(d[54]), "+f"(d[55]), "+f"(d[56]), "+f"(d[57]), "+f"(d[58]), "+f"(d[59]), "+f"(d[60]), "+f"(d[61]), "+f"(d[62]), "+f"(d[63]), "+f"(d[64]), "+f"(d[65]), "+f"(d[66]), "+f"(d[67]), "+f"(d[68]), "+f"(d[69]), "+f"(d[70]), "+f"(d[71]), "+f"(d[72]), "+f"(d[73]), "+f"(d[74]), "+f"(d[75]), "+f"(d[76]), "+f"(d[77]), "+f"(d[78]), "+f"(d[79]), "+f"(d[80]), "+f"(d[81]), "+f"(d[82]), "+f"(d[83]), "+f"(d[84]), "+f"(d[85]), "+f"(d[86]), "+f"(d[87]), "+f"(d[88]), "+f"(d[89]), "+f"(d[90]), "+f"(d[91]), "+f"(d[92]), "+f"(d[93]), "+f"(d[94]), "+f"(d[95]), "+f"(d[96]), "+f"(d[97]), "+f"(d[98]), "+f"(d[99]), "+f"(d[100]), "+f"(d[101]), "+f"(d[102]), "+f"(d[103]), "+f"(d[104]), "+f"(d[105]), "+f"(d[106]), "+f"(d[107])
    : "l"(da), "l"(db), "r"(scaleD));
}
__device__ __forceinline__ void wgmma_ss_n72(float* d, uint64_t da, uint64_t db, int scaleD) {
  asm volatile("{\n.reg .pred p;\nsetp.ne.b32 p, %38, 0;\nwgmma.mma_async.sync.aligned.m64n72k16.f32.bf16.bf16 "
    "{%0,%1,%2,%3,%4,%5,%6,%7,%8,%9,%10,%11,%12,%13,%14,%15,%16,%17,%18,%19,%20,%21,%22,%23,%24,%25,%26,%27,%28,%29,%30,%31,%32,%33,%34,%35}, "
    "%36, %37, p, 1, 1, 0, 1;\n}\n"
    : "+f"(d[0]), "+f"(d[1]), "+f"(d[2]), "+f"(d[3]), "+f"(d[4]), "+f"(d[5]), "+f"(d[6]), "+f"(d[7]), "+f"(d[8]), "+f"(d[9]), "+f"(d[10]), "+f"(d[11]), "+f"(d[12]), "+f"(d[13]), "+f"(d[14]), "+f"(d[15]), "+f"(d[16]), "+f"(d[17]), "+f"(d[18]), "+f"(d[19]), "+f"(d[20]), "+f"(d[21]), "+f"(d[22]), "+f"(d[23]), "+f"(d[24]), "+f"(d[25]), "+f"(d[26]), "+f"(d[27]), "+f"(d[28]), "+f"(d[29]), "+f"(d[30]), "+f"(d[31]), "+f"(d[32]), "+f"(d[33]), "+f"(d[34]), "+f"(d[35])
    : "l"(da), "l"(db), "r"(scaleD));
}
__device__ __forceinline__ void wgmma_ss_n128(float* d, uint64_t da, uint64_t db, int scaleD) {
  asm volatile("{\n.reg .pred p;\nsetp.ne.b32 p, %66, 0;\nwgmma.mma_async.sync.aligned.m64n128k16.f32.bf16.bf16 "
    "{%0,%1,%2,%3,%4,%5,%6,%7,%8,%9,%10,%11,%12,%13,%14,%15,%16,%17,%18,%19,%20,%21,%22,%23,%24,%25,%26,%27,%28,%29,%30,%31,%32,%33,%34,%35,%36,%37,%38,%39,%40,%41,%42,%43,%44,%45,%46,%47,%48,%49,%50,%51,%52,%53,%54,%55,%56,%57,%58,%59,%60,%61,%62,%63}, "
    "%64, %65, p, 1, 1, 0, 1;\n}\n"
    : "+f"(d[0]), "+f"(d[1]), "+f"(d[2]), "+f"(d[3]), "+f"(d[4]), "+f"(d[5]), "+f"(d[6]), "+f"(d[7]), "+f"(d[8]), "+f"(d[9]), "+f"(d[10]), "+f"(d[11]), "+f"(d[12]), "+f"(d[13]), "+f"(d[14]), "+f"(d[15]), "+f"(d[16]), "+f"(d[17]), "+f"(d[18]), "+f"(d[19]), "+f"(d[20]), "+f"(d[21]), "+f"(d[22]), "+f"(d[23]), "+f"(d[24]), "+f"(d[25]), "+f"(d[26]), "+f"(d[27]), "+f"(d[28]), "+f"(d[29]), "+f"(d[30]), "+f"(d[31]), "+f"(d[32]), "+f"(d[33]), "+f"(d[34]), "+f"(d[35]), "+f"(d[36]), "+f"(d[37]), "+f"(d[38]), "+f"(d[39]), "+f"(d[40]), "+f"(d[41]), "+f"(d[42]), "+f"(d[43]), "+f"(d[44]), "+f"(d[45]), "+f"(d[46]), "+f"(d[47]), "+f"(d[48]), "+f"(d[49]), "+f"(d[50]), "+f"(d[51]), "+f"(d[52]), "+f"(d[53]), "+f"(d[54]), "+f"(d[55]), "+f"(d[56]), "+f"(d[57]), "+f"(d[58]), "+f"(d[59]), "+f"(d[60]), "+f"(d[61]), "+f"(d[62]), "+f"(d[63])
    : "l"(da), "l"(db), "r"(scaleD));
}
__device__ __forceinline__ void wgmma_ss_n160(float* d, uint64_t da, uint64_t db, int scaleD) {
  asm volatile("{\n.reg .pred p;\nsetp.ne.b32 p, %82, 0;\nwgmma.mma_async.sync.aligned.m64n160k16.f32.bf16.bf16 "
    "{%0,%1,%2,%3,%4,%5,%6,%7,%8,%9,%10,%11,%12,%13,%14,%15,%16,%17,%18,%19,%20,%21,%22,%23,%24,%25,%26,%27,%28,%29,%30,%31,%32,%33,%34,%35,%36,%37,%38,%39,%40,%41,%42,%43,%44,%45,%46,%47,%48,%49,%50,%51,%52,%53,%54,%55,%56,%57,%58,%59,%60,%61,%62,%63,%64,%65,%66,%67,%68,%69,%70,%71,%72,%73,%74,%75,%76,%77,%78,%79}, "
    "%80, %81, p, 1, 1, 0, 1;\n}\n"
    : "+f"(d[0]), "+f"(d[1]), "+f"(d[2]), "+f"(d[3]), "+f"(d[4]), "+f"(d[5]), "+f"(d[6]), "+f"(d[7]), "+f"(d[8]), "+f"(d[9]), "+f"(d[10]), "+f"(d[11]), "+f"(d[12]), "+f"(d[13]), "+f"(d[14]), "+f"(d[15]), "+f"(d[16]), "+f"(d[17]), "+f"(d[18]), "+f"(d[19]), "+f"(d[20]), "+f"(d[21]), "+f"(d[22]), "+f"(d[23]), "+f"(d[24]), "+f"(d[25]), "+f"(d[26]), "+f"(d[27]), "+f"(d[28]), "+f"(d[29]), "+f"(d[30]), "+f"(d[31]), "+f"(d[32]), "+f"(d[33]), "+f"(d[34]), "+f"(d[35]), "+f"(d[36]), "+f"(d[37]), "+f"(d[38]), "+f"(d[39]), "+f"(d[40]), "+f"(d[41]), "+f"(d[42]), "+f"(d[43]), "+f"(d[44]), "+f"(d[45]), "+f"(d[46]), "+f"(d[47]), "+f"(d[48]), "+f"(d[49]), "+f"(d[50]), "+f"(d[51]), "+f"(d[52]), "+f"(d[53]), "+f"(d[54]), "+f"(d[55]), "+f"(d[56]), "+f"(d[57]), "+f"(d[58]), "+f"(d[59]), "+f"(d[60]), "+f"(d[61]), "+f"(d[62]), "+f"(d[63]), "+f"(d[64]), "+f"(d[65]), "+f"(d[66]), "+f"(d[67]), "+f"(d[68]), "+f"(d[69]), "+f"(d[70]), "+f"(d[71]), "+f"(d[72]), "+f"(d[73]), "+f"(d[74]), "+f"(d[75]), "+f"(d[76]), "+f"(d[77]), "+f"(d[78]), "+f"(d[79])
    : "l"(da), "l"(db), "r"(scaleD));
}
__device__ __forceinline__ void wgmma_rs_n144(float* d, const uint32_t* a, uint64_t db, int scaleD) {
  asm volatile("{\n.reg .pred p;\nsetp.ne.b32 p, %77, 0;\nwgmma.mma_async.sync.aligned.m64n144k16.f32.bf16.bf16 "
    "{%0,%1,%2,%3,%4,%5,%6,%7,%8,%9,%10,%11,%12,%13,%14,%15,%16,%17,%18,%19,%20,%21,%22,%23,%24,%25,%26,%27,%28,%29,%30,%31,%32,%33,%34,%35,%36,%37,%38,%39,%40,%41,%42,%43,%44,%45,%46,%47,%48,%49,%50,%51,%52,%53,%54,%55,%56,%57,%58,%59,%60,%61,%62,%63,%64,%65,%66,%67,%68,%69,%70,%71}, "
    "{%72,%73,%74,%75}, %76, p, 1, 1, 1;\n}\n"
    : "+f"(d[0]), "+f"(d[1]), "+f"(d[2]), "+f"(d[3]), "+f"(d[4]), "+f"(d[5]), "+f"(d[6]), "+f"(d[7]), "+f"(d[8]), "+f"(d[9]), "+f"(d[10]), "+f"(d[11]), "+f"(d[12]), "+f"(d[13]), "+f"(d[14]), "+f"(d[15]), "+f"(d[16]), "+f"(d[17]), "+f"(d[18]), "+f"(d[19]), "+f"(d[20]), "+f"(d[21]), "+f"(d[22]), "+f"(d[23]), "+f"(d[24]), "+f"(d[25]), "+f"(d[26]), "+f"(d[27]), "+f"(d[28]), "+f"(d[29]), "+f"(d[30]), "+f"(d[31]), "+f"(d[32]), "+f"(d[33]), "+f"(d[34]), "+f"(d[35]), "+f"(d[36]), "+f"(d[37]), "+f"(d[38]), "+f"(d[39]), "+f"(d[40]), "+f"(d[41]), "+f"(d[42]), "+f"(d[43]), "+f"(d[44]), "+f"(d[45]), "+f"(d[46]), "+f"(d[47]), "+f"(d[48]), "+f"(d[49]), "+f"(d[50]), "+f"(d[51]), "+f"(d[52]), "+f"(d[53]), "+f"(d[54]), "+f"(d[55]), "+f"(d[56]), "+f"(d[57]), "+f"(d[58]), "+f"(d[59]), "+f"(d[60]), "+f"(d[61]), "+f"(d[62]), "+f"(d[63]), "+f"(d[64]), "+f"(d[65]), "+f"(d[66]), "+f"(d[67]), "+f"(d[68]), "+f"(d[69]), "+f"(d[70]), "+f"(d[71])
    : "r"(a[0]), "r"(a[1]), "r"(a[2]), "r"(a[3]), "l"(db), "r"(scaleD));
}
__device__ __forceinline__ void wgmma_rs_n64(float* d, const uint32_t* a, uint64_t db, int scaleD) {
  asm volatile("{\n.reg .pred p;\nsetp.ne.b32 p, %37, 0;\nwgmma.mma_async.sync.aligned.m64n64k16.f32.bf16.bf16 "
    "{%0,%1,%2,%3,%4,%5,%6,%7,%8,%9,%10,%11,%12,%13,%14,%15,%16,%17,%18,%19,%20,%21,%22,%23,%24,%25,%26,%27,%28,%29,%30,%31}, "
    "{%32,%33,%34,%35}, %36, p, 1, 1, 1;\n}\n"
    : "+f"(d[0]), "+f"(d[1]), "+f"(d[2]), "+f"(d[3]), "+f"(d[4]), "+f"(d[5]), "+f"(d[6]), "+f"(d[7]), "+f"(d[8]), "+f"(d[9]), "+f"(d[10]), "+f"(d[11]), "+f"(d[12]), "+f"(d[13]), "+f"(d[14]), "+f"(d[15]), "+f"(d[16]), "+f"(d[17]), "+f"(d[18]), "+f"(d[19]), "+f"(d[20]), "+f"(d[21]), "+f"(d[22]), "+f"(d[23]), "+f"(d[24]), "+f"(d[25]), "+f"(d[26]), "+f"(d[27]), "+f"(d[28]), "+f"(d[29]), "+f"(d[30]), "+f"(d[31])
    : "r"(a[0]), "r"(a[1]), "r"(a[2]), "r"(a[3]), "l"(db), "r"(scaleD));
}

template <int V> struct Int { static constexpr int value = V; };
struct Cur {
  uint32_t s, ph;
  __device__ __forceinline__ void next() { if (++s == NST) { s = 0; ph ^= 1; } }
};

__device__ __forceinline__ uint32_t o_place(uint32_t w, uint32_t e) { return (((w ? 0xd5310u : 0xa8d57u) >> (4 * e)) & 15) * 8192 + 90112; }
#define z1_block(rb, w, j) (Q.Z + ((rb) * 16 + (w) * 8 + (j)) * ZB)
#define xn_block(hw) (Q.Z + (512 + (hw) * 2) * ZB)
#define z2_block(kb, j) (Q.Z + (256 + (kb) * 8 + (j)) * ZB)
template <int N> __device__ __forceinline__ void pause(uint32_t zero) {
  if (N <= 0) return;
  uint32_t z = clock() + threadIdx.x;
  do {
#pragma unroll (N > 8 ? 1 : 8)
    for (int i = 0; i < N; i++) asm volatile("shfl.sync.bfly.b32 %0, %0, 1, 0x1f, 0xffffffff;" : "+r"(z)::"memory");
  } while (__any_sync(~0u, z & zero));
}

__global__ void __cluster_dims__(2, 1, 1) __launch_bounds__(384, 1) mega_kernel(const Ptrs Q, const __grid_constant__ Params P) {
  extern __shared__ __align__(1024) uint8_t smem_raw[];
  const uint32_t sb = smem_u32(smem_raw);
  const uint32_t bars = sb + SM_BAR;
  const int tid = threadIdx.x;
  int lane = tid & 31;
  const int wid = __shfl_sync(~0u, tid >> 5, 0);
  const int cl = blockIdx.x >> 1;
  const int bid = (cl < 4 ? cl * 8 + 32 : cl - 4 + (max(cl - 29, 0) * 37 >> 8)) * 2 + (blockIdx.x & 1);
  const int rb = bid & 15, j = bid >> 4;
  uint4 wv[5];
  {
    const int n8 = min(tid >> 3, 26), part = n8 / 9;
    const uint8_t* src = (const uint8_t*)Q.wqkv + (8 * rb + (tid & 7)) * (3 * DM * 2) + (part * (DM - 72) + 72 * j + 8 * n8) * 2;
#pragma unroll
    for (int u = 0; u < 5; u++) wv[u] = ldnc128_if(tid < 216 && cl < 64 && (u < 4 || rb < 8), src + u * (128 * 3 * DM * 2));
  }
  if (cl >= 64) return;
  if (wid >= 7 && lane == 0) {
    if (wid < 10) {
#pragma unroll
      for (uint32_t b = 0; b < B_AD / 3; b += 8) mbar_init(bars + (wid - 7) * (B_AD / 3) + b, 1);
    } else if (wid == 10) {
#pragma unroll
      for (uint32_t b = B_AD; b < B_EVT; b += 8) mbar_init(bars + b, b < B_LAG ? 2 : 4);
    } else {
#pragma unroll
      for (uint32_t b = B_EVT; b < 1024; b += 8) if (b < B_OFF || b >= B_IMG) mbar_init(bars + b, b < B_IMG ? 4 : b < B_EMPTY ? 8 : 16);
    }
    asm volatile("fence.mbarrier_init.release.cluster;" ::: "memory");
  }
  __syncthreads();

  if (wid >= 8) {
    reg_dealloc<56>();
    const uint32_t el = elect_one();
    const uint64_t pol = policy_evict_first();
    uint32_t* const fj = Q.flags + FJ + j * 32;
    if (wid == 8) {
      if (el) { prefetch_map(&P.wsp); prefetch_map(&P.winb[j & 1]); prefetch_map(&P.wins); prefetch_map(&P.wout); prefetch_map(&P.act[1]); prefetch_map(&P.res[0]); prefetch_map(&P.res[1]); prefetch_map(&P.row[1]); }
      const uint32_t epoch = ldcg32(fj + FJ_EP + rb);
      Cur c{0, 1};
      const uint32_t rk = bid & 1;
      uint32_t st, full;
      auto slot = [&](uint32_t bytes) {
        st = sb + c.s * ST_BYTES; full = bars + B_FULL + c.s * 8;
        mbar_wait(full, c.ph);
        expect_tx_p(el, full, bytes);
        mbar_wait(full - B_FULL + B_EMPTY, c.ph);
      };
#pragma unroll 1
      for (int L = 0; L < 2; L++) {
#pragma unroll 1
        for (int i = 0; i < 9; i++) {
          if (L == 0 && i == 0) {
            flag_wait(fj + FJ_WQ, (epoch + 1) * 16);
            fence_async_g();
            TRC(el, 2, 45);
          }
          slot(27648);
          bulk_mc_h(el, st + ST_B + rk * 13824, Q.WQ + j * WQ_SL + i * 27648 + rk * 13824, 13824, full, EF(0), pol);
          c.next();
        }
        if (L == 0) {
          flag_wait(fj + FJ_WO, (epoch + 1) * 16);
          fence_async_g();
          TRC(el, 2, 46);
        }
#pragma unroll 1
        while (c.s) {
          mbar_wait(bars + B_EMPTY + c.s * 8, c.ph);
          if (el) { mbar_arrive(bars + B_FULL + c.s * 8); asm volatile("mbarrier.arrive.shared::cta.b64 _, [%0], 16;" ::"r"(bars + B_EMPTY + c.s * 8) : "memory"); }
          c.next();
        }
        expect_tx_p(el, bars + B_WF, WO_SL);
        mbar_wait(bars + B_EMPTY, c.ph);
        mbar_wait(bars + B_EMPTY + 8, c.ph);
        bulk_mc_h(el, sb + rk * (WO_SL / 2), Q.WO + j * WO_SL + rk * (WO_SL / 2), WO_SL / 2, bars + B_WF, EF(1), pol);
#pragma unroll 1
        for (int r = 0; r < 10; r++) {
          const bool big = r >= 2 && r < 8;
          const int a0 = (r < 5 ? 36 : 0) + ((9 * j) >> 1) + (big ? 2 - 2 * (j & 1) : 3 * (j & 1) + rk), ks = big ? 32 : 48;
          int k = big ? (r < 5 ? r - 2 : r - 5) * 192 + rk * 16 : (r & 1) * 288;
          const CUtensorMap* m = big ? &P.winb[j & 1] : &P.wins;
          const uint32_t dst = sb + SM_B3 + rk * 6144;
#pragma unroll
          for (int p = 0; p < 6; p++, k += ks) {
            if (!(p & 3) && r == 0) mbar_wait(bars + B_XD + p * 2, L);
            if (p) mbar_wait_c(bars + B_E3 + p * 8, ~r & 1); else mbar_wait(bars + B_E3, ~r & 1);
            expect_tx_p(el, bars + B_F3 + p * 8, 12288);
            tma3d_mc_h(el, dst + p * 12288, m, 0, k, a0, bars + B_F3 + p * 8, EF(2), pol);
          }
        }
        TRC(el, 2, L * 16 + 6);
        mbar_wait(bars + B_ZOK, L);
        fence_async_g();
        TRC(el, 2, L * 16 + 7);
        const uint8_t* src = z2_block(0, j) + rk * 18432;
#pragma unroll 1
        for (int r = 0; r < 8; r++) {
          const int k = (r & 3) * 512 + (r >> 2) * 64;
#pragma unroll
          for (int p = 0; p < 4; p++, src += 8 * ZB) {
            if ((p == 1 || p == 2) && r == 0) mbar_wait(bars + B_E3 - 8 + p * 24, 1);
            mbar_wait_c(bars + B_AD + p * 8, ~r & 1);
            if (p) mbar_wait_c(bars + B_EMPTY + p * 8, c.ph); else mbar_wait(bars + B_EMPTY, c.ph);
            expect_tx_p(el, bars + B_FULL + p * 8, ST_BYTES);
            bulk_mc_h(el, sb + p * ST_BYTES + ST_B + rk * 18432, src, 18432, bars + B_FULL + p * 8, EF(4), pol);
            tma3d_h(el, sb + p * ST_BYTES, &P.wsp, k + p * 128, rb * 64, 0, bars + B_FULL + p * 8, EF(3), pol);
          }
          c.ph ^= 1;
        }
        mbar_wait(bars + B_Z1, L);
        fence_async_g();
#pragma unroll 1
        for (int i = 0; i < 11; i++) {
          const int cb = i - 2 + j;
          if (i < 4) mbar_wait(bars + B_AD + c.s * 8, 1);
          slot(ZB);
          if (i < 2) bulk_load_h(el, st + ST_B, z1_block(rb, i, j), ZB, full, true, pol);
          else tma2d_mc_h(el, st + ST_B + rk * 18432, &P.wout, (cb >= 9 ? cb - 9 : cb) * 64, 288 * j + rk * 144, full, EF(5), pol);
          c.next();
        }
      }
    } else if (wid < 11) {
      uint32_t id = bid * 2 + wid - 9;
#define AGENT_IDS asm volatile("" : "+r"(lane), "+r"(id)); const uint32_t w = id & 1, hw = id & 31, rb = hw >> 1, j = id >> 5, ev = bars + B_EVT + w * EV_N * 8; \
      uint32_t* const fr = Q.flags + hw * 32; uint32_t* const fj = Q.flags + FJ + j * 32; (void)fr; (void)fj; (void)ev; (void)rb
      uint32_t t8 = 0;
      Cur c{0, 1};
#pragma unroll 1
      for (int L = 0; L < 2; L++) {
        if (L) {
          AGENT_IDS;
          const uint32_t full = bars + B_FULLA + w * 32 + c.s * 8, dst = sb + c.s * ST_BYTES + w * 8192;
          expect_tx_p(el, full, 8192);
          mbar_wait_c(ev + EV_PT * 8, 1);
          TRC(el, 3, w * 32 + 16);
          flag_release_p(el, fr + FR_X2);
          TRC(el, 3, w * 32 + 17);
          mbar_wait_c(bars + B_EMPTY + c.s * 8, c.ph);
          flag_wait(fr + FR_X2, t8);
          fence_async_g();
          tma3d_h(el, dst, &P.act[1], 0, rb * 64, w, full, false, pol);
          c.next();
          TRC(el, 3, w * 32 + 18);
        }
#pragma unroll 1
        for (int i = L; i < 9; i++) {
          AGENT_IDS;
          const uint32_t full = bars + B_FULLA + w * 32 + c.s * 8, dst = sb + c.s * ST_BYTES + w * 8192;
          if (L == 0 && i == AEP) t8 = (ldcg32(fr + FR_EP + j) + 1) * 8;
          mbar_wait_c(bars + B_EMPTY + c.s * 8, c.ph);
          expect_tx_p(el, full, 8192);
          tma3d_h(el, dst, &P.act[L], i * 64, rb * 64, w, full, false, pol);
          c.next();
          if (i == PZI || i == PZI + 1) {
            uint8_t* d = (i == PZI ? xn_block(hw) : z1_block(rb, 0, 0) + w * 4608) + j * 9216 + lane * 16;
#pragma unroll 1
            for (int u = i == PZI ? 0 : 3; u < 6; u++, d += 1536) { stg128(d, ~0u, ~0u, ~0u, ~0u); stg128(d + 512, ~0u, ~0u, ~0u, ~0u); stg128(d + 1024, ~0u, ~0u, ~0u, ~0u); }
          }
          if (i == PZI) { stg128(Q.ST1 + (hw * 8 + j) * 32 + lane, ~0u, ~0u, ~0u, ~0u); stg128(Q.ZST + (hw * 8 + j) * 32 + lane, ~0u, ~0u, ~0u, ~0u); }
          if (i == RFI) {
            expect_tx_p(el, bars + B_WT + w * 8, 9216);
            tma3d_h(el, sb + SM_STG + w * 9216, &P.row[L], 0, 3 * w, rb * 64 + 8 * j, bars + B_WT + w * 8, false, pol);
          }
          if (i == 4 && L > w) {
            expect_tx_p(el, bars + B_XRW + 8, 864);
            bulk_load_p(el, sb + 3 * ST_BYTES + SM_CSQ, Q.CSP + (NCTA + (id >> 1)) * 216, 864, bars + B_XRW + 8);
          }
        }
        if (c.s) { c.s = 0; c.ph ^= 1; }
        {
          AGENT_IDS;
          const uint32_t tag = (t8 >> 2) - 1 + L;
          uint4* const xs = Q.XST + hw * 128;
          const uint32_t tab = sb + L * (3 * ST_BYTES) + SM_XST + w * 768 + lane * 8;
          TRC(el, 3, w * 32 + L * 16 + 13);
#pragma unroll 1
          for (int it = 0; it < (1 << 22); it++) {
            const uint4 a = ll_ld128(xs + 2 * lane), b = ll_ld128(xs + 64 + 2 * lane), h = ll_ld128(xs - (rb ? 192 : 0) + 2 * (lane | 24));
            if (__all_sync(~0u, a.z == tag && b.z == tag && h.z == tag)) { sts64(tab, h.x, h.y); sts64(tab + 256, a.x, a.y); sts64(tab + 512, b.x, b.y); break; }
          }
          __syncwarp();
          if (el) mbar_arrive(bars + B_CSQ);
          TRC(el, 3, w * 32 + L * 16 + 14);
          uint32_t* f = Q.flags + rb * 64 + FR_PZ + L;
          flag_release_p(el, f);
          expect_tx_p(el, bars + B_RES + w * 8, 9216);
          tma3d_h(el, sb + SM_STG + w * 9216, &P.res[L], j * 72, hw * 32, 0, bars + B_RES + w * 8, !L, pol);
          pause<FD3>(Q.zero);
          flag_wait(f, t8 * 2);
          fence_async_g();
          TRC(el, 3, w * 32 + L * 16 + 15);
        }
        {
          AGENT_IDS;
          uint32_t* f = Q.flags + rb * 64 + FR_O + L;
#pragma unroll 1
          for (int e = 0; e < 5; e++) {
            const uint32_t nb = e ? 16384 : 8192, full = bars + B_OF + w * 40 + e * 8, dst = sb + o_place(w, e);
            const uint8_t* src = z1_block(rb, w, 0) + (e ? e * 16384 - 8192 : 0);
            expect_tx_p(el, full, nb);
            if (e == 0) {
              mbar_wait_c(ev + EV_O * 8, L);
              TRC(el, 3, w * 32 + L * 16 + 3);
              flag_add_p(el, f);
              flag_wait(f + w * (FR_OL - FR_O), t8 * (2 - w));
              if (w) fence_async_g();
            }
            if (w && (e == 0 || e == 3)) mbar_wait_c(bars + (e ? B_X3 : B_OF + YPACE * 8), L);
            bulk_load_h(el, dst, src, nb, full, EF(6), pol);
            TRC(el && e == 0, 3, w * 32 + L * 16 + 5);
          }
        }
        {
          AGENT_IDS;
          const uint8_t* src = xn_block(hw);
          uint32_t full = bars + B_AF3 + w * 96, dst = sb + w * 6144;
          if (L) flag_wait(fj + FJ_P4, t8 * 4);
          mbar_wait_c(bars + B_XD + 8, L);
          mbar_wait_c(ev + EV_X1 * 8, L);
          TRC(el, 3, w * 32 + L * 16 + 6);
          pause<SDEL>(Q.zero);
#pragma unroll 1
          for (int k = 0; k < 12; k++, src += 6144, dst += 12288, full += 8) {
            expect_tx_p(el, full, 6144);
            if (k >= APACE) mbar_wait_c(full - APACE * 8, L);
            bulk_load_h(el, dst, src, 6144, full, EF(7), pol);
            TRC(el && k == 0, 3, w * 32 + L * 16 + 8);
          }
        }
        if (wid == 10) {
          AGENT_IDS;
          mbar_wait_c(ev - (EV_N - EV_ZN) * 8, L);
          mbar_wait_c(ev + EV_ZN * 8, L);
          asm volatile("fence.release.gpu;" ::: "memory");
          flag_add_p(el, fj + FJ_ZN + L);
          flag_add_p(el, fr - 32 + FR_XR + L);
          pause<FD4>(Q.zero);
          flag_wait(fj + FJ_ZN + L, t8 * 2);
          flag_wait(fr - 32 + FR_XR + L, t8);
          if (el) mbar_arrive(bars + B_ZOK);
        } else if (WPF) {
          AGENT_IDS;
          mbar_wait_c(ev + EV_ZN * 8, L);
          if (el) asm volatile("cp.async.bulk.prefetch.tensor.3d.L2.global [%0, {%1, %2, %3}];" ::"l"(&P.wsp), "r"(j * 128), "r"(rb * 64), "r"(0) : "memory");

        }
        float cv;
        {
        AGENT_IDS;
        cv = (lane & 3) ? 0.f : -blo(ldnc16(Q.b_sp + 128 * rb + 16 * j + 2 * (lane >> 2) + w));
        mbar_wait_c(ev + EV_Z1 * 8, L);
        const uint32_t ro = (w * 64 + 8 * j + (lane >> 2)) * 128, x0 = ((lane & 3) * 2) ^ (lane >> 2);
#pragma unroll 1
        for (int i = 0; i < 32; i++) {
          const bool tail = (i >> 1) == 12;
          const int kb = tail ? i + 6 : i < 24 ? i : i - 2;
          if (!(i & 7)) mbar_wait_c(bars + B_RT + i, L);
          if (i == 24) mbar_wait_c(bars + B_WT + w * 8, 1);
          if (!tail) mbar_wait(bars + B_FULL + c.s * 8, c.ph ^ 1);
          if (i == 3) {
            uint32_t id2 = id;
            asm volatile("" : "+r"(id2));
            expect_tx_p(el, bars + B_WT + w * 8, 3072);
#pragma unroll 1
            for (int r = 0; r < 8; r++)
              bulk_load_p(el, sb + SM_WT + w * 3200 + r * 400, (const uint8_t*)Q.w_sp + (64 * (id2 & 30) + 16 * (id2 >> 5) + 2 * r + w) * (SEQ * 2) + 29 * 128, 384, bars + B_WT + w * 8);
          }
#pragma unroll
          for (int e = 0; e < 2; e++) {
            const uint4 a = lds128(!tail ? sb + c.s * ST_BYTES + ro + ((x0 ^ e) << 4) : sb + SM_WT + w * 3200 + (lane >> 2) * 400 + (i - 24) * 256 + (lane & 3) * 32 + e * 16);
            const uint4 m = lds128(sb + SM_RT + 4096 + kb * 128 + (lane & 3) * 32 + e * 16);
            cv = fmaf(blo(a.x), blo(m.x), fmaf(bhi(a.x), bhi(m.x), fmaf(blo(a.y), blo(m.y), fmaf(bhi(a.y), bhi(m.y), cv))));
            cv = fmaf(blo(a.z), blo(m.z), fmaf(bhi(a.z), bhi(m.z), fmaf(blo(a.w), blo(m.w), fmaf(bhi(a.w), bhi(m.w), cv))));
          }
          if (!tail) {
            __syncwarp();
            if (el) mbar_arrive(bars + B_AD + c.s * 8);
            c.next();
          }
        }
        }
        AGENT_IDS;
        TRC(el, 3, w * 32 + L * 16 + 11);
        asm volatile("" : "+r"(t8));
        const uint32_t tag = (t8 >> 2) - 1 + L;
        cv = qsum(cv);
        uint2* const cs = (uint2*)(Q.XST + hw * 128 + 1);
        if ((lane & 3) == 0) ll_st64(cs + 32 * j + (lane >> 2) * 4, __float_as_uint(cv), tag);
        pause<FD5>(Q.zero);
#pragma unroll 1
        for (int it = 0; it < (1 << 22); it++) {
          const uint2 a = ll_ld64(cs + 4 * lane), b = ll_ld64(cs + 128 + 4 * lane);
          if (__all_sync(~0u, a.y == tag && b.y == tag)) { sts32(sb + SM_CV + w * 256 + lane * 4, a.x); sts32(sb + SM_CV + w * 256 + 128 + lane * 4, b.x); break; }
        }
        __syncwarp();
        if (el) mbar_arrive(bars + B_CV + w * 8);
        TRC(el, 3, w * 32 + L * 16 + 12);
#pragma unroll 1
        for (int kb = 30; kb < 32; kb++) {
          mbar_wait_c(bars + B_FULL + c.s * 8, c.ph ^ 1);
          if (el) mbar_arrive(bars + B_AD + c.s * 8);
          c.next();
        }
        c.ph ^= ((c.s + 11) >> 2) & 1; c.s = (c.s + 11) & 3;
        if (L == 0) {
          mbar_wait_c(ev + EV_PT * 8, 0);
          flag_add_p(el, fj + FJ_P4);
        }
      }
    } else {
      const uint32_t epoch = ldcg32(fj + FJ_EP + rb);
      mbar_wait(bars + B_IMG, 0);
      TRC(el, 2, 41);
      flag_release_p(el, fj + FJ_WQ);
      TRC(el, 2, 42);
#pragma unroll 1
      for (int L = 0; L < 2; L++) {
        float* const csf = Q.CSP + (NCTA + bid) * 216;
        if (L == 0) {
          flag_wait(fj + FJ_WQ, (epoch + 1) * 16);
          fence_async_g();
          expect_tx_p(el, bars + B_XRW, 13824);
          bulk_load_p(el, sb + ST_BYTES + SM_WOI, Q.CSP + j * 16 * 216, 6912, bars + B_XRW);
          bulk_load_p(el, sb + 2 * ST_BYTES + SM_WOI, Q.CSP + (j * 16 + 8) * 216, 6912, bars + B_XRW);
          mbar_wait(bars + B_XRW, 0);
#pragma unroll 1
          for (int f = lane; f < 54; f += 32) {
            float s[4] = {0.f, 0.f, 0.f, 0.f};
#pragma unroll 2
            for (int r = 0; r < 16; r++) {
              const uint4 v = lds128(sb + ST_BYTES + SM_WOI + (r >> 3) * ST_BYTES + (r & 7) * 864 + f * 16);
              s[0] += __uint_as_float(v.x); s[1] += __uint_as_float(v.y); s[2] += __uint_as_float(v.z); s[3] += __uint_as_float(v.w);
            }
            sts128(sb + SM_CSQ + f * 16, __float_as_uint(s[0]), __float_as_uint(s[1]), __float_as_uint(s[2]), __float_as_uint(s[3]));
            stg128(csf + f * 4, __float_as_uint(s[0]), __float_as_uint(s[1]), __float_as_uint(s[2]), __float_as_uint(s[3]));
          }
          __syncwarp();
          if (el) mbar_arrive(bars + B_XRW + 8);
          TRC(el, 2, 43);
          mbar_wait(bars + B_WOI, 0);
          bulk_store_p(el, Q.WO + j * WO_SL + rb * (41 * 128), sb + SM_WOI, (rb < 15 ? 41 : 33) * 128);
          publish_p(el, fj + FJ_WO);
          TRC(el, 2, 44);
          if (el) prefetch_l2((const uint8_t*)Q.w_in + bid * 41472, 41472);
          float o0 = 0.f, o1 = 0.f;
#pragma unroll 1
          for (int u = 0; u < 2; u++) {
            const uint8_t* src = (u ? (const uint8_t*)Q.w_sp + 500 * (SEQ * 2) + 2048 : (const uint8_t*)Q.w_in + 100 * (2 * FH * 2) + FH * 2) + lane * 16;
            const uint4 a = ldnc128(src), b = ldnc128(src + 300 * (2 * FH * 2) + 2048);
            const uint32_t x[8] = {a.x, a.y, a.z, a.w, b.x, b.y, b.z, b.w};
            float sq = 0.f;
#pragma unroll
            for (int e = 0; e < 8; e++) sq = fmaf(blo(x[e]), blo(x[e]), fmaf(bhi(x[e]), bhi(x[e]), sq));
            o0 = o1;
            asm("sqrt.approx.f32 %0, %1;" : "=f"(o1) : "f"(wsum(sq) * (u ? C0S * C0S * SEQ / 512.f : 2.f * GA * GA * DM / 512.f)));
          }
          const uint32_t off = (__float_as_uint(o0) & 0x7f800000u) >> 16 | 0x8000u | OFM;
          const uint32_t c0 = min(max(__float_as_uint(o1) & 0x7f800000u, 0x04000000u), 0x7e000000u) | 0x00400000u;
          if (el) sts128(sb + SM_OFF, off * 0x10001u, c0, __float_as_uint(GB), ((c0 >> 16) - 0x200u) * 0x10001u);
        }
        mbar_wait(bars + B_EVT + EV_O * 8, L);
        mbar_wait(bars + B_EVT + (EV_N + EV_O) * 8, L);
        flag_release_p(el, Q.flags + rb * 64 + FR_OL + L);
#pragma unroll 1
        for (int w = 0; w < 2; w++) {
          mbar_wait(bars + B_EVT + (w * EV_N + EV_XS) * 8, L);
          if (!w) mbar_wait(bars + B_AF3 + 96 + XP0 * 8, L);
          if (el) asm volatile("cp.async.bulk.tensor.3d.global.shared::cta.tile.bulk_group [%0, {%2, %3, %4}], [%1];\ncp.async.bulk.commit_group;\ncp.async.bulk.wait_group.read 0;" ::"l"(&P.res[1]), "r"(sb + SM_STG + 9216), "r"(j * 72), "r"(rb * 64 + w * 32), "r"(0) : "memory");
          __syncwarp();
          if (lane < 2 && !w) mbar_arrive(bars + B_S5);
        }
        sts64(sb + SM_CV + 512 + lane * 8, 0x3f803f80u, 0x3f803f80u);
        fence_async_s();
        __syncwarp();
        if (el) { asm volatile("cp.async.bulk.wait_group 0;" ::: "memory"); mbar_arrive(bars + B_GATE3); }
        const uint32_t tag = epoch * 2 + L + 1;
        asm volatile("" : "+r"(lane));
#pragma unroll 1
        for (int b = 0; b < 8; b++) {
          if (!(b & 3)) {
            const int mb = b >> 2;
            mbar_wait(bars + B_ZS + mb * 8, L);
            pause<ZD1>(Q.zero);
            TRC(el && !mb, 2, L * 16 + 8);
            uint4 v;
#pragma unroll 1
            for (int it = 0; it < (1 << 22); it++) {
              v = ll_ld128(Q.ZST + ((rb * 2 + mb) * 8 + (lane >> 2)) * 32 + 4 * j + (lane & 3));
              if (__all_sync(~0u, max(max(v.x, v.y), max(v.z, v.w)) != ~0u)) break;
            }
            const bool o = lane & 16;
            float ss = __uint_as_float(o ? v.y : v.x) + __shfl_xor_sync(~0u, __uint_as_float(o ? v.x : v.y), 16), sq = __uint_as_float(o ? v.w : v.z) + __shfl_xor_sync(~0u, __uint_as_float(o ? v.z : v.w), 16);
            ss += __shfl_xor_sync(~0u, ss, 4); sq += __shfl_xor_sync(~0u, sq, 4); ss += __shfl_xor_sync(~0u, ss, 8); sq += __shfl_xor_sync(~0u, sq, 8);
            const float mean = ss * (1.f / FH), rs = blo(pack2(rsq_fast(fmaxf(fmaf(sq, 1.f / FH, -mean * mean), 0.f) + 4.f * GA * GA * LN_EPS), 0.f));
            if (!(lane & 12)) ll_st64(Q.RT + (mb * 16 + rb) * 64 + 8 * j + 2 * (lane & 3) + (lane >> 4), pack2(rs, rs * (mean - blo(lds32(sb + SM_OFF)))), tag);
            TRC(el && !mb, 2, L * 16 + 10);
            pause<ZD2>(Q.zero);
          }
          uint4 v[4];
#pragma unroll 1
          for (int it = 0; it < (1 << 22); it++) {
            bool ok = true;
#pragma unroll
            for (int u = 0; u < 4; u++) { v[u] = ll_ld128((const uint4*)Q.RT + b * 128 + u * 32 + lane); ok = ok && v[u].y == tag && v[u].w == tag; }
            if (__all_sync(~0u, ok)) break;
          }
#pragma unroll
          for (int u = 0; u < 4; u++) {
            const uint32_t rt = sb + SM_RT + b * 512 + u * 128, ro = (lane >> 3) * 32 + (lane & 3) * 8 + ((lane >> 2) & 1) * 2;
            sts32(rt + 4096 + lane * 4, __byte_perm(v[u].x, v[u].z, 0x7632));
            asm volatile("st.shared.u16 [%0], %1;\nst.shared.u16 [%0 + 4], %2;" ::"r"(rt + ro), "h"((uint16_t)v[u].x), "h"((uint16_t)v[u].z) : "memory");
          }
          __syncwarp();
          if (el && (b & 1)) mbar_arrive(bars + B_RT + (b - 1) * 4);
          TRC(el && b < 2, 2, L * 16 + 11 + b);
        }
        TRC(el, 2, L * 16 + 9);
        mbar_wait(bars + B_EVT + EV_Z1 * 8, L);
        mbar_wait(bars + B_EVT + (EV_N + EV_Z1) * 8, L);
        fence_gpu();
        if (el) mbar_arrive(bars + B_Z1);
      }
    }
  } else {
    int w = wid >> 2, q = wid & 3, rb = bid & 15, j = bid >> 4;
    int g = lane >> 2, t = lane & 3;
#define PHASE asm volatile("" : "+r"(w), "+r"(q), "+r"(rb), "+r"(j))
#define stg (sb + SM_STG + w * 9216)
    const bool tr = (tid & 127) == 0;
    (void)tr;
    Cur c{0, 0};
    const uint32_t ebar = mapa(bars + B_EMPTY, (bid & 1) ^ (lane & 1));
    auto release = [&](uint32_t s) { if (lane < 2) mbar_arrive_cluster(ebar + s * 8); };
    uint32_t ia = 0;
    auto wait_ab = [&]() { mbar_wait_c(bars + B_FULL + c.s * 8, c.ph); mbar_wait_c(bars + B_FULLA + w * 32 + c.s * 8, (ia >> c.s) & 1); ia ^= 1u << c.s; };
    uint32_t lagph = 0;
    auto yield = [&](int left, int lag) { if (w == 1 && left == lag) mbar_wait_c(bars + B_LAG, lagph); };
    auto yield_done = [&]() { if (w == 0 && lane == 0) mbar_arrive(bars + B_LAG); };
    uint32_t rp = 0;
    auto check = [&](auto n, uint32_t dst, const uint8_t* src) {
      const uint32_t a = dst + lane * 32 + (lane >> 2) * 4;
#pragma unroll 1
      for (int it = 0; it < (1 << 16); it++) {
        uint32_t x = lds32(a);
#pragma unroll
        for (int e = 1; e < n.value; e++) x = max(x, lds32(a + e * 1024));
        if (!__any_sync(~0u, x == ~0u)) break;
        fence_async_s();
        __syncwarp();
        expect_tx_p(lane == 0, bars + B_RB + q * 8, n.value * 1024);
        bulk_load_p(lane == 0, dst, src, n.value * 1024, bars + B_RB + q * 8);
        mbar_wait_c(bars + B_RB + q * 8, rp & 1);
        rp++;
      }
    };
    auto signal = [&](int e) { __syncwarp(); if (lane == 0) mbar_arrive(bars + B_EVT + w * EV_N * 8 + e * 8); };
    TRC(tr, w, 0);

    {
      uint8_t* dst = Q.WQ + j * WQ_SL + rb * 3456 + tid * 16;
#pragma unroll
      for (int u = 0; u < 5; u++) {
        stg128_if((u < 4 || rb < 8) && tid < 216, dst + u * (16 * 3456), wv[u].x, wv[u].y, wv[u].z, wv[u].w);
        if (u == 0) TRC(tr, w, 60);
      }
      if (Q.zero == 0) {
        float s[8];
#pragma unroll
        for (int u = 0; u < 5; u++) {
          const uint32_t x[4] = {wv[u].x, wv[u].y, wv[u].z, wv[u].w};
#pragma unroll
          for (int e = 0; e < 4; e++) { s[2 * e] = u ? s[2 * e] + blo(x[e]) : blo(x[e]); s[2 * e + 1] = u ? s[2 * e + 1] + bhi(x[e]) : bhi(x[e]); }
        }
#pragma unroll
        for (int m = 4; m; m >>= 1) {
#pragma unroll
          for (int e = 0; e < m; e++) s[e] = ((tid & m) ? s[e + m] : s[e]) + __shfl_xor_sync(~0u, (tid & m) ? s[e] : s[e + m], m);
        }
        stg32_if(tid < 216, Q.CSP + bid * 216 + tid, __float_as_uint(s[0]));
      }
      __syncwarp();
      if (lane == 0) mbar_arrive(bars + B_IMG);
    }
    reg_alloc<224>();
    auto fetch_wo = [&]() {
#pragma unroll 1
      for (int u = tid; u < 328; u += 256) {
        const int m = min(41 * rb + (u >> 3), 647), k8 = m / 9;
        cp_async16(sb + SM_WOI + u * 16, (const uint8_t*)Q.wo + (8 * k8 + (u & 7)) * (DM * 2) + (72 * j + 8 * (m - k8 * 9)) * 2);
      }
    };
    const uint32_t epoch = ldcg32(Q.flags + (rb * 2 + w) * 32 + FR_EP + j);
    TRC(tr, w, 1);

#pragma unroll 1
    for (int L = 0; L < 2; L++) {
      const int tb = 2 + L * 24;
      asm volatile("" : "+r"(lane), "+r"(g), "+r"(t));
      if (PHM & 1) PHASE;
      (void)tb;
      const uint32_t tag = epoch * 2 + L + 1;
      {
        uint32_t Pk[27][2];
        float rk[2][2], sc[2][2];
        const bool up0 = 2 * t > g, up1 = 2 * t + 1 > g;
        constexpr int HA_[6] = {0, 2, 4, 7, 12, 15}, HC_[6] = {6, 9, 10, 11, 14, 17};
        const bool remote = q == 0 && rb > 0;
        uint4* hp = Q.HALO + ((((rb - (q == 0)) * 2 + w) * 8 + j) * 6) * 32 + lane;
        const uint32_t att = 2 * ST_BYTES + w * 8192 + lane * 16;
        const uint8_t* hs = remote ? (const uint8_t*)hp : smem_raw + att + (q == 3 ? ST_BYTES : q == 2 ? 3072 : 0);
        uint8_t* od = z1_block(rb, q >> 1, 0) + (9 * j) * 1024 + (4 * (q & 1) + w) * 128 + lane * 4;
        ACLK_INIT;
        {
          float acc[108];
#pragma unroll
          for (int i = 0; i < 108; i++) acc[i] = 0.f;
          float sx[2] = {0.f, 0.f}, sq[2] = {0.f, 0.f};
          uint32_t prev = 0;
#pragma unroll 1
          for (int kb = 0; kb < 7; kb++) {
            wait_ab();
            TRC(tr && kb == 0, w, tb + 0);
            PCLK(kb * 4);
            const uint32_t st = sb + c.s * ST_BYTES, da = dlo(st + w * 8192, 16), db = dlo(st + ST_B, 3456);
            wgmma_fence();
#pragma unroll
            for (int kk = 0; kk < 4; kk++) {
              wgmma_ss_n216(acc, dsc<1024, 1>(da, kk * 32), dsc<128, 0>(db, kk * 6912), 1);
              if (kk == 0) { wgmma_commit(); wgmma_wait<1>(); if (kb > 0) release(prev); }
              if (kk == 3) wgmma_commit();
              if (kk == XK1) {
            if (kb >= KS && kb < KS + 3) {
              mbar_wait_c(bars + B_WT + w * 8, 0);
#pragma unroll
              for (int u = 0; u < 3; u++) {
                const uint2 x = lds64(stg + (2 * q + (lane >> 4)) * 1152 + (lane & 15) * 8 + (kb - KS) * 384 + u * 128);
                sx[0] += blo(x.x) + bhi(x.x); sx[1] += blo(x.y) + bhi(x.y);
                sq[0] = fmaf(blo(x.x), blo(x.x), fmaf(bhi(x.x), bhi(x.x), sq[0])); sq[1] = fmaf(blo(x.y), blo(x.y), fmaf(bhi(x.y), bhi(x.y), sq[1]));
              }
            }
            if (kb == KS + 3) {
              const bool o = lane & 1;
              float v = (o ? sq[0] + sq[1] : sx[0] + sx[1]) + __shfl_xor_sync(~0u, o ? sx[0] + sx[1] : sq[0] + sq[1], 1);
              v += __shfl_xor_sync(~0u, v, 2); v += __shfl_xor_sync(~0u, v, 4); v += __shfl_xor_sync(~0u, v, 8);
              const float m = v * (-1.f / DM), r = rsq_fast(fmaxf(fmaf(__shfl_xor_sync(~0u, v, 1), 1.f / DM, -m * m), 0.f) + LN_EPS);
              ll_st128_if(!(lane & 15), Q.XST + (rb * 2 + w) * 128 + 16 * j + 4 * q + (lane >> 3), m, r, tag);
            }
              }
              if (kk == XK2 && L == 0) {
            if (kb == 0) fetch_wo();
            if (kb == 3) {
              asm volatile("cp.async.wait_all;" ::: "memory");
              fence_async_s();
              __syncwarp();
              if (lane == 0) mbar_arrive(bars + B_WOI);
            }
              }
            }
            prev = c.s; c.next();
          }
          const uint32_t ls = sb + L * (3 * ST_BYTES), cs = ls + SM_CSQ + t * 8;
          float2 cv[27];
          mbar_wait_c(bars + B_XRW + 8, L);
#pragma unroll
          for (int kb = 7; kb < 9; kb++) {
            wait_ab();
            yield(9 - kb, LAG1);
            PCLK(kb * 4);
            const uint32_t st = sb + c.s * ST_BYTES, da = dlo(st + w * 8192, 16), db = dlo(st + ST_B, 3456);
            wgmma_fence();
#pragma unroll
            for (int kk = 0; kk < 4; kk++) {
              wgmma_ss_n216(acc, dsc<1024, 1>(da, kk * 32), dsc<128, 0>(db, kk * 6912), 1);
              if (kk == 0) { wgmma_commit(); wgmma_wait<1>(); release(prev); }
              if (kb == 7 && kk < 3) {
#pragma unroll
                for (int G = 9 * kk; G < 9 * kk + 9; G++) cv[G] = lds64f(cs + G * 32);
                wgmma_fence();
              }
            }
            wgmma_commit();
            prev = c.s; c.next();
          }
          yield_done();
          mbar_wait_c(bars + B_CSQ, L);
          const uint32_t xs = ls + SM_XST + w * 768 + 256 + q * 128;
          const float2 n0 = lds64f(xs + g * 8), n1 = lds64f(xs + g * 8 + 64);
          const float m0 = n0.x, m1 = n1.x;
#pragma unroll
          for (int u = 0; u < 4; u++) {
            rk[u >> 1][u & 1] = __uint_as_float(lds32(xs + t * 16 + ((u & 1 ? up1 : up0) ? -64 : 0) + (u & 1) * 8 + (u >> 1) * 64 + 4));
            sc[u >> 1][u & 1] = rk[u >> 1][u & 1] * ((u >> 1 ? n1.y : n0.y) * (0.23570226039551584f * 1.4426950408889634f));
          }
          PCLK(36);
          wgmma_wait<0>();
          PCLK(37);
          release(prev);
          lagph ^= 1;
          TRC(tr, w, tb + 1);
          ACLK(0);
#pragma unroll
          for (int G = 9; G < 27; G++) Pk[G][1] = pack2(fmaf(m1, cv[G].x, acc[4 * G + 2]), fmaf(m1, cv[G].y, acc[4 * G + 3]));
          if (q < 3) {
#pragma unroll
            for (int i = 0; i < 6; i++) sts128(sb + att + (q >> 1) * ST_BYTES + (q & 1) * 3072 + i * 512, Pk[9 + HA_[i]][1], Pk[10 + HA_[i]][1], tag, Pk[9 + HC_[i]][1]);
          } else if (rb < 15) {
#pragma unroll
            for (int i = 0; i < 6; i++) ll_st128(hp + i * 32, __uint_as_float(Pk[9 + HA_[i]][1]), __uint_as_float(Pk[10 + HA_[i]][1]), tag, __uint_as_float(Pk[9 + HC_[i]][1]));
          }
#pragma unroll
          for (int G = 0; G < 27; G++) {
            Pk[G][0] = pack2(fmaf(m0, cv[G].x, acc[4 * G]), fmaf(m0, cv[G].y, acc[4 * G + 1]));
            if (G < 9) Pk[G][1] = pack2(fmaf(m1, cv[G].x, acc[4 * G + 2]), fmaf(m1, cv[G].y, acc[4 * G + 3]));
          }
        }
        ACLK(1);
        constexpr int GA_[4] = {0, 2, 4, 7}, GB_[4] = {1, 3, 5, 8}, GC_[4] = {2, 4, 6, 6};
        float S1[4][4], S2[4][4];
        uint32_t qa[4][2], qc[4][2];
#pragma unroll
        for (int h = 0; h < 4; h++) {
#pragma unroll
          for (int r = 0; r < 2; r++) {
            qa[h][r] = (h == 0 || h == 3 || t >= h) ? Pk[GA_[h]][r] : 0u;
            qc[h][r] = (h == 3 ? t == 3 : t <= h) ? Pk[GC_[h]][r] : 0u;
          }
#pragma unroll
          for (int i = 0; i < 4; i++) S1[h][i] = S2[h][i] = 0.f;
          mma16(S1[h], qa[h][0], qa[h][1], Pk[GB_[h]][0], Pk[GB_[h]][1], Pk[9 + GA_[h]][0], Pk[9 + GB_[h]][0]);
          mma16(S2[h], qa[h][0], qa[h][1], Pk[GB_[h]][0], Pk[GB_[h]][1], Pk[9 + GA_[h]][1], Pk[9 + GB_[h]][1]);
        }
#pragma unroll
        for (int h = 0; h < 4; h++) {
          mma8(S1[h], qc[h][0], qc[h][1], Pk[9 + GC_[h]][0]);
          mma8(S2[h], qc[h][0], qc[h][1], Pk[9 + GC_[h]][1]);
        }
        uint32_t V1[9], V2[9];
#pragma unroll
        for (int i = 0; i < 9; i++) { V1[i] = movm(Pk[18 + i][0]); V2[i] = movm(Pk[18 + i][1]); }
        uint4 hv[6];
#pragma unroll
        for (int i = 0; i < 6; i++) hv[i] = ll_ld128g(hs + i * 512);
        const uint32_t mup = (up0 ? 0xffffu : 0u) | (up1 ? 0xffff0000u : 0u);
        auto finish = [&](const float (&x0)[4], const float (&x1)[4], const uint32_t (&Vb)[9], uint32_t ma, int hi) {
          uint32_t p[4], n[4];
          float rs[4];
#pragma unroll
          for (int h = 0; h < 4; h++) {
            const float m = qmax(fmaxf(x0[h], x1[h])), e0 = ex2(x0[h] - m), e1 = ex2(x1[h] - m);
            n[h] = pack2(e0, e1);
            p[h] = pack2(e0 * rk[hi][0], e1 * rk[hi][1]);
          }
#pragma unroll
          for (int h = 0; h < 4; h += 2) {
            float D[4] = {0.f, 0.f, 0.f, 0.f};
            mma8(D, n[h], n[h + 1], 0x3f803f80u);
            rs[h] = rcp_fast(D[0]); rs[h + 1] = rcp_fast(D[2]);
          }
#pragma unroll
          for (int i = 0; i < 9; i++) {
            const int h = i < 4 ? 0 : i == 4 ? 1 : 2;
            const bool nx = (i == 2 || i == 4 || i == 6) ? 2 * t >= i : i == 3 || i > 6;
            float O[4] = {0.f, 0.f, 0.f, 0.f};
            mma16(O, p[h] & ma, p[h + 1] & ma, p[h] & ~ma, p[h + 1] & ~ma, V1[i], Vb[i]);
            const float r = nx ? rs[h + 1] : rs[h];
            stg32(od + i * 1024 + hi * 256, pack2((nx ? O[2] : O[0]) * r, (nx ? O[3] : O[1]) * r));
          }
        };
        {
          float x0[4], x1[4];
#pragma unroll
          for (int h = 0; h < 4; h++) { x0[h] = (up0 ? S1[h][2] : S2[h][2]) * sc[1][0]; x1[h] = (up1 ? S1[h][3] : S2[h][3]) * sc[1][1]; }
          finish(x0, x1, V2, mup, 1);
        }
        ACLK(2);
        bar_sync(1 + w, 128);
#pragma unroll 1
        for (int it = 0; it < (1 << 20); it++) {
          if (remote) {
            bool ok = true;
#pragma unroll
            for (int i = 0; i < 6; i++) ok = ok && hv[i].z == tag;
            if (__all_sync(~0u, ok)) break;
          }
#pragma unroll
          for (int i = 0; i < 6; i++) hv[i] = ll_ld128g(hs + i * 512);
          if (!remote) break;
        }
        uint32_t H[18];
#pragma unroll
        for (int i = 0; i < 6; i++) { H[HA_[i]] = hv[i].x; H[HA_[i] + 1] = hv[i].y; H[HC_[i]] = hv[i].w; }
        float S0[4][4];
#pragma unroll
        for (int h = 0; h < 4; h++) {
#pragma unroll
          for (int i = 0; i < 4; i++) S0[h][i] = 0.f;
          mma16(S0[h], qa[h][0], qa[h][1], Pk[GB_[h]][0], Pk[GB_[h]][1], H[GA_[h]], H[GB_[h]]);
        }
#pragma unroll
        for (int h = 0; h < 4; h++) mma8(S0[h], qc[h][0], qc[h][1], H[GC_[h]]);
        uint32_t V0[9];
#pragma unroll
        for (int i = 0; i < 9; i++) V0[i] = movm(H[9 + i]);
        ACLK(3);
        {
          const bool nohalo = (rb | q) == 0;
          const float b0 = up0 && nohalo ? -INFINITY : 0.f, b1 = up1 && nohalo ? -INFINITY : 0.f;
          float x0[4], x1[4];
#pragma unroll
          for (int h = 0; h < 4; h++) { x0[h] = fmaf(up0 ? S0[h][0] : S1[h][0], sc[0][0], b0); x1[h] = fmaf(up1 ? S0[h][1] : S1[h][1], sc[0][1], b1); }
          finish(x0, x1, V0, ~mup, 0);
        }
        ACLK(4);
        signal(EV_O);
        ACLK_OUT;
        TRC(tr, w, tb + 2);
      }
      if (c.s) { c.s = 0; c.ph ^= 1; }
      if (PHM & 2) PHASE;
      {
        float acc[36];
        const int hw = rb * 2 + w;
        const uint32_t xt = stg + (8 * q + g) * 144 + t * 4;
        uint32_t xm = sb + SM_STG + 9216 + (8 * q + (lane & 7)) * 144 + (lane & 8) * 576 + (lane & 16);
        uint8_t* xn = xn_block(hw) + j * 9216 + q * 256 + lane * 4;
        uint32_t* sp = (uint32_t*)(Q.ST1 + (hw * 8 + j) * 32 + 8 * q) + lane;
        const uint4* sg = Q.ST1 + (hw * 8 + t) * 32 + 8 * q + g;
        asm volatile("" : "+r"(xm), "+l"(xn), "+l"(sp), "+l"(sg));
        mbar_wait_c(bars + B_RES + w * 8, L);
        TRC(tr, w, tb + 21);
#pragma unroll
        for (int i = 0; i < 18; i++) { const uint32_t x = lds32(xt + (i >> 1) * 16 + (i & 1) * 4608); acc[2 * i] = blo(x); acc[2 * i + 1] = bhi(x); asm volatile("" : "+f"(acc[2 * i]), "+f"(acc[2 * i + 1])); }
        mbar_wait_c(bars + B_WF, L);
        const uint32_t db = dlo(sb, 1152), of = bars + (w ? B_OF + 40 : B_AV + 96);
        uint32_t da[5];
#pragma unroll
        for (int e = 0; e < 5; e++) da[e] = __shfl_sync(~0u, dlo(sb + o_place(w, e), 1024), 0);
        if (w) {
#pragma unroll 1
          for (int kb = q; kb < 9; kb += 4) {
            const uint32_t e = (kb + 1) >> 1;
            mbar_wait_c(bars + B_OF + e * 8, L);
            check(Int<8>{}, sb + o_place(0, e) + (kb && !(kb & 1)) * 8192, z1_block(rb, 0, 0) + kb * 8192);
            if (lane <= !kb) mbar_arrive(bars + B_AV + (12 + e) * 8);
          }
          bar_sync(7, 256);
        }
        mbar_wait_c(of, L & w);
        TRC(tr, w, tb + 3);
        wgmma_fence();
#pragma unroll
        for (int kk = 0; kk < 4; kk++) wgmma_ss_n72(acc, dsc<128, 0>(da[0], kk * 2048), dsc<128, 0>(db, kk * 2304), 1);
        wgmma_commit();
#pragma unroll 1
        for (int h = 0; h < 2; h++) {
#pragma unroll
          for (int u = 0; u < 4; u++) {
            if (!(u & 1)) { mbar_wait_c(of + 8 + h * 16 + u * 4, 1 + 2 * h + (u >> 1) < SPL ? L & w : L); wgmma_fence(); }
            if (u == 3 && h && !w) bar_arrive(7, 256);
#pragma unroll
            for (int kk = 0; kk < 4; kk++) wgmma_ss_n72(acc, dsc<128, 0>(da[1 + (u >> 1)], (u & 1) * 8192 + kk * 2048), dsc<128, 0>(db + h * 2304, (1 + u) * 9216 + kk * 2304), 1);
            if (u != 2) wgmma_commit();
            if (u == 0) { wgmma_wait<1>(); if (lane + w == 0 && h) mbar_arrive(bars + B_X3); }
          }
          da[1] = da[3]; da[2] = da[4];
        }
        RCLK_INIT;
        wgmma_wait<0>();
        RCLK(0);
        if (lane < 2) mbar_arrive_cluster(ebar + B_XD - B_EMPTY + w * 8);
        TRC(tr && P5TRACE != 5, w, tb + 4);
        {
          float s0 = 0.f, s1 = 0.f, q0 = 0.f, q1 = 0.f;
#pragma unroll
          for (int i = 0; i < 36; i++) {
            if (i & 2) { s1 += acc[i]; q1 = fmaf(acc[i], acc[i], q1); } else { s0 += acc[i]; q0 = fmaf(acc[i], acc[i], q0); }
          }
          const bool o1 = t & 1, o2 = t & 2;
          const float ss = (o1 ? s1 : s0) + __shfl_xor_sync(~0u, o1 ? s0 : s1, 1), sq = (o1 ? q1 : q0) + __shfl_xor_sync(~0u, o1 ? q0 : q1, 1);
          const float v = (o2 ? sq : ss) + __shfl_xor_sync(~0u, o2 ? ss : sq, 2);
          asm volatile("st.relaxed.gpu.global.u32 [%0], %1;" ::"l"(sp), "r"(__float_as_uint(v)) : "memory");
        }
        RCLK(1);
        RCLK(2);
        pause<PDEL>(Q.zero);
        uint4 pa, pb;
        auto there = [&](const uint4& a, const uint4& b) { return __all_sync(~0u, max(max(max(a.x, a.y), max(a.z, a.w)), max(max(b.x, b.y), max(b.z, b.w))) != ~0u); };
#pragma unroll 1
        for (int it = 0; it < (1 << 20); it++) {
          pa = ll_ld128(sg); pb = ll_ld128(sg + 128);
          if (there(pa, pb)) break;
        }
        RCLK(3);
        float mean0 = qsum(__uint_as_float(pa.x) + __uint_as_float(pb.x)) * (-1.f / DM), mean1 = qsum(__uint_as_float(pa.y) + __uint_as_float(pb.y)) * (-1.f / DM);
        const float rs0 = GA * rsq_fast(fmaxf(fmaf(qsum(__uint_as_float(pa.z) + __uint_as_float(pb.z)), 1.f / DM, -mean0 * mean0), 0.f) + LN_EPS);
        const float rs1 = GA * rsq_fast(fmaxf(fmaf(qsum(__uint_as_float(pa.w) + __uint_as_float(pb.w)), 1.f / DM, -mean1 * mean1), 0.f) + LN_EPS);
        mean0 *= rs0; mean1 *= rs1;
#pragma unroll
        for (int i = 0; i < 18; i++) {
          const float a = (i & 1) ? rs1 : rs0, b = (i & 1) ? mean1 : mean0;
          stg32(xn + (i >> 1) * 1024 + (i & 1) * 128, pack2(fmaf(acc[2 * i], a, b), fmaf(acc[2 * i + 1], a, b)));
        }
        signal(EV_X1);
        RCLK(4);
        if (w) {
#pragma unroll 1
          for (int u = q; u < 24; u += 4) {
            const uint32_t mb = u < 2 * SPL ? u >= SPL : u & 1, k = u < 2 * SPL ? u - mb * SPL : u >> 1;
            mbar_wait_c(bars + B_AF3 + mb * 96 + k * 8, L);
            SCLK3(u);
            check(Int<6>{}, sb + k * 12288 + mb * 6144, xn_block(rb * 2 + mb) + k * 6144);
            SCLK3(24 + u);
            if (lane <= (u < 2 * SPL)) mbar_arrive(bars + B_AV + (u < SPL ? 12 + k : k) * 8);
          }
          TRVI(lane == 0 && P5TRACE != 5, 5, 56 + L * 4 + q, rp);
          mbar_wait_c(bars + B_S5, L);
        }
#pragma unroll
        for (int u = 0; u < 4; u++)
          stsm4(xm + u * 32, pack2(acc[8 * u], acc[8 * u + 1]), pack2(acc[8 * u + 2], acc[8 * u + 3]), pack2(acc[8 * u + 4], acc[8 * u + 5]), pack2(acc[8 * u + 6], acc[8 * u + 7]));
        asm volatile("stmatrix.sync.aligned.m8n8.x2.shared.b16 [%0], {%1,%2};" ::"r"(xm + 128), "r"(pack2(acc[32], acc[33])), "r"(pack2(acc[34], acc[35])) : "memory");
        fence_async_s();
        signal(EV_XS);
        RCLK(5);
        TRC(tr, w, tb + 5);
        RCLK(6);
        RCLK_OUT;
      }
      if (PHM & 4) PHASE;
      {
      float acc[160];
#pragma unroll
      for (int i = 0; i < 160; i++) acc[i] = 0.f;
      float s[2] = {0.f, 0.f}, qq[2] = {0.f, 0.f}, zo = 0.f;
      const uint32_t zp = sb + SM_ZP3 + (tid & 127) * 4;
      auto zstat = [&](int mb, bool on) {
        const bool o1 = t & 1, o2 = t & 2;
        const float ss = ((o1 ? s[1] : s[0]) + __shfl_xor_sync(~0u, o1 ? s[0] : s[1], 1)) * 0x1p60f, sq = (o1 ? qq[1] : qq[0]) + __shfl_xor_sync(~0u, o1 ? qq[0] : qq[1], 1);
        const uint32_t v = __float_as_uint((o2 ? sq : ss) + zo + __shfl_xor_sync(~0u, o2 ? ss : sq, 2));
        asm volatile("{\n.reg .pred p, q, r;\nsetp.eq.u32 p, %4, 1;\nsetp.eq.u32 q, %4, 2;\nsetp.eq.and.u32 r, %5, 0, q;\n@p st.shared.u32 [%0], %2;\n@p bar.arrive 13, 256;\n"
                     "@q st.relaxed.gpu.global.u32 [%1], %2;\n@r mbarrier.arrive.shared::cta.b64 _, [%3];\n}" ::"r"(zp + mb * 512), "l"((uint32_t*)(Q.ZST + ((rb * 2 + mb) * 8 + j) * 32) + (tid & 127)),
                     "r"(v), "r"(bars + B_ZS + mb * 8), "r"(on ? 1 + w : 0), "r"(lane) : "memory");
        s[0] = s[1] = qq[0] = qq[1] = 0.f;
      };
      const uint32_t ebar3 = ebar + (B_E3 - B_EMPTY);
#pragma unroll 1
      for (int half = 0; half < 2; half++) {
        const bool big = half != w;
        auto rel3 = [&](int p) { if (lane < 2) mbar_arrive_cluster(ebar3 + p * 8); };
        if (half + w > 0) bar_sync(6 + w, 256);
        auto pass = [&](auto nk) {
          constexpr int NK = nk.value;
          uint32_t d0 = dlo(sb, 1024), ph = half & ~w, af = bars + B_AV;
          const uint32_t db = dlo(sb + SM_B3, NK == 3 ? 6144 : 2048);
          const bool lead = NK == 3 && !half;
          if (lead) {
#pragma unroll
            for (int u = 0; u < 2 * SPL; u++) {
              const int mb = u / SPL, p = u % SPL;
              if (!mb) mbar_wait_c(bars + B_F3 + p * 8, 0);
              mbar_wait_c(af + (mb ? p : 12 + p) * 8, mb || p > 4 ? L : 1);
              TRC(tr && u == 0, w, tb + 6);
              SCLK2(u);
              if (p == 0) SCLK(mb * 4);
              wgmma_fence();
#pragma unroll
              for (int kk = 0; kk < 3; kk++) {
                wgmma_ss_n128(acc + mb * 80, dsc<128, 0>(d0, p * 12288 + kk * 2048 + mb * 6144), dsc<1024, 1>(db, p * 12288 + kk * 2048), p + kk > 0);
                if (kk == 0 && u > SPL) { wgmma_commit(); wgmma_wait<1>(); rel3(p - 1); }
              }
              wgmma_commit();
            }
          }
#pragma unroll 1
          for (int it = 0; it < 6 / NK; it++) {
#pragma unroll
            for (int p = 0; p < 6; p++) {
              if (p < SPL && lead && it == 0) continue;
              mbar_wait_c(bars + B_F3 + p * 8, ph);
              if (NK == 3) mbar_wait_c(af + p * 8, L);
              TRC(tr && p == 0 && it == 0, w, tb + 6 + half * 4);
              if (lead) SCLK2(12 + it * 6 + p);
              if (NK == 2 ? !(p & 1) : p % 3 == 0) SCLK(half * 11 + (NK == 2 ? it * 3 + p / 2 : it * 2 + p / 3));
              wgmma_fence();
#pragma unroll
              for (int u = 0; u < 2 * NK; u++) {
                const int kk = u >> 1, mb = u & 1, e = p * NK + kk;
                const uint64_t da = dsc<128, 0>(d0, (e / 3) * 12288 + (e % 3) * 2048 + mb * 6144);
                if (NK == 3) wgmma_ss_n128(acc + mb * 80, da, dsc<1024, 1>(db, p * 12288 + kk * 2048), e > 0 || it > 0);
                else wgmma_ss_n160(acc + mb * 80, da, dsc<1024, 1>(db, p * 12288 + kk * 6144), e > 0 || it > 0);
                if (u == 0) { wgmma_commit(); wgmma_wait<1>(); if (p > 0 || it > 0) rel3((p + 5) % 6); }
                if (p * 8 + u == (NK == 2 ? HO3 : HO4) && it == 6 / NK - 1) bar_arrive(7 - w, 256);
              }
              wgmma_commit();
            }
            d0 += NK * 1536; af += 48;
            ph ^= 1;
          }
        };
        if (big) pass(Int<2>{}); else pass(Int<3>{});
        if (w) { bar_sync(13, 256); zo = __uint_as_float(lds32(zp + half * 512)); }
        if (half) zstat(1, true);
        const uint32_t off2 = lds32(sb + SM_OFF);
        const int go = (j & 1) ? (big ? 0 : 20) : (big ? 16 : 0);
        const float* gbp = (const float*)(smem_raw + SM_OFF + 8);
        asm volatile("" : "+l"(gbp));
        uint8_t* zd = half ? z1_block(rb, 0, j) + go * 1024 + (q & 1) * 2048 + (q >> 1) * 512 + lane * 16 : z2_block(rb, j) + q * 9216 + go * 128 + ((g & 3) * 2 + (g >> 2)) * 16 + t * 4;
        wgmma_wait<0>();
        SCLK(half * 11 + 9);
        rel3(5);
        TRC(tr, w, tb + 7 + half * 4);
        auto gelu = [&](auto z2) {
          constexpr int NC = z2.value ? NC2 : NC1;
          float gate[NC], gb = GB, gn = GB;
          uint32_t qa[2][3] = {{0, 0, 0}, {0, 0, 0}};
#pragma unroll
          for (int e = 0; e < NC; e++) gate[e] = GB;
#pragma unroll
          for (int G = 0; G < 20; G++) {
            if (G == 16 && !big) break;
            if (G % (z2.value ? LD2 : LD1) == 0) { gb = gn; if (G < 20 - (z2.value ? LD2 : LD1)) asm volatile("ld.f32 %0, [%1];" : "=f"(gn) : "l"(gbp) : "memory"); }
#pragma unroll
            for (int r = 0; r < 2; r++) {
              float z[2];
              float& gt = gate[(G * 2 + r) % NC];
#pragma unroll
              for (int e = 0; e < 2; e++) {
                const float v = acc[4 * G + 2 * r + e];
                z[e] = fmaf(v, tanh_fast(v * fmaf(v, v, gt)), v);
                if (z2.value) { s[r] = fmaf(z[e], 0x1p-60f, s[r]); qq[r] = fmaf(z[e], z[e], qq[r]); }
              }
              const uint32_t pk = pack2(z[0], z[1]);
              if (z2.value) {
                stg32(zd + G * 128 + r * 4608, hsub2(pk, off2));
                gt = fmaf(qq[r], s[r], gb);
              } else {
                gt = fmaf(__uint_as_float(pk), 0x1p-60f, gb);
                if ((G & 3) == 3) stg128(zd + (G >> 2) * 4096 + r * (8 * ZB), qa[r][0], qa[r][1], qa[r][2], pk);
                else qa[r][G & 3] = pk;
              }
            }
          }
        };
#pragma unroll 1
        for (int mb = 0;; mb++) {
          if (half) gelu(Int<0>{}); else gelu(Int<1>{});
          if (mb) break;
          zstat(0, !half);
#pragma unroll
          for (int i = 0; i < 80; i++) acc[i] = acc[80 + i];
          zd += half ? 1024 : 128 * ZB;
        }
        mbar_wait_c(bars + B_GATE3, L);
        signal(half ? EV_Z1 : EV_ZN);
        SCLK(half * 11 + 10);
        TRC(tr, w, tb + 8 + half * 4);
      }
      }
      if (PHM & 8) PHASE;
      const uint32_t aoff = (w * 64 + q * 16 + (lane & 15)) * 128 + (((lane >> 4) ^ (lane & 7)) << 4);
      uint32_t hA[18][4];
      {
        float acc[144];
        {
          const uint32_t c16 = lds32(sb + SM_OFF + 12), a[4] = {c16, c16, c16, c16};
          wgmma_fence();
          wgmma_rs_n144(acc, a, dsc<0, 0>(dlo(sb + SM_CV + 512, 0), 0), 0);
          wgmma_rs_n144(acc + 72, a, dsc<0, 0>(dlo(sb + SM_CV + 512, 0), 128), 0);
          wgmma_commit();
        }
        uint32_t prev = 0;
        auto stage = [&](int kb) {
          mbar_wait_c(bars + B_FULL + c.s * 8, c.ph);
          TRC(tr && kb == 0, w, tb + 13);
          SCLK(22 + kb);
          const uint32_t st = sb + c.s * ST_BYTES, db = dlo(st + ST_B, 4608), rt = sb + SM_RT + kb * 128 + t * 8;
          uint32_t a[4][4];
#pragma unroll
          for (int kk = 0; kk < 4; kk++) {
            uint32_t r[4];
            ldsm4(r, st + (aoff ^ (kk << 5)));
            const uint2 sc = lds64(rt + kk * 32);
            a[kk][0] = hmul2(__byte_perm(r[0], r[2], 0x5410), sc.x); a[kk][2] = hmul2(__byte_perm(r[0], r[2], 0x7632), sc.y);
            a[kk][1] = hmul2(__byte_perm(r[1], r[3], 0x5410), sc.x); a[kk][3] = hmul2(__byte_perm(r[1], r[3], 0x7632), sc.y);
          }
          if (kb + w == 0) bar_sync(6, 256);
          wgmma_fence();
#pragma unroll
          for (int i = 0; i < 8; i++) {
            const int kk = i & 3, hf = i >> 2;
            wgmma_rs_n144(acc + hf * 72, a[kk], dsc<128, 0>(db, kk * 9216 + hf * 2304), 1);
            if (i == 0) { wgmma_commit(); wgmma_wait<1>(); if (kb) release(prev); }
            if (i == 3) wgmma_commit();
          }
          wgmma_commit();
          prev = c.s; c.next();
        };
#pragma unroll 1
        for (int kb = 0; kb < 32; kb += 2) {
          if (!(kb & 7)) mbar_wait_c(bars + B_RT + kb, L);
          stage(kb);
          stage(kb + 1);
        }
        mbar_wait_c(bars + B_CV + w * 8, L);
        const float gk = 0.5f / GA;
        const float c1 = __uint_as_float(lds32(sb + SM_OFF + 4));
        const float gb0 = -gk * (c1 + __uint_as_float(lds32(sb + SM_CV + w * 256 + (16 * q + g) * 4))), gb1 = -gk * (c1 + __uint_as_float(lds32(sb + SM_CV + w * 256 + (16 * q + g + 8) * 4)));
        if (w == 1) { mbar_wait_c(bars + B_FULL + c.s * 8, c.ph); release(c.s); c.next(); }
        mbar_wait_c(bars + B_FULL + c.s * 8, c.ph);
        const uint32_t zs = sb + c.s * ST_BYTES + ST_B + (tid & 127) * 16;
        uint4 zl, zh;
#pragma unroll
        for (int u = 0; u < 18; u++) {
          if (u == 0) wgmma_wait<1>();
          if (u == 9) {
            wgmma_wait<0>();
            release(prev);
            if (L == 0) signal(EV_PT);
            TRC(tr, w, tb + 14);
            SCLK(54);
          }
          if (!(u & 1)) { zl = lds128(zs + u * 2048); zh = lds128(zs + u * 2048 + 2048); }
          const uint4 z = (u & 1) ? make_uint4(zl.z, zh.z, zl.w, zh.w) : make_uint4(zl.x, zh.x, zl.y, zh.y);
          hA[u][0] = hmul2(z.x, pack2(fmaf(acc[8 * u], gk, gb0), fmaf(acc[8 * u + 1], gk, gb0)));
          hA[u][1] = hmul2(z.y, pack2(fmaf(acc[8 * u + 2], gk, gb1), fmaf(acc[8 * u + 3], gk, gb1)));
          hA[u][2] = hmul2(z.z, pack2(fmaf(acc[8 * u + 4], gk, gb0), fmaf(acc[8 * u + 5], gk, gb0)));
          hA[u][3] = hmul2(z.w, pack2(fmaf(acc[8 * u + 6], gk, gb1), fmaf(acc[8 * u + 7], gk, gb1)));
        }
        __syncwarp();
        release(c.s);
        c.next();
        if (w == 0) { mbar_wait_c(bars + B_FULL + c.s * 8, c.ph); release(c.s); c.next(); }
        TRC(tr, w, tb + 15);
      }
      {
        CLK_INIT;
        if (w == 1) bar_arrive(6, 256);
        uint4 v[4];
#pragma unroll
        for (int u = 0; u < 4; u++) v[u] = make_uint4(0u, 0u, 0u, 0u);
        uint32_t rl = sb + SM_STG + w * 8192 + q * 2048 + (lane >> 3) * 128 + (((lane & 7) ^ (lane >> 3)) << 4);
        uint8_t* rd = Q.out + (128 * rb + 32 * q + 2 * (lane >> 3) + w) * (DM * 2) + j * 128 + (lane & 7) * 16;
        asm volatile("" : "+r"(rl), "+l"(rd));
        auto send = [&](int u0, int u1) {
#pragma unroll
          for (int u = u0; u < u1; u++)
            asm volatile("red.relaxed.gpu.global.add.noftz.v4.bf16x2 [%0], {%1,%2,%3,%4};" ::"l"(rd + u * (8 * DM * 2)), "r"(v[u].x), "r"(v[u].y), "r"(v[u].z), "r"(v[u].w) : "memory");
        };
#pragma unroll 1
        for (int p = 0; p < 9; p++) {
          float acc[32];
          CLK(0);
          mbar_wait_c(bars + B_FULL + c.s * 8, c.ph);
          const uint32_t db = dlo(sb + c.s * ST_BYTES + ST_B, 0);
          CLK(1);
          bar_sync(6 + w, 256);
          CLK(2);
          wgmma_fence();
#pragma unroll
          for (int kk = 0; kk < 18; kk++) {
            wgmma_rs_n64(acc, hA[kk], dsc<1024, 1>(db, kk * 2048), kk != 0);
            if (kk == PPK && (w == 0 || p < 8)) bar_arrive(7 - w, 256);
          }
          wgmma_commit();
          CLK(3);
          if (p > 0) { send(NOW, 4); rd += p + j == 9 ? -1024 : 128; }
          CLK(5);
          wgmma_wait<0>();
          CLK(4);
          if (L == 0 || p < 5) release(c.s);
          c.next();
          TRC(tr && p == 8, w, tb + 16);
#pragma unroll
          for (int u = 0; u < 4; u++)
            stsm4(sb + SM_STG + (aoff ^ (u << 5)), pack2(acc[8 * u], acc[8 * u + 1]), pack2(acc[8 * u + 2], acc[8 * u + 3]), pack2(acc[8 * u + 4], acc[8 * u + 5]), pack2(acc[8 * u + 6], acc[8 * u + 7]));
          __syncwarp();
#pragma unroll
          for (int u = 0; u < 4; u++) v[u] = lds128(rl + u * 512 ^ (u & 1) << 6);
          send(0, NOW);
        }
        send(NOW, 4);
        TRC(tr, w, tb + 17);
        if (L == 0) signal(EV_PT);
        CLK_OUT;
        TRC(tr, w, tb + 18);
      }
    }
    if ((tid & 127) == 0) Q.flags[(rb * 2 + w) * 32 + FR_EP + j] = epoch + 1;
    if (tid == 0) Q.flags[FJ + j * 32 + FJ_EP + rb] = epoch + 1;
  }
}

typedef CUresult (*EncodeFn)(CUtensorMap*, CUtensorMapDataType, cuuint32_t, void*, const cuuint64_t*, const cuuint64_t*, const cuuint32_t*,
                             const cuuint32_t*, CUtensorMapInterleave, CUtensorMapSwizzle, CUtensorMapL2promotion, CUtensorMapFloatOOBfill);

static void make_map(EncodeFn fn, CUtensorMap* m, const void* ptr, int rank, uint64_t d0, uint64_t d1, uint64_t d2, uint64_t s1, uint64_t s2,
                     uint32_t b0, uint32_t b1, uint32_t b2, CUtensorMapSwizzle swz) {
  cuuint64_t dims[3] = {d0, d1, d2}, strides[2] = {s1, s2};
  cuuint32_t box[3] = {b0, b1, b2}, es[3] = {1, 1, 1};
  fn(m, CU_TENSOR_MAP_DATA_TYPE_BFLOAT16, rank, const_cast<void*>(ptr), dims, strides, box, es, CU_TENSOR_MAP_INTERLEAVE_NONE, swz,
     CU_TENSOR_MAP_L2_PROMOTION_L2_128B, CU_TENSOR_MAP_FLOAT_OOB_FILL_NONE);
}

}

extern "C" void kernel_launch(void* const* d_in, const int* in_sizes, int n_in, void* d_out, int out_size) {
  using namespace mk;
  (void)in_sizes; (void)n_in; (void)out_size;
  static EncodeFn fn = nullptr;
  static Scratch* sc = nullptr;
  if (!fn) {
    cudaDriverEntryPointQueryResult qr;
    cudaGetDriverEntryPoint("cuTensorMapEncodeTiled", (void**)&fn, cudaEnableDefault, &qr);
    cudaGetSymbolAddress((void**)&sc, g_scratch);
    cudaFuncSetAttribute(mega_kernel, cudaFuncAttributeMaxDynamicSharedMemorySize, SM_TOTAL);
  }
  Params p;
  Ptrs a;
  a.x = (const uint8_t*)d_in[0];
  a.wqkv = (const __nv_bfloat16*)d_in[1];
  a.wo = (const __nv_bfloat16*)d_in[2];
  a.w_in = (const __nv_bfloat16*)d_in[4];
  a.w_sp = (const __nv_bfloat16*)d_in[5];
  a.b_sp = (const __nv_bfloat16*)d_in[6];
  a.out = (uint8_t*)d_out;
  a.zero = 0;
  a.WQ = sc->WQ; a.flags = sc->flags; a.CSP = sc->CSP; a.XST = sc->XST; a.HALO = sc->HALO; a.ST1 = sc->ST1; a.ZST = sc->ZST; a.RT = sc->RT; a.Z = sc->Z; a.WO = sc->WO;
  make_map(fn, &p.wsp, a.w_sp, 3, 2048, 1024, 2, 8192, 4096, 64, 64, 2, CU_TENSOR_MAP_SWIZZLE_128B);
  for (int i = 0; i < 2; i++) {
    make_map(fn, &p.act[i], i ? a.out : a.x, 3, DM, 1024, 2, 2304, 1152, 64, 64, 1, CU_TENSOR_MAP_SWIZZLE_128B);
    make_map(fn, &p.row[i], i ? a.out : a.x, 3, 192, 6, 1024, 384, 2304, 192, 3, 8, CU_TENSOR_MAP_SWIZZLE_NONE);
    make_map(fn, &p.res[i], i ? a.out : a.x, 3, DM, 1024, 2, 2304, 1152, 72, 32, 2, CU_TENSOR_MAP_SWIZZLE_NONE);
  }
  for (int i = 0; i < 2; i++) make_map(fn, &p.winb[i], a.w_in + 32 * i, 3, 64, 576, 72 - i, 9216, 128, 64, 16, 3, CU_TENSOR_MAP_SWIZZLE_128B);
  make_map(fn, &p.wins, a.w_in, 3, 64, 576, 72, 9216, 128, 64, 48, 1, CU_TENSOR_MAP_SWIZZLE_128B);
  make_map(fn, &p.wout, d_in[7], 2, 576, 2304, 1, 1152, 0, 64, 144, 1, CU_TENSOR_MAP_SWIZZLE_128B);
  mega_kernel<<<NGRID, 384, SM_TOTAL, cudaStreamPerThread>>>(a, p);
}
```

```cpp
#include <cuda_runtime.h>
#include <cuda.h>
#include <cuda_bf16.h>
#include <stdint.h>

#define MK_TRACE 0
#define MK_DBG 0
#define P5TRACE 0
#define LAG1 1
#define C0S 32.f
#define OFM 0x10u
#define NC2 2
#define NC1 8
#define PDEL 8
#define LD1 4
#define LD2 2
#define ZD1 8
#define ZD2 20
#define WPF 1
#define YPACE 2
#define SPL 3
#define XP0 10
#define EFM 0x23333022
#define EF(i) ((((EFM >> (4 * (i))) & 3) == 3) || (((EFM >> (4 * (i))) >> L) & 1))
#define AEP 2
#define PZI 4
#define KS 1
#define RFI 3
#define XK1 1
#define XK2 2
#define SDEL 10
#define FD3 14
#define FD4 0
#define FD5 0
#define PHM 15
#define NOW 2
#define WTI 12
#define QG 9
#define EARR 0
#define APACE 7
#define HO3 41
#define HO4 41
#define PPK 17

namespace mk {

constexpr int SEQ = 2048, DM = 576, FH = 2304;
constexpr int NCTA = 128;
constexpr int NGRID = 132;
constexpr uint32_t ZB = 36864;
constexpr uint32_t WQ_SL = 72 * 3456;
constexpr uint32_t WO_SL = 72 * 1152;
constexpr float LN_EPS = 1e-5f;
constexpr float GA = 0.3292034911525734f, GB = 2.423681954311584f;

constexpr uint32_t ST_BYTES = 53248, ST_B = 16384, NST = 4;
constexpr uint32_t SM_STG = NST * ST_BYTES;
constexpr uint32_t SM_BAR = SM_STG + 2 * 9216, B_OFF = 896;
constexpr uint32_t SM_OFF = SM_BAR + B_OFF;
constexpr uint32_t SM_TOTAL = SM_BAR + 1024;
constexpr uint32_t SM_RT = SM_STG + 9216, SM_CV = SM_STG + 17408, SM_WT = SM_STG;
constexpr uint32_t SM_WOI = 44032, SM_CSQ = 49280, SM_XST = 50176;
enum { EV_PT = 0, EV_O = 1, EV_X1 = 2, EV_ZN = 3, EV_Z1 = 4, EV_XS = 5, EV_N = 6 };
constexpr uint32_t B_FULL = 0, B_FULLA = 32, B_RES = 96, B_WT = 112, B_GATE3 = 128, B_Z1 = 136, B_ZOK = 144, B_CV = 152, B_XRW = 168, B_F3 = 184, B_WF = 232, B_OF = 240,
                   B_RT = 320, B_AF3 = 352, B_RB = 544,
                   B_AD = 576, B_S5 = 608, B_AV = 616, B_CSQ = 760,
                   B_LAG = 768, B_X3 = 776, B_ZS = 784, B_EVT = 800,
                   B_IMG = 912, B_WOI = 920, B_E3 = 928, B_XD = 976,
                   B_EMPTY = 992;
constexpr uint32_t SM_B3 = 9 * 16384, SM_ZP3 = SM_STG + 8192;

enum { FR_X2 = 0, FR_O = 1, FR_XR = 5, FR_OL = 7, FR_PZ = 9, FR_EP = 16, FJ = 32 * 32, FJ_WQ = 0, FJ_WO = 1, FJ_ZN = 3, FJ_P4 = 5, FJ_EP = 16, F_N = FJ + 8 * 32 };

struct Scratch {
  alignas(1024) uint32_t flags[F_N];
  alignas(1024) float CSP[2 * NCTA * 216];
  alignas(1024) uint2 RT[SEQ];
  alignas(1024) uint4 XST[2 * SEQ];
  alignas(1024) uint4 ST1[SEQ * 4];
  alignas(1024) uint4 ZST[SEQ * 4];
  alignas(1024) uint4 HALO[32 * 8 * 6 * 32];
  alignas(1024) uint8_t WO[8 * WO_SL];
  alignas(1024) uint8_t WQ[8 * WQ_SL];
  alignas(1024) uint8_t Z[576 * ZB];
};
__device__ Scratch g_scratch;

struct Ptrs {
  const __nv_bfloat16* wqkv;
  uint8_t* WQ;
  uint32_t* flags;
  float* CSP;
  const uint8_t* x;
  uint32_t zero;
  uint4 *XST, *HALO, *ST1, *ZST;
  uint2* RT;
  uint8_t *Z, *WO, *out;
  const __nv_bfloat16 *wo, *w_in, *w_sp, *b_sp;
};
struct Params {
  CUtensorMap wsp, winb[2], wins, wout;
  CUtensorMap act[2];
  CUtensorMap res[2];
  CUtensorMap row[2];
};

__device__ __forceinline__ uint32_t smem_u32(const void* p) { return (uint32_t)__cvta_generic_to_shared(p); }
__device__ __forceinline__ void mbar_init(uint32_t bar, uint32_t cnt) { asm volatile("mbarrier.init.shared::cta.b64 [%0], %1;" ::"r"(bar), "r"(cnt)); }
__device__ __forceinline__ void mbar_arrive(uint32_t bar) { asm volatile("mbarrier.arrive.shared::cta.b64 _, [%0];" ::"r"(bar) : "memory"); }
__device__ __forceinline__ void mbar_wait(uint32_t bar, uint32_t parity) {
  asm volatile(
      "{\n.reg .pred p;\n.reg .u32 c;\nmov.u32 c, 0;\nLAB_WAIT:\n"
      "mbarrier.try_wait.parity.shared::cta.b64 p, [%0], %1;\n@p bra LAB_DONE;\n"
      "add.u32 c, c, 1;\nsetp.lt.u32 p, c, 0x100000;\n@p bra LAB_WAIT;\ntrap;\nLAB_DONE:\n}" ::"r"(bar), "r"(parity)
      : "memory");
}
__device__ __forceinline__ void mbar_wait_c(uint32_t bar, uint32_t parity) {
  asm volatile("{\n.reg .pred p;\nLAB_WAIT:\nmbarrier.try_wait.parity.shared::cta.b64 p, [%0], %1;\n@!p bra LAB_WAIT;\n}" ::"r"(bar), "r"(parity) : "memory");
}
__device__ __forceinline__ void flag_wait(const uint32_t* f, uint32_t target) {
  asm volatile(
      "{\n.reg .pred p;\n.reg .u32 c, v;\nmov.u32 c, 0;\nLAB_WAIT:\n"
      "ld.relaxed.gpu.global.u32 v, [%0];\nsub.u32 v, v, %1;\nsetp.ge.s32 p, v, 0;\n@p bra LAB_DONE;\n"
      "add.u32 c, c, 1;\nsetp.lt.u32 p, c, 0x400000;\n@p bra LAB_WAIT;\ntrap;\nLAB_DONE:\nfence.acquire.gpu;\n}" ::"l"(f), "r"(target)
      : "memory");
}
__device__ __forceinline__ void fence_gpu() { asm volatile("fence.acq_rel.gpu;" ::: "memory"); }
__device__ __forceinline__ void fence_async_g() { asm volatile("fence.proxy.async.global;" ::: "memory"); }
__device__ __forceinline__ void fence_async_s() { asm volatile("fence.proxy.async.shared::cta;" ::: "memory"); }
__device__ __forceinline__ uint32_t elect_one() {
  uint32_t p; asm volatile("{\n.reg .pred P;\nelect.sync _|P, 0xffffffff;\nselp.u32 %0, 1, 0, P;\n}" : "=r"(p)); return p;
}
__device__ __forceinline__ void expect_tx_p(uint32_t el, uint32_t bar, uint32_t bytes) {
  asm volatile("{\n.reg .pred P;\nsetp.ne.u32 P, %2, 0;\n@P mbarrier.arrive.expect_tx.shared::cta.b64 _, [%0], %1;\n}" ::"r"(bar), "r"(bytes), "r"(el) : "memory");
}
__device__ __forceinline__ void bulk_load_p(uint32_t el, uint32_t dst, const void* src, uint32_t bytes, uint32_t bar) {
  asm volatile("{\n.reg .pred P;\nsetp.ne.u32 P, %4, 0;\n@P cp.async.bulk.shared::cluster.global.mbarrier::complete_tx::bytes [%0], [%1], %2, [%3];\n}" ::"r"(dst), "l"(src), "r"(bytes), "r"(bar), "r"(el) : "memory");
}
__device__ __forceinline__ uint64_t policy_evict_first() { uint64_t p; asm("createpolicy.fractional.L2::evict_first.b64 %0, 1.0;" : "=l"(p)); return p; }
__device__ __forceinline__ void bulk_load_h(uint32_t el, uint32_t dst, const void* src, uint32_t bytes, uint32_t bar, bool ef, uint64_t pol) {
  if (ef) {
    asm volatile("{\n.reg .pred P;\nsetp.ne.u32 P, %4, 0;\n@P cp.async.bulk.shared::cluster.global.mbarrier::complete_tx::bytes.L2::cache_hint [%0], [%1], %2, [%3], %5;\n}" ::"r"(dst), "l"(src), "r"(bytes), "r"(bar), "r"(el), "l"(pol) : "memory");
  } else {
    asm volatile("{\n.reg .pred P;\nsetp.ne.u32 P, %4, 0;\n@P cp.async.bulk.shared::cluster.global.mbarrier::complete_tx::bytes [%0], [%1], %2, [%3];\n}" ::"r"(dst), "l"(src), "r"(bytes), "r"(bar), "r"(el) : "memory");
  }
}
__device__ __forceinline__ void bulk_mc_h(uint32_t el, uint32_t dst, const void* src, uint32_t bytes, uint32_t bar, bool ef, uint64_t pol) {
  if (ef) {
    asm volatile("{\n.reg .pred P;\nsetp.ne.u32 P, %4, 0;\n@P cp.async.bulk.shared::cluster.global.mbarrier::complete_tx::bytes.multicast::cluster.L2::cache_hint [%0], [%1], %2, [%3], %5, %6;\n}" ::"r"(dst), "l"(src), "r"(bytes), "r"(bar), "r"(el), "h"((uint16_t)3), "l"(pol) : "memory");
  } else {
    asm volatile("{\n.reg .pred P;\nsetp.ne.u32 P, %4, 0;\n@P cp.async.bulk.shared::cluster.global.mbarrier::complete_tx::bytes.multicast::cluster [%0], [%1], %2, [%3], %5;\n}" ::"r"(dst), "l"(src), "r"(bytes), "r"(bar), "r"(el), "h"((uint16_t)3) : "memory");
  }
}
__device__ __forceinline__ void tma3d_h(uint32_t el, uint32_t dst, const CUtensorMap* m, int c0, int c1, int c2, uint32_t bar, bool ef, uint64_t pol) {
  if (ef) {
    asm volatile("{\n.reg .pred P;\nsetp.ne.u32 P, %6, 0;\n@P cp.async.bulk.tensor.3d.shared::cluster.global.mbarrier::complete_tx::bytes.L2::cache_hint [%0], [%1, {%3, %4, %5}], [%2], %7;\n}" ::"r"(dst), "l"(m), "r"(bar), "r"(c0), "r"(c1), "r"(c2), "r"(el), "l"(pol) : "memory");
  } else {
    asm volatile("{\n.reg .pred P;\nsetp.ne.u32 P, %6, 0;\n@P cp.async.bulk.tensor.3d.shared::cluster.global.mbarrier::complete_tx::bytes [%0], [%1, {%3, %4, %5}], [%2];\n}" ::"r"(dst), "l"(m), "r"(bar), "r"(c0), "r"(c1), "r"(c2), "r"(el) : "memory");
  }
}
__device__ __forceinline__ void tma2d_mc_h(uint32_t el, uint32_t dst, const CUtensorMap* m, int c0, int c1, uint32_t bar, bool ef, uint64_t pol) {
  if (ef) {
    asm volatile("{\n.reg .pred P;\nsetp.ne.u32 P, %5, 0;\n@P cp.async.bulk.tensor.2d.shared::cluster.global.mbarrier::complete_tx::bytes.multicast::cluster.L2::cache_hint [%0], [%1, {%3, %4}], [%2], %6, %7;\n}" ::"r"(dst), "l"(m), "r"(bar), "r"(c0), "r"(c1), "r"(el), "h"((uint16_t)3), "l"(pol) : "memory");
  } else {
    asm volatile("{\n.reg .pred P;\nsetp.ne.u32 P, %5, 0;\n@P cp.async.bulk.tensor.2d.shared::cluster.global.mbarrier::complete_tx::bytes.multicast::cluster [%0], [%1, {%3, %4}], [%2], %6;\n}" ::"r"(dst), "l"(m), "r"(bar), "r"(c0), "r"(c1), "r"(el), "h"((uint16_t)3) : "memory");
  }
}
__device__ __forceinline__ void tma3d_mc_h(uint32_t el, uint32_t dst, const CUtensorMap* m, int c0, int c1, int c2, uint32_t bar, bool ef, uint64_t pol) {
  if (ef) {
    asm volatile("{\n.reg .pred P;\nsetp.ne.u32 P, %6, 0;\n@P cp.async.bulk.tensor.3d.shared::cluster.global.mbarrier::complete_tx::bytes.multicast::cluster.L2::cache_hint [%0], [%1, {%3, %4, %5}], [%2], %7, %8;\n}" ::"r"(dst), "l"(m), "r"(bar), "r"(c0), "r"(c1), "r"(c2), "r"(el), "h"((uint16_t)3), "l"(pol) : "memory");
  } else {
    asm volatile("{\n.reg .pred P;\nsetp.ne.u32 P, %6, 0;\n@P cp.async.bulk.tensor.3d.shared::cluster.global.mbarrier::complete_tx::bytes.multicast::cluster [%0], [%1, {%3, %4, %5}], [%2], %7;\n}" ::"r"(dst), "l"(m), "r"(bar), "r"(c0), "r"(c1), "r"(c2), "r"(el), "h"((uint16_t)3) : "memory");
  }
}
__device__ __forceinline__ void mbar_arrive_cluster(uint32_t addr) { asm volatile("mbarrier.arrive.shared::cluster.b64 _, [%0];" ::"r"(addr) : "memory"); }
__device__ __forceinline__ uint32_t mapa(uint32_t addr, uint32_t rank) { uint32_t r; asm("mapa.shared::cluster.u32 %0, %1, %2;" : "=r"(r) : "r"(addr), "r"(rank)); return r; }
__device__ __forceinline__ void bulk_store_p(uint32_t el, void* dst, uint32_t src, uint32_t bytes) {
  asm volatile("{\n.reg .pred P;\nsetp.ne.u32 P, %3, 0;\n@P cp.async.bulk.global.shared::cta.bulk_group [%0], [%1], %2;\n}" ::"l"(dst), "r"(src), "r"(bytes), "r"(el) : "memory");
}
__device__ __forceinline__ void flag_release_p(uint32_t el, uint32_t* f) {
  asm volatile("{\n.reg .pred P;\nsetp.ne.u32 P, %1, 0;\nfence.proxy.async;\n@P red.relaxed.gpu.global.add.u32 [%0], 1;\n}" ::"l"(f), "r"(el) : "memory");
}
__device__ __forceinline__ void flag_add_p(uint32_t el, uint32_t* f) {
  asm volatile("{\n.reg .pred P;\nsetp.ne.u32 P, %1, 0;\n@P red.relaxed.gpu.global.add.u32 [%0], 1;\n}" ::"l"(f), "r"(el) : "memory");
}
__device__ __forceinline__ void prefetch_l2(const void* src, uint32_t bytes) { asm volatile("cp.async.bulk.prefetch.L2.global [%0], %1;" ::"l"(src), "r"(bytes) : "memory"); }
__device__ __forceinline__ void prefetch_map(const CUtensorMap* m) { asm volatile("prefetch.tensormap [%0];" ::"l"(m) : "memory"); }
__device__ __forceinline__ void wgmma_fence() { asm volatile("wgmma.fence.sync.aligned;" ::: "memory"); }
__device__ __forceinline__ void wgmma_commit() { asm volatile("wgmma.commit_group.sync.aligned;" ::: "memory"); }
template <int N> __device__ __forceinline__ void wgmma_wait() { asm volatile("wgmma.wait_group.sync.aligned %0;" ::"n"(N) : "memory"); }
__device__ __forceinline__ uint32_t dlo(uint32_t addr, uint32_t lbo) { return ((addr & 0x3FFFF) >> 4) + ((lbo >> 4) << 16); }
template <uint32_t SBO, uint32_t SWZ> __device__ __forceinline__ uint64_t dsc(uint32_t lo, uint32_t off) {
  uint64_t d; asm("mov.b64 %0, {%1, %2};" : "=l"(d) : "r"(lo + (off >> 4)), "n"((SBO >> 4) | (SWZ << 30))); return d;
}
template <int R> __device__ __forceinline__ void reg_alloc() { asm volatile("setmaxnreg.inc.sync.aligned.u32 %0;" ::"n"(R)); }
template <int R> __device__ __forceinline__ void reg_dealloc() { asm volatile("setmaxnreg.dec.sync.aligned.u32 %0;" ::"n"(R)); }
__device__ __forceinline__ void bar_sync(int id, int n) { asm volatile("bar.sync %0, %1;" ::"r"(id), "r"(n) : "memory"); }
__device__ __forceinline__ void bar_arrive(int id, int n) { asm volatile("bar.arrive %0, %1;" ::"r"(id), "r"(n) : "memory"); }
__device__ __forceinline__ void ldsm4(uint32_t* r, uint32_t addr) {
  asm volatile("ldmatrix.sync.aligned.m8n8.x4.shared.b16 {%0,%1,%2,%3}, [%4];" : "=r"(r[0]), "=r"(r[1]), "=r"(r[2]), "=r"(r[3]) : "r"(addr) : "memory");
}
__device__ __forceinline__ uint32_t movm(uint32_t a) { uint32_t d; asm volatile("movmatrix.sync.aligned.m8n8.trans.b16 %0, %1;" : "=r"(d) : "r"(a)); return d; }
__device__ __forceinline__ void mma16(float* c, uint32_t a0, uint32_t a1, uint32_t a2, uint32_t a3, uint32_t b0, uint32_t b1) {
  asm volatile("mma.sync.aligned.m16n8k16.row.col.f32.bf16.bf16.f32 {%0,%1,%2,%3}, {%4,%5,%6,%7}, {%8,%9}, {%0,%1,%2,%3};"
               : "+f"(c[0]), "+f"(c[1]), "+f"(c[2]), "+f"(c[3]) : "r"(a0), "r"(a1), "r"(a2), "r"(a3), "r"(b0), "r"(b1));
}
__device__ __forceinline__ void mma8(float* c, uint32_t a0, uint32_t a1, uint32_t b0) {
  asm volatile("mma.sync.aligned.m16n8k8.row.col.f32.bf16.bf16.f32 {%0,%1,%2,%3}, {%4,%5}, {%6}, {%0,%1,%2,%3};"
               : "+f"(c[0]), "+f"(c[1]), "+f"(c[2]), "+f"(c[3]) : "r"(a0), "r"(a1), "r"(b0));
}
__device__ __forceinline__ uint32_t pack2(float lo, float hi) { uint32_t r; asm("cvt.rn.bf16x2.f32 %0, %1, %2;" : "=r"(r) : "f"(hi), "f"(lo)); return r; }
__device__ __forceinline__ float blo(uint32_t v) { return __uint_as_float(v << 16); }
__device__ __forceinline__ float bhi(uint32_t v) { return __uint_as_float(v & 0xffff0000u); }
__device__ __forceinline__ float tanh_fast(float x) { float y; asm("tanh.approx.f32 %0, %1;" : "=f"(y) : "f"(x)); return y; }
__device__ __forceinline__ float rcp_fast(float x) { float y; asm("rcp.approx.ftz.f32 %0, %1;" : "=f"(y) : "f"(x)); return y; }
__device__ __forceinline__ float rsq_fast(float x) { float y; asm("rsqrt.approx.ftz.f32 %0, %1;" : "=f"(y) : "f"(x)); return y; }
__device__ __forceinline__ float ex2(float x) { float y; asm("ex2.approx.ftz.f32 %0, %1;" : "=f"(y) : "f"(x)); return y; }
__device__ __forceinline__ float qsum(float v) { v += __shfl_xor_sync(~0u, v, 1); v += __shfl_xor_sync(~0u, v, 2); return v; }
__device__ __forceinline__ float qmax(float v) { v = fmaxf(v, __shfl_xor_sync(~0u, v, 1)); v = fmaxf(v, __shfl_xor_sync(~0u, v, 2)); return v; }
__device__ __forceinline__ void stg32(void* p, uint32_t v) { asm volatile("st.global.u32 [%0], %1;" ::"l"(p), "r"(v) : "memory"); }
__device__ __forceinline__ void stg128(void* p, uint32_t a, uint32_t b, uint32_t c, uint32_t d) { asm volatile("st.global.v4.u32 [%0], {%1,%2,%3,%4};" ::"l"(p), "r"(a), "r"(b), "r"(c), "r"(d) : "memory"); }
__device__ __forceinline__ uint32_t ldcg32(const void* p) { uint32_t v; asm volatile("ld.global.L1::no_allocate.u32 %0, [%1];" : "=r"(v) : "l"(p) : "memory"); return v; }
__device__ __forceinline__ void stg128_if(bool c, void* p, uint32_t a, uint32_t b, uint32_t cc, uint32_t d) {
  asm volatile("{\n.reg .pred P;\nsetp.ne.u32 P, %5, 0;\n@P st.global.v4.u32 [%0], {%1,%2,%3,%4};\n}" ::"l"(p), "r"(a), "r"(b), "r"(cc), "r"(d), "r"((uint32_t)c) : "memory");
}
__device__ __forceinline__ uint2 lds64(uint32_t a) { uint2 v; asm volatile("ld.shared.v2.u32 {%0,%1}, [%2];" : "=r"(v.x), "=r"(v.y) : "r"(a) : "memory"); return v; }
__device__ __forceinline__ uint4 ldcg128(const void* p) { uint4 v; asm volatile("ld.global.cg.v4.u32 {%0,%1,%2,%3}, [%4];" : "=r"(v.x), "=r"(v.y), "=r"(v.z), "=r"(v.w) : "l"(p) : "memory"); return v; }
__device__ __forceinline__ uint32_t ldnc16(const void* p) { uint16_t v; asm volatile("ld.global.nc.u16 %0, [%1];" : "=h"(v) : "l"(p)); return v; }
__device__ __forceinline__ uint4 ldnc128(const void* p) { uint4 v; asm volatile("ld.global.nc.v4.u32 {%0,%1,%2,%3}, [%4];" : "=r"(v.x), "=r"(v.y), "=r"(v.z), "=r"(v.w) : "l"(p)); return v; }
__device__ __forceinline__ void cp_async16(uint32_t dst, const void* src) { asm volatile("cp.async.cg.shared.global [%0], [%1], 16;" ::"r"(dst), "l"(src) : "memory"); }
__device__ __forceinline__ uint32_t hsub2(uint32_t a, uint32_t b) { uint32_t d; asm("sub.rn.bf16x2 %0, %1, %2;" : "=r"(d) : "r"(a), "r"(b)); return d; }
__device__ __forceinline__ void stg32_if(bool c, void* p, uint32_t v) {
  asm volatile("{\n.reg .pred P;\nsetp.ne.u32 P, %2, 0;\n@P st.global.u32 [%0], %1;\n}" ::"l"(p), "r"(v), "r"((uint32_t)c) : "memory");
}
__device__ __forceinline__ float wsum(float v) { for (int o = 16; o; o >>= 1) v += __shfl_xor_sync(~0u, v, o); return v; }
__device__ __forceinline__ uint32_t hmul2(uint32_t a, uint32_t b) { uint32_t d; asm("mul.rn.bf16x2 %0, %1, %2;" : "=r"(d) : "r"(a), "r"(b)); return d; }
__device__ __forceinline__ void sts32(uint32_t a, uint32_t v) { asm volatile("st.shared.u32 [%0], %1;" ::"r"(a), "r"(v) : "memory"); }
__device__ __forceinline__ uint32_t lds32(uint32_t a) { uint32_t v; asm volatile("ld.shared.u32 %0, [%1];" : "=r"(v) : "r"(a) : "memory"); return v; }
__device__ __forceinline__ void sts128(uint32_t a, uint32_t x, uint32_t y, uint32_t z, uint32_t w) { asm volatile("st.shared.v4.u32 [%0], {%1,%2,%3,%4};" ::"r"(a), "r"(x), "r"(y), "r"(z), "r"(w) : "memory"); }
__device__ __forceinline__ uint4 lds128(uint32_t a) { uint4 v; asm volatile("ld.shared.v4.u32 {%0,%1,%2,%3}, [%4];" : "=r"(v.x), "=r"(v.y), "=r"(v.z), "=r"(v.w) : "r"(a) : "memory"); return v; }
__device__ __forceinline__ void ll_st64(uint2* p, uint32_t v, uint32_t tag) {
  asm volatile("{\n.reg .b64 r;\nmov.b64 r, {%1,%2};\nst.relaxed.gpu.global.b64 [%0], r;\n}" ::"l"(p), "r"(v), "r"(tag) : "memory");
}
__device__ __forceinline__ uint2 ll_ld64(const uint2* p) {
  uint2 v; asm volatile("{\n.reg .b64 r;\nld.relaxed.gpu.global.b64 r, [%2];\nmov.b64 {%0,%1}, r;\n}" : "=r"(v.x), "=r"(v.y) : "l"(p) : "memory"); return v;
}
__device__ __forceinline__ void ll_st128(uint4* p, float a, float b, uint32_t tag, float c = 0.f) {
  asm volatile("{\n.reg .b128 r;\n.reg .b64 lo, hi;\nmov.b64 lo, {%1,%2};\nmov.b64 hi, {%3,%4};\nmov.b128 r, {lo, hi};\nst.relaxed.gpu.global.b128 [%0], r;\n}" ::"l"(p), "r"(__float_as_uint(a)), "r"(__float_as_uint(b)), "r"(tag), "r"(__float_as_uint(c)) : "memory");
}
__device__ __forceinline__ uint4 ll_ld128g(const void* p) {
  uint4 v; asm volatile("{\n.reg .b128 r;\n.reg .b64 lo, hi;\nld.relaxed.gpu.b128 r, [%4];\nmov.b128 {lo, hi}, r;\nmov.b64 {%0,%1}, lo;\nmov.b64 {%2,%3}, hi;\n}" : "=r"(v.x), "=r"(v.y), "=r"(v.z), "=r"(v.w) : "l"(p) : "memory"); return v;
}
__device__ __forceinline__ uint4 ll_ld128(const uint4* p) {
  uint4 v; asm volatile("{\n.reg .b128 r;\n.reg .b64 lo, hi;\nld.relaxed.gpu.global.b128 r, [%4];\nmov.b128 {lo, hi}, r;\nmov.b64 {%0,%1}, lo;\nmov.b64 {%2,%3}, hi;\n}" : "=r"(v.x), "=r"(v.y), "=r"(v.z), "=r"(v.w) : "l"(p) : "memory"); return v;
}
__device__ __forceinline__ void publish_p(uint32_t el, uint32_t* f) {
  asm volatile("{\n.reg .pred P;\nsetp.ne.u32 P, %1, 0;\n@P cp.async.bulk.commit_group;\n@P cp.async.bulk.wait_group 0;\n@P red.release.gpu.global.add.u32 [%0], 1;\n}" ::"l"(f), "r"(el) : "memory");
}
__device__ __forceinline__ void stsm4(uint32_t addr, uint32_t a, uint32_t b, uint32_t c, uint32_t d) {
  asm volatile("stmatrix.sync.aligned.m8n8.x4.shared.b16 [%0], {%1,%2,%3,%4};" ::"r"(addr), "r"(a), "r"(b), "r"(c), "r"(d) : "memory");
}
__device__ __forceinline__ void sts64(uint32_t a, uint32_t x, uint32_t y) { asm volatile("st.shared.v2.u32 [%0], {%1,%2};" ::"r"(a), "r"(x), "r"(y) : "memory"); }
__device__ __forceinline__ void ll_st128_if(bool on, uint4* p, float a, float b, uint32_t tag) {
  asm volatile("{\n.reg .pred P;\n.reg .b128 r;\n.reg .b64 lo, hi;\nsetp.ne.u32 P, %4, 0;\nmov.b64 lo, {%1,%2};\nmov.b64 hi, {%3,%3};\nmov.b128 r, {lo, hi};\n@P st.relaxed.gpu.global.b128 [%0], r;\n}" ::"l"(p), "r"(__float_as_uint(a)), "r"(__float_as_uint(b)), "r"(tag), "r"((uint32_t)on) : "memory");
}
__device__ __forceinline__ uint4 ldnc128_if(bool c, const void* p) {
  uint4 v = make_uint4(0u, 0u, 0u, 0u);
  asm volatile("{\n.reg .pred P;\nsetp.ne.u32 P, %5, 0;\n@P ld.global.nc.v4.u32 {%0,%1,%2,%3}, [%4];\n}" : "+r"(v.x), "+r"(v.y), "+r"(v.z), "+r"(v.w) : "l"(p), "r"((uint32_t)c));
  return v;
}
__device__ __forceinline__ uint32_t hfma2(uint32_t a, uint32_t b, uint32_t c) { uint32_t d; asm("fma.rn.bf16x2 %0, %1, %2, %3;" : "=r"(d) : "r"(a), "r"(b), "r"(c)); return d; }
__device__ __forceinline__ float2 lds64f(uint32_t a) { float2 v; asm volatile("ld.shared.v2.f32 {%0,%1}, [%2];" : "=f"(v.x), "=f"(v.y) : "r"(a) : "memory"); return v; }
#define TRC(cond, role, idx) do {} while (0)
#define TRV(role, idx, v) do {} while (0)
#define TRVI(c, role, idx, v) do {} while (0)

#define ACLK_INIT do {} while (0)
#define ACLK(i) do {} while (0)
#define ACLK_OUT do {} while (0)
#define QCLK(i) do {} while (0)
#define PH 1
#define RCLK(i) do {} while (0)
#define RCLK_INIT do {} while (0)
#define RCLK_OUT do {} while (0)
#define SCLK(i) do {} while (0)
#define SCLK2(i) do {} while (0)
#define SCLK3(i) do {} while (0)
#define PL 1
#define PCLK(i) do {} while (0)
#define PQ 1
#define CLK_INIT do {} while (0)
#define CLK(i) do {} while (0)
#define CLK_OUT do {} while (0)

__device__ __forceinline__ void wgmma_ss_n216(float* d, uint64_t da, uint64_t db, int scaleD) {
  asm volatile("{\n.reg .pred p;\nsetp.ne.b32 p, %110, 0;\nwgmma.mma_async.sync.aligned.m64n216k16.f32.bf16.bf16 "
    "{%0,%1,%2,%3,%4,%5,%6,%7,%8,%9,%10,%11,%12,%13,%14,%15,%16,%17,%18,%19,%20,%21,%22,%23,%24,%25,%26,%27,%28,%29,%30,%31,%32,%33,%34,%35,%36,%37,%38,%39,%40,%41,%42,%43,%44,%45,%46,%47,%48,%49,%50,%51,%52,%53,%54,%55,%56,%57,%58,%59,%60,%61,%62,%63,%64,%65,%66,%67,%68,%69,%70,%71,%72,%73,%74,%75,%76,%77,%78,%79,%80,%81,%82,%83,%84,%85,%86,%87,%88,%89,%90,%91,%92,%93,%94,%95,%96,%97,%98,%99,%100,%101,%102,%103,%104,%105,%106,%107}, "
    "%108, %109, p, 1, 1, 0, 1;\n}\n"
    : "+f"(d[0]), "+f"(d[1]), "+f"(d[2]), "+f"(d[3]), "+f"(d[4]), "+f"(d[5]), "+f"(d[6]), "+f"(d[7]), "+f"(d[8]), "+f"(d[9]), "+f"(d[10]), "+f"(d[11]), "+f"(d[12]), "+f"(d[13]), "+f"(d[14]), "+f"(d[15]), "+f"(d[16]), "+f"(d[17]), "+f"(d[18]), "+f"(d[19]), "+f"(d[20]), "+f"(d[21]), "+f"(d[22]), "+f"(d[23]), "+f"(d[24]), "+f"(d[25]), "+f"(d[26]), "+f"(d[27]), "+f"(d[28]), "+f"(d[29]), "+f"(d[30]), "+f"(d[31]), "+f"(d[32]), "+f"(d[33]), "+f"(d[34]), "+f"(d[35]), "+f"(d[36]), "+f"(d[37]), "+f"(d[38]), "+f"(d[39]), "+f"(d[40]), "+f"(d[41]), "+f"(d[42]), "+f"(d[43]), "+f"(d[44]), "+f"(d[45]), "+f"(d[46]), "+f"(d[47]), "+f"(d[48]), "+f"(d[49]), "+f"(d[50]), "+f"(d[51]), "+f"(d[52]), "+f"(d[53]), "+f"(d[54]), "+f"(d[55]), "+f"(d[56]), "+f"(d[57]), "+f"(d[58]), "+f"(d[59]), "+f"(d[60]), "+f"(d[61]), "+f"(d[62]), "+f"(d[63]), "+f"(d[64]), "+f"(d[65]), "+f"(d[66]), "+f"(d[67]), "+f"(d[68]), "+f"(d[69]), "+f"(d[70]), "+f"(d[71]), "+f"(d[72]), "+f"(d[73]), "+f"(d[74]), "+f"(d[75]), "+f"(d[76]), "+f"(d[77]), "+f"(d[78]), "+f"(d[79]), "+f"(d[80]), "+f"(d[81]), "+f"(d[82]), "+f"(d[83]), "+f"(d[84]), "+f"(d[85]), "+f"(d[86]), "+f"(d[87]), "+f"(d[88]), "+f"(d[89]), "+f"(d[90]), "+f"(d[91]), "+f"(d[92]), "+f"(d[93]), "+f"(d[94]), "+f"(d[95]), "+f"(d[96]), "+f"(d[97]), "+f"(d[98]), "+f"(d[99]), "+f"(d[100]), "+f"(d[101]), "+f"(d[102]), "+f"(d[103]), "+f"(d[104]), "+f"(d[105]), "+f"(d[106]), "+f"(d[107])
    : "l"(da), "l"(db), "r"(scaleD));
}
__device__ __forceinline__ void wgmma_ss_n72(float* d, uint64_t da, uint64_t db, int scaleD) {
  asm volatile("{\n.reg .pred p;\nsetp.ne.b32 p, %38, 0;\nwgmma.mma_async.sync.aligned.m64n72k16.f32.bf16.bf16 "
    "{%0,%1,%2,%3,%4,%5,%6,%7,%8,%9,%10,%11,%12,%13,%14,%15,%16,%17,%18,%19,%20,%21,%22,%23,%24,%25,%26,%27,%28,%29,%30,%31,%32,%33,%34,%35}, "
    "%36, %37, p, 1, 1, 0, 1;\n}\n"
    : "+f"(d[0]), "+f"(d[1]), "+f"(d[2]), "+f"(d[3]), "+f"(d[4]), "+f"(d[5]), "+f"(d[6]), "+f"(d[7]), "+f"(d[8]), "+f"(d[9]), "+f"(d[10]), "+f"(d[11]), "+f"(d[12]), "+f"(d[13]), "+f"(d[14]), "+f"(d[15]), "+f"(d[16]), "+f"(d[17]), "+f"(d[18]), "+f"(d[19]), "+f"(d[20]), "+f"(d[21]), "+f"(d[22]), "+f"(d[23]), "+f"(d[24]), "+f"(d[25]), "+f"(d[26]), "+f"(d[27]), "+f"(d[28]), "+f"(d[29]), "+f"(d[30]), "+f"(d[31]), "+f"(d[32]), "+f"(d[33]), "+f"(d[34]), "+f"(d[35])
    : "l"(da), "l"(db), "r"(scaleD));
}
__device__ __forceinline__ void wgmma_ss_n128(float* d, uint64_t da, uint64_t db, int scaleD) {
  asm volatile("{\n.reg .pred p;\nsetp.ne.b32 p, %66, 0;\nwgmma.mma_async.sync.aligned.m64n128k16.f32.bf16.bf16 "
    "{%0,%1,%2,%3,%4,%5,%6,%7,%8,%9,%10,%11,%12,%13,%14,%15,%16,%17,%18,%19,%20,%21,%22,%23,%24,%25,%26,%27,%28,%29,%30,%31,%32,%33,%34,%35,%36,%37,%38,%39,%40,%41,%42,%43,%44,%45,%46,%47,%48,%49,%50,%51,%52,%53,%54,%55,%56,%57,%58,%59,%60,%61,%62,%63}, "
    "%64, %65, p, 1, 1, 0, 1;\n}\n"
    : "+f"(d[0]), "+f"(d[1]), "+f"(d[2]), "+f"(d[3]), "+f"(d[4]), "+f"(d[5]), "+f"(d[6]), "+f"(d[7]), "+f"(d[8]), "+f"(d[9]), "+f"(d[10]), "+f"(d[11]), "+f"(d[12]), "+f"(d[13]), "+f"(d[14]), "+f"(d[15]), "+f"(d[16]), "+f"(d[17]), "+f"(d[18]), "+f"(d[19]), "+f"(d[20]), "+f"(d[21]), "+f"(d[22]), "+f"(d[23]), "+f"(d[24]), "+f"(d[25]), "+f"(d[26]), "+f"(d[27]), "+f"(d[28]), "+f"(d[29]), "+f"(d[30]), "+f"(d[31]), "+f"(d[32]), "+f"(d[33]), "+f"(d[34]), "+f"(d[35]), "+f"(d[36]), "+f"(d[37]), "+f"(d[38]), "+f"(d[39]), "+f"(d[40]), "+f"(d[41]), "+f"(d[42]), "+f"(d[43]), "+f"(d[44]), "+f"(d[45]), "+f"(d[46]), "+f"(d[47]), "+f"(d[48]), "+f"(d[49]), "+f"(d[50]), "+f"(d[51]), "+f"(d[52]), "+f"(d[53]), "+f"(d[54]), "+f"(d[55]), "+f"(d[56]), "+f"(d[57]), "+f"(d[58]), "+f"(d[59]), "+f"(d[60]), "+f"(d[61]), "+f"(d[62]), "+f"(d[63])
    : "l"(da), "l"(db), "r"(scaleD));
}
__device__ __forceinline__ void wgmma_ss_n160(float* d, uint64_t da, uint64_t db, int scaleD) {
  asm volatile("{\n.reg .pred p;\nsetp.ne.b32 p, %82, 0;\nwgmma.mma_async.sync.aligned.m64n160k16.f32.bf16.bf16 "
    "{%0,%1,%2,%3,%4,%5,%6,%7,%8,%9,%10,%11,%12,%13,%14,%15,%16,%17,%18,%19,%20,%21,%22,%23,%24,%25,%26,%27,%28,%29,%30,%31,%32,%33,%34,%35,%36,%37,%38,%39,%40,%41,%42,%43,%44,%45,%46,%47,%48,%49,%50,%51,%52,%53,%54,%55,%56,%57,%58,%59,%60,%61,%62,%63,%64,%65,%66,%67,%68,%69,%70,%71,%72,%73,%74,%75,%76,%77,%78,%79}, "
    "%80, %81, p, 1, 1, 0, 1;\n}\n"
    : "+f"(d[0]), "+f"(d[1]), "+f"(d[2]), "+f"(d[3]), "+f"(d[4]), "+f"(d[5]), "+f"(d[6]), "+f"(d[7]), "+f"(d[8]), "+f"(d[9]), "+f"(d[10]), "+f"(d[11]), "+f"(d[12]), "+f"(d[13]), "+f"(d[14]), "+f"(d[15]), "+f"(d[16]), "+f"(d[17]), "+f"(d[18]), "+f"(d[19]), "+f"(d[20]), "+f"(d[21]), "+f"(d[22]), "+f"(d[23]), "+f"(d[24]), "+f"(d[25]), "+f"(d[26]), "+f"(d[27]), "+f"(d[28]), "+f"(d[29]), "+f"(d[30]), "+f"(d[31]), "+f"(d[32]), "+f"(d[33]), "+f"(d[34]), "+f"(d[35]), "+f"(d[36]), "+f"(d[37]), "+f"(d[38]), "+f"(d[39]), "+f"(d[40]), "+f"(d[41]), "+f"(d[42]), "+f"(d[43]), "+f"(d[44]), "+f"(d[45]), "+f"(d[46]), "+f"(d[47]), "+f"(d[48]), "+f"(d[49]), "+f"(d[50]), "+f"(d[51]), "+f"(d[52]), "+f"(d[53]), "+f"(d[54]), "+f"(d[55]), "+f"(d[56]), "+f"(d[57]), "+f"(d[58]), "+f"(d[59]), "+f"(d[60]), "+f"(d[61]), "+f"(d[62]), "+f"(d[63]), "+f"(d[64]), "+f"(d[65]), "+f"(d[66]), "+f"(d[67]), "+f"(d[68]), "+f"(d[69]), "+f"(d[70]), "+f"(d[71]), "+f"(d[72]), "+f"(d[73]), "+f"(d[74]), "+f"(d[75]), "+f"(d[76]), "+f"(d[77]), "+f"(d[78]), "+f"(d[79])
    : "l"(da), "l"(db), "r"(scaleD));
}
__device__ __forceinline__ void wgmma_rs_n144(float* d, const uint32_t* a, uint64_t db, int scaleD) {
  asm volatile("{\n.reg .pred p;\nsetp.ne.b32 p, %77, 0;\nwgmma.mma_async.sync.aligned.m64n144k16.f32.bf16.bf16 "
    "{%0,%1,%2,%3,%4,%5,%6,%7,%8,%9,%10,%11,%12,%13,%14,%15,%16,%17,%18,%19,%20,%21,%22,%23,%24,%25,%26,%27,%28,%29,%30,%31,%32,%33,%34,%35,%36,%37,%38,%39,%40,%41,%42,%43,%44,%45,%46,%47,%48,%49,%50,%51,%52,%53,%54,%55,%56,%57,%58,%59,%60,%61,%62,%63,%64,%65,%66,%67,%68,%69,%70,%71}, "
    "{%72,%73,%74,%75}, %76, p, 1, 1, 1;\n}\n"
    : "+f"(d[0]), "+f"(d[1]), "+f"(d[2]), "+f"(d[3]), "+f"(d[4]), "+f"(d[5]), "+f"(d[6]), "+f"(d[7]), "+f"(d[8]), "+f"(d[9]), "+f"(d[10]), "+f"(d[11]), "+f"(d[12]), "+f"(d[13]), "+f"(d[14]), "+f"(d[15]), "+f"(d[16]), "+f"(d[17]), "+f"(d[18]), "+f"(d[19]), "+f"(d[20]), "+f"(d[21]), "+f"(d[22]), "+f"(d[23]), "+f"(d[24]), "+f"(d[25]), "+f"(d[26]), "+f"(d[27]), "+f"(d[28]), "+f"(d[29]), "+f"(d[30]), "+f"(d[31]), "+f"(d[32]), "+f"(d[33]), "+f"(d[34]), "+f"(d[35]), "+f"(d[36]), "+f"(d[37]), "+f"(d[38]), "+f"(d[39]), "+f"(d[40]), "+f"(d[41]), "+f"(d[42]), "+f"(d[43]), "+f"(d[44]), "+f"(d[45]), "+f"(d[46]), "+f"(d[47]), "+f"(d[48]), "+f"(d[49]), "+f"(d[50]), "+f"(d[51]), "+f"(d[52]), "+f"(d[53]), "+f"(d[54]), "+f"(d[55]), "+f"(d[56]), "+f"(d[57]), "+f"(d[58]), "+f"(d[59]), "+f"(d[60]), "+f"(d[61]), "+f"(d[62]), "+f"(d[63]), "+f"(d[64]), "+f"(d[65]), "+f"(d[66]), "+f"(d[67]), "+f"(d[68]), "+f"(d[69]), "+f"(d[70]), "+f"(d[71])
    : "r"(a[0]), "r"(a[1]), "r"(a[2]), "r"(a[3]), "l"(db), "r"(scaleD));
}
__device__ __forceinline__ void wgmma_rs_n64(float* d, const uint32_t* a, uint64_t db, int scaleD) {
  asm volatile("{\n.reg .pred p;\nsetp.ne.b32 p, %37, 0;\nwgmma.mma_async.sync.aligned.m64n64k16.f32.bf16.bf16 "
    "{%0,%1,%2,%3,%4,%5,%6,%7,%8,%9,%10,%11,%12,%13,%14,%15,%16,%17,%18,%19,%20,%21,%22,%23,%24,%25,%26,%27,%28,%29,%30,%31}, "
    "{%32,%33,%34,%35}, %36, p, 1, 1, 1;\n}\n"
    : "+f"(d[0]), "+f"(d[1]), "+f"(d[2]), "+f"(d[3]), "+f"(d[4]), "+f"(d[5]), "+f"(d[6]), "+f"(d[7]), "+f"(d[8]), "+f"(d[9]), "+f"(d[10]), "+f"(d[11]), "+f"(d[12]), "+f"(d[13]), "+f"(d[14]), "+f"(d[15]), "+f"(d[16]), "+f"(d[17]), "+f"(d[18]), "+f"(d[19]), "+f"(d[20]), "+f"(d[21]), "+f"(d[22]), "+f"(d[23]), "+f"(d[24]), "+f"(d[25]), "+f"(d[26]), "+f"(d[27]), "+f"(d[28]), "+f"(d[29]), "+f"(d[30]), "+f"(d[31])
    : "r"(a[0]), "r"(a[1]), "r"(a[2]), "r"(a[3]), "l"(db), "r"(scaleD));
}

template <int V> struct Int { static constexpr int value = V; };
struct Cur {
  uint32_t s, ph;
  __device__ __forceinline__ void next() { if (++s == NST) { s = 0; ph ^= 1; } }
};

__device__ __forceinline__ uint32_t o_place(uint32_t w, uint32_t e) { return (((w ? 0xd5310u : 0xa8d57u) >> (4 * e)) & 15) * 8192 + 90112; }
#define z1_block(rb, w, j) (Q.Z + ((rb) * 16 + (w) * 8 + (j)) * ZB)
#define xn_block(hw) (Q.Z + (512 + (hw) * 2) * ZB)
#define z2_block(kb, j) (Q.Z + (256 + (kb) * 8 + (j)) * ZB)
template <int N> __device__ __forceinline__ void pause(uint32_t zero) {
  if (N <= 0) return;
  uint32_t z = clock() + threadIdx.x;
  do {
#pragma unroll (N > 8 ? 1 : 8)
    for (int i = 0; i < N; i++) asm volatile("shfl.sync.bfly.b32 %0, %0, 1, 0x1f, 0xffffffff;" : "+r"(z)::"memory");
  } while (__any_sync(~0u, z & zero));
}

__global__ void __cluster_dims__(2, 1, 1) __launch_bounds__(384, 1) mega_kernel(const Ptrs Q, const __grid_constant__ Params P) {
  extern __shared__ __align__(1024) uint8_t smem_raw[];
  const uint32_t sb = smem_u32(smem_raw);
  const uint32_t bars = sb + SM_BAR;
  const int tid = threadIdx.x;
  int lane = tid & 31;
  const int wid = __shfl_sync(~0u, tid >> 5, 0);
  const int cl = blockIdx.x >> 1;
  const int bid = (cl < 4 ? cl * 8 + 32 : cl - 4 + (max(cl - 29, 0) * 37 >> 8)) * 2 + (blockIdx.x & 1);
  const int rb = bid & 15, j = bid >> 4;
  uint4 wv[5];
  {
    const int n8 = min(tid >> 3, 26), part = n8 / 9;
    const uint8_t* src = (const uint8_t*)Q.wqkv + (8 * rb + (tid & 7)) * (3 * DM * 2) + (part * (DM - 72) + 72 * j + 8 * n8) * 2;
#pragma unroll
    for (int u = 0; u < 5; u++) wv[u] = ldnc128_if(tid < 216 && cl < 64 && (u < 4 || rb < 8), src + u * (128 * 3 * DM * 2));
  }
  if (cl >= 64) return;
  if (wid >= 7 && lane == 0) {
    if (wid < 10) {
#pragma unroll
      for (uint32_t b = 0; b < B_AD / 3; b += 8) mbar_init(bars + (wid - 7) * (B_AD / 3) + b, 1);
    } else if (wid == 10) {
#pragma unroll
      for (uint32_t b = B_AD; b < B_EVT; b += 8) mbar_init(bars + b, b < B_LAG ? 2 : 4);
    } else {
#pragma unroll
      for (uint32_t b = B_EVT; b < 1024; b += 8) if (b < B_OFF || b >= B_IMG) mbar_init(bars + b, b < B_IMG ? 4 : b < B_EMPTY ? 8 : 16);
    }
    asm volatile("fence.mbarrier_init.release.cluster;" ::: "memory");
  }
  __syncthreads();

  if (wid >= 8) {
    reg_dealloc<56>();
    const uint32_t el = elect_one();
    const uint64_t pol = policy_evict_first();
    uint32_t* const fj = Q.flags + FJ + j * 32;
    if (wid == 8) {
      if (el) { prefetch_map(&P.wsp); prefetch_map(&P.winb[j & 1]); prefetch_map(&P.wins); prefetch_map(&P.wout); prefetch_map(&P.act[1]); prefetch_map(&P.res[0]); prefetch_map(&P.res[1]); prefetch_map(&P.row[1]); }
      const uint32_t epoch = ldcg32(fj + FJ_EP + rb);
      Cur c{0, 1};
      const uint32_t rk = bid & 1;
      uint32_t st, full;
      auto slot = [&](uint32_t bytes) {
        st = sb + c.s * ST_BYTES; full = bars + B_FULL + c.s * 8;
        mbar_wait(full, c.ph);
        expect_tx_p(el, full, bytes);
        mbar_wait(full - B_FULL + B_EMPTY, c.ph);
      };
#pragma unroll 1
      for (int L = 0; L < 2; L++) {
#pragma unroll 1
        for (int i = 0; i < 9; i++) {
          if (L == 0 && i == 0) {
            flag_wait(fj + FJ_WQ, (epoch + 1) * 16);
            fence_async_g();
            TRC(el, 2, 45);
          }
          if (L == 1 && i == QG) mbar_wait(bars + B_FULLA + 24, 0);
          slot(27648);
          bulk_mc_h(el, st + ST_B + rk * 13824, Q.WQ + j * WQ_SL + i * 27648 + rk * 13824, 13824, full, EF(0), pol);
          c.next();
        }
        if (L == 0) {
          flag_wait(fj + FJ_WO, (epoch + 1) * 16);
          fence_async_g();
          TRC(el, 2, 46);
        }
#pragma unroll 1
        while (c.s) {
          mbar_wait(bars + B_EMPTY + c.s * 8, c.ph);
          if (el) { mbar_arrive(bars + B_FULL + c.s * 8); asm volatile("mbarrier.arrive.shared::cta.b64 _, [%0], 16;" ::"r"(bars + B_EMPTY + c.s * 8) : "memory"); }
          c.next();
        }
        expect_tx_p(el, bars + B_WF, WO_SL);
        mbar_wait(bars + B_EMPTY, c.ph);
        mbar_wait(bars + B_EMPTY + 8, c.ph);
        bulk_mc_h(el, sb + rk * (WO_SL / 2), Q.WO + j * WO_SL + rk * (WO_SL / 2), WO_SL / 2, bars + B_WF, EF(1), pol);
#pragma unroll 1
        for (int r = 0; r < 10; r++) {
          const bool big = r >= 2 && r < 8;
          const int a0 = (r < 5 ? 36 : 0) + ((9 * j) >> 1) + (big ? 2 - 2 * (j & 1) : 3 * (j & 1) + rk), ks = big ? 32 : 48;
          int k = big ? (r < 5 ? r - 2 : r - 5) * 192 + rk * 16 : (r & 1) * 288;
          const CUtensorMap* m = big ? &P.winb[j & 1] : &P.wins;
          const uint32_t dst = sb + SM_B3 + rk * 6144;
#pragma unroll
          for (int p = 0; p < 6; p++, k += ks) {
            if (!(p & 3) && r == 0) mbar_wait(bars + B_XD + p * 2, L);
            if (p) mbar_wait_c(bars + B_E3 + p * 8, ~r & 1); else mbar_wait(bars + B_E3, ~r & 1);
            expect_tx_p(el, bars + B_F3 + p * 8, 12288);
            tma3d_mc_h(el, dst + p * 12288, m, 0, k, a0, bars + B_F3 + p * 8, EF(2), pol);
          }
        }
        TRC(el, 2, L * 16 + 6);
        mbar_wait(bars + B_ZOK, L);
        fence_async_g();
        TRC(el, 2, L * 16 + 7);
        const uint8_t* src = z2_block(0, j) + rk * 18432;
#pragma unroll 1
        for (int r = 0; r < 8; r++) {
          const int k = (r & 3) * 512 + ((r >> 2) ^ 1) * 64;
#pragma unroll
          for (int p = 0; p < 4; p++, src += 8 * ZB) {
            if ((p == 1 || p == 2) && r == 0) mbar_wait(bars + B_E3 - 8 + p * 24, 1);
            mbar_wait_c(bars + B_AD + p * 8, ~r & 1);
            if (p) mbar_wait_c(bars + B_EMPTY + p * 8, c.ph); else mbar_wait(bars + B_EMPTY, c.ph);
            expect_tx_p(el, bars + B_FULL + p * 8, ST_BYTES);
            bulk_mc_h(el, sb + p * ST_BYTES + ST_B + rk * 18432, src, 18432, bars + B_FULL + p * 8, EF(4), pol);
            tma3d_h(el, sb + p * ST_BYTES, &P.wsp, k + p * 128, rb * 64, 0, bars + B_FULL + p * 8, EF(3), pol);
          }
          c.ph ^= 1;
        }
        mbar_wait(bars + B_Z1, L);
        fence_async_g();
#pragma unroll 1
        for (int i = 0; i < 11; i++) {
          const int cb = i - 2 + j;
          if (i < 4) mbar_wait(bars + B_AD + c.s * 8, 1);
          slot(ZB);
          if (i < 2) bulk_load_h(el, st + ST_B, z1_block(rb, i, j), ZB, full, true, pol);
          else tma2d_mc_h(el, st + ST_B + rk * 18432, &P.wout, (cb >= 9 ? cb - 9 : cb) * 64, 288 * j + rk * 144, full, EF(5), pol);
          c.next();
        }
      }
    } else if (wid < 11) {
      uint32_t id = bid * 2 + wid - 9;
#define AGENT_IDS asm volatile("" : "+r"(lane), "+r"(id)); const uint32_t w = id & 1, hw = id & 31, rb = hw >> 1, j = id >> 5, ev = bars + B_EVT + w * EV_N * 8; \
      uint32_t* const fr = Q.flags + hw * 32; uint32_t* const fj = Q.flags + FJ + j * 32; (void)fr; (void)fj; (void)ev; (void)rb
      uint32_t t8 = 0;
      Cur c{0, 1};
#pragma unroll 1
      for (int L = 0; L < 2; L++) {
        if (L) {
          AGENT_IDS;
          const uint32_t full = bars + B_FULLA + w * 32 + c.s * 8, dst = sb + c.s * ST_BYTES + w * 8192;
          expect_tx_p(el, full, 8192);
          mbar_wait_c(ev + EV_PT * 8, 1);
          TRC(el, 3, w * 32 + 16);
          flag_release_p(el, fr + FR_X2);
          TRC(el, 3, w * 32 + 17);
          mbar_wait_c(bars + B_EMPTY + c.s * 8, c.ph);
          flag_wait(fr + FR_X2, t8);
          fence_async_g();
          tma3d_h(el, dst, &P.act[1], 0, rb * 64, w, full, false, pol);
          c.next();
          TRC(el, 3, w * 32 + 18);
        }
#pragma unroll 1
        for (int i = L; i < 9; i++) {
          AGENT_IDS;
          const uint32_t full = bars + B_FULLA + w * 32 + c.s * 8, dst = sb + c.s * ST_BYTES + w * 8192;
          if (L == 0 && i == AEP) t8 = (ldcg32(fr + FR_EP + j) + 1) * 8;
          mbar_wait_c(bars + B_EMPTY + c.s * 8, c.ph);
          expect_tx_p(el, full, 8192);
          tma3d_h(el, dst, &P.act[L], i * 64, rb * 64, w, full, false, pol);
          c.next();
          if (i == PZI || i == PZI + 1) {
            uint8_t* d = (i == PZI ? xn_block(hw) : z1_block(rb, 0, 0) + w * 4608) + j * 9216 + lane * 16;
#pragma unroll 1
            for (int u = i == PZI ? 0 : 3; u < 6; u++, d += 1536) { stg128(d, ~0u, ~0u, ~0u, ~0u); stg128(d + 512, ~0u, ~0u, ~0u, ~0u); stg128(d + 1024, ~0u, ~0u, ~0u, ~0u); }
          }
          if (i == PZI) { stg128(Q.ST1 + (hw * 8 + j) * 32 + lane, ~0u, ~0u, ~0u, ~0u); stg128(Q.ZST + (hw * 8 + j) * 32 + lane, ~0u, ~0u, ~0u, ~0u); }
          if (i == RFI) {
            expect_tx_p(el, bars + B_WT + w * 8, 9216);
            tma3d_h(el, sb + SM_STG + w * 9216, &P.row[L], 0, 3 * w, rb * 64 + 8 * j, bars + B_WT + w * 8, false, pol);
          }
          if (i == 4 && L > w) {
            expect_tx_p(el, bars + B_XRW + 8, 864);
            bulk_load_p(el, sb + 3 * ST_BYTES + SM_CSQ, Q.CSP + (NCTA + (id >> 1)) * 216, 864, bars + B_XRW + 8);
          }
        }
        if (c.s) { c.s = 0; c.ph ^= 1; }
        {
          AGENT_IDS;
          const uint32_t tag = (t8 >> 2) - 1 + L;
          uint4* const xs = Q.XST + hw * 128;
          const uint32_t tab = sb + L * (3 * ST_BYTES) + SM_XST + w * 768 + lane * 8;
          TRC(el, 3, w * 32 + L * 16 + 13);
#pragma unroll 1
          for (int it = 0; it < (1 << 22); it++) {
            const uint4 a = ll_ld128(xs + 2 * lane), b = ll_ld128(xs + 64 + 2 * lane), h = ll_ld128(xs - (rb ? 192 : 0) + 2 * (lane | 24));
            if (__all_sync(~0u, a.z == tag && b.z == tag && h.z == tag)) { sts64(tab, h.x, h.y); sts64(tab + 256, a.x, a.y); sts64(tab + 512, b.x, b.y); break; }
          }
          __syncwarp();
          if (el) mbar_arrive(bars + B_CSQ);
          TRC(el, 3, w * 32 + L * 16 + 14);
          uint32_t* f = Q.flags + rb * 64 + FR_PZ + L;
          flag_release_p(el, f);
          expect_tx_p(el, bars + B_RES + w * 8, 9216);
          tma3d_h(el, sb + SM_STG + w * 9216, &P.res[L], j * 72, (hw ^ 1) * 32, 0, bars + B_RES + w * 8, !L, pol);
          pause<FD3>(Q.zero);
          flag_wait(f, t8 * 2);
          fence_async_g();
          TRC(el, 3, w * 32 + L * 16 + 15);
        }
        {
          AGENT_IDS;
          uint32_t* f = Q.flags + rb * 64 + FR_O + L;
#pragma unroll 1
          for (int e = 0; e < 5; e++) {
            const uint32_t nb = e ? 16384 : 8192, full = bars + B_OF + w * 40 + e * 8, dst = sb + o_place(w, e);
            const uint8_t* src = z1_block(rb, w, 0) + (e ? e * 16384 - 8192 : 0);
            expect_tx_p(el, full, nb);
            if (e == 0) {
              mbar_wait_c(ev + EV_O * 8, L);
              TRC(el, 3, w * 32 + L * 16 + 3);
              if (!w) flag_add_p(el, f);
              flag_wait(f + w * (FR_OL - FR_O), t8);
              if (w) fence_async_g();
            }
            if (w && (e == 0 || e == 3)) mbar_wait_c(bars + (e ? B_X3 : B_OF + YPACE * 8), L);
            bulk_load_h(el, dst, src, nb, full, EF(6), pol);
            TRC(el && e == 0, 3, w * 32 + L * 16 + 5);
          }
        }
        {
          AGENT_IDS;
          const uint8_t* src = xn_block(hw);
          uint32_t full = bars + B_AF3 + w * 96, dst = sb + w * 6144;
          if (L) flag_wait(fj + FJ_P4, t8 * 4);
          mbar_wait_c(bars + B_XD + 8, L);
          mbar_wait_c(ev + EV_X1 * 8, L);
          TRC(el, 3, w * 32 + L * 16 + 6);
          pause<SDEL>(Q.zero);
#pragma unroll 1
          for (int k = 0; k < 12; k++, src += 6144, dst += 12288, full += 8) {
            expect_tx_p(el, full, 6144);
            if (k >= APACE) mbar_wait_c(full - APACE * 8, L);
            bulk_load_h(el, dst, src, 6144, full, EF(7), pol);
            TRC(el && k == 0, 3, w * 32 + L * 16 + 8);
          }
        }
        if (wid == 10) {
          AGENT_IDS;
          mbar_wait_c(ev - (EV_N - EV_ZN) * 8, L);
          mbar_wait_c(ev + EV_ZN * 8, L);
          asm volatile("fence.release.gpu;" ::: "memory");
          flag_add_p(el, fj + FJ_ZN + L);
          flag_add_p(el, fr - 32 + FR_XR + L);
          pause<FD4>(Q.zero);
          flag_wait(fj + FJ_ZN + L, t8 * 2);
          flag_wait(fr - 32 + FR_XR + L, t8);
          if (el) mbar_arrive(bars + B_ZOK);
        } else if (WPF) {
          AGENT_IDS;
          mbar_wait_c(ev + EV_ZN * 8, L);
          if (el) asm volatile("cp.async.bulk.prefetch.tensor.3d.L2.global [%0, {%1, %2, %3}];" ::"l"(&P.wsp), "r"(j * 128 + 64), "r"(rb * 64), "r"(0) : "memory");

        }
        float cv;
        {
        AGENT_IDS;
        cv = (lane & 3) ? 0.f : -blo(ldnc16(Q.b_sp + 128 * rb + 16 * j + 2 * (lane >> 2) + w));
        const uint32_t ro = (w * 64 + 8 * j + (lane >> 2)) * 128, x0 = ((lane & 3) * 2) ^ (lane >> 2);
#pragma unroll 1
        for (int i = 0; i < 32; i++) {
          const bool tail = (i >> 1) == 12;
          const int kb = tail ? i + 6 : i < 24 ? i : i - 2;
          if (!(i & 7)) mbar_wait_c(bars + B_RT + i, L);
          if (i == 24) mbar_wait_c(bars + B_WT + w * 8, 1);
          if (!tail) mbar_wait(bars + B_FULL + c.s * 8, c.ph ^ 1);
          uint4 x[2];
#pragma unroll
          for (int e = 0; e < 2; e++) x[e] = lds128(!tail ? sb + c.s * ST_BYTES + ro + ((x0 ^ e) << 4) : sb + SM_WT + w * 3200 + (lane >> 2) * 400 + (i - 24) * 256 + (lane & 3) * 32 + e * 16);
          if (!tail) {
            __syncwarp();
            if (el) mbar_arrive(bars + B_AD + c.s * 8);
            c.next();
          }
#pragma unroll
          for (int e = 0; e < 2; e++) {
            const uint4 a = x[e], m = lds128(sb + SM_RT + 4096 + kb * 128 + (lane & 3) * 32 + e * 16);
            cv = fmaf(blo(a.x), blo(m.x), fmaf(bhi(a.x), bhi(m.x), fmaf(blo(a.y), blo(m.y), fmaf(bhi(a.y), bhi(m.y), cv))));
            cv = fmaf(blo(a.z), blo(m.z), fmaf(bhi(a.z), bhi(m.z), fmaf(blo(a.w), blo(m.w), fmaf(bhi(a.w), bhi(m.w), cv))));
          }
          if (i == WTI) {
            uint32_t id2 = id;
            asm volatile("" : "+r"(id2));
            expect_tx_p(el, bars + B_WT + w * 8, 3072);
#pragma unroll 1
            for (int r = 0; r < 8; r++)
              bulk_load_p(el, sb + SM_WT + w * 3200 + r * 400, (const uint8_t*)Q.w_sp + (64 * (id2 & 30) + 16 * (id2 >> 5) + 2 * r + w) * (SEQ * 2) + 28 * 128, 384, bars + B_WT + w * 8);
          }
        }
        }
        AGENT_IDS;
        TRC(el, 3, w * 32 + L * 16 + 11);
        asm volatile("" : "+r"(t8));
        const uint32_t tag = (t8 >> 2) - 1 + L;
        cv = qsum(cv);
        uint2* const cs = (uint2*)(Q.XST + hw * 128 + 1);
        if ((lane & 3) == 0) ll_st64(cs + 32 * j + (lane >> 2) * 4, __float_as_uint(cv), tag);
        pause<FD5>(Q.zero);
#pragma unroll 1
        for (int it = 0; it < (1 << 22); it++) {
          const uint2 a = ll_ld64(cs + 4 * lane), b = ll_ld64(cs + 128 + 4 * lane);
          if (__all_sync(~0u, a.y == tag && b.y == tag)) { sts32(sb + SM_CV + w * 256 + lane * 4, a.x); sts32(sb + SM_CV + w * 256 + 128 + lane * 4, b.x); break; }
        }
        __syncwarp();
        if (el) mbar_arrive(bars + B_CV + w * 8);
        TRC(el, 3, w * 32 + L * 16 + 12);
#pragma unroll 1
        for (int kb = 30; kb < 32; kb++) {
          mbar_wait_c(bars + B_FULL + c.s * 8, c.ph ^ 1);
          if (el) mbar_arrive(bars + B_AD + c.s * 8);
          c.next();
        }
        c.ph ^= ((c.s + 11) >> 2) & 1; c.s = (c.s + 11) & 3;
        if (L == 0) {
          mbar_wait_c(ev + EV_PT * 8, 0);
          flag_add_p(el, fj + FJ_P4);
        }
      }
    } else {
      const uint32_t epoch = ldcg32(fj + FJ_EP + rb);
      mbar_wait(bars + B_IMG, 0);
      TRC(el, 2, 41);
      flag_release_p(el, fj + FJ_WQ);
      TRC(el, 2, 42);
#pragma unroll 1
      for (int L = 0; L < 2; L++) {
        float* const csf = Q.CSP + (NCTA + bid) * 216;
        if (L == 0) {
          flag_wait(fj + FJ_WQ, (epoch + 1) * 16);
          fence_async_g();
          expect_tx_p(el, bars + B_XRW, 13824);
          bulk_load_p(el, sb + ST_BYTES + SM_WOI, Q.CSP + j * 16 * 216, 6912, bars + B_XRW);
          bulk_load_p(el, sb + 2 * ST_BYTES + SM_WOI, Q.CSP + (j * 16 + 8) * 216, 6912, bars + B_XRW);
          mbar_wait(bars + B_XRW, 0);
#pragma unroll 1
          for (int f = lane; f < 54; f += 32) {
            float s[4] = {0.f, 0.f, 0.f, 0.f};
#pragma unroll 2
            for (int r = 0; r < 16; r++) {
              const uint4 v = lds128(sb + ST_BYTES + SM_WOI + (r >> 3) * ST_BYTES + (r & 7) * 864 + f * 16);
              s[0] += __uint_as_float(v.x); s[1] += __uint_as_float(v.y); s[2] += __uint_as_float(v.z); s[3] += __uint_as_float(v.w);
            }
            sts128(sb + SM_CSQ + f * 16, __float_as_uint(s[0]), __float_as_uint(s[1]), __float_as_uint(s[2]), __float_as_uint(s[3]));
            stg128(csf + f * 4, __float_as_uint(s[0]), __float_as_uint(s[1]), __float_as_uint(s[2]), __float_as_uint(s[3]));
          }
          __syncwarp();
          if (el) mbar_arrive(bars + B_XRW + 8);
          TRC(el, 2, 43);
          mbar_wait(bars + B_WOI, 0);
          bulk_store_p(el, Q.WO + j * WO_SL + rb * (41 * 128), sb + SM_WOI, (rb < 15 ? 41 : 33) * 128);
          publish_p(el, fj + FJ_WO);
          TRC(el, 2, 44);
          if (el) prefetch_l2((const uint8_t*)Q.w_in + bid * 41472, 41472);
          float o0 = 0.f, o1 = 0.f;
#pragma unroll 1
          for (int u = 0; u < 2; u++) {
            const uint8_t* src = (u ? (const uint8_t*)Q.w_sp + 500 * (SEQ * 2) + 2048 : (const uint8_t*)Q.w_in + 100 * (2 * FH * 2) + FH * 2) + lane * 16;
            const uint4 a = ldnc128(src), b = ldnc128(src + 300 * (2 * FH * 2) + 2048);
            const uint32_t x[8] = {a.x, a.y, a.z, a.w, b.x, b.y, b.z, b.w};
            float sq = 0.f;
#pragma unroll
            for (int e = 0; e < 8; e++) sq = fmaf(blo(x[e]), blo(x[e]), fmaf(bhi(x[e]), bhi(x[e]), sq));
            o0 = o1;
            asm("sqrt.approx.f32 %0, %1;" : "=f"(o1) : "f"(wsum(sq) * (u ? C0S * C0S * SEQ / 512.f : 2.f * GA * GA * DM / 512.f)));
          }
          const uint32_t off = (__float_as_uint(o0) & 0x7f800000u) >> 16 | 0x8000u | OFM;
          const uint32_t c0 = min(max(__float_as_uint(o1) & 0x7f800000u, 0x04000000u), 0x7e000000u) | 0x00400000u;
          if (el) sts128(sb + SM_OFF, off * 0x10001u, c0, __float_as_uint(GB), ((c0 >> 16) - 0x200u) * 0x10001u);
        }
        mbar_wait(bars + B_EVT + EV_O * 8, L);
        mbar_wait(bars + B_EVT + (EV_N + EV_O) * 8, L);
        flag_release_p(el, Q.flags + rb * 64 + FR_OL + L);
#pragma unroll 1
        for (int w = 0; w < 2; w++) {
          mbar_wait(bars + B_EVT + (w * EV_N + EV_XS) * 8, L);
          if (!w) mbar_wait(bars + B_AF3 + 96 + XP0 * 8, L);
          if (el) asm volatile("cp.async.bulk.tensor.3d.global.shared::cta.tile.bulk_group [%0, {%2, %3, %4}], [%1];\ncp.async.bulk.commit_group;\ncp.async.bulk.wait_group.read 0;" ::"l"(&P.res[1]), "r"(sb + SM_STG + 9216), "r"(j * 72), "r"(rb * 64 + (w ^ 1) * 32), "r"(0) : "memory");
          __syncwarp();
          if (lane < 2 && !w) mbar_arrive(bars + B_S5);
        }
        sts64(sb + SM_CV + 512 + lane * 8, 0x3f803f80u, 0x3f803f80u);
        fence_async_s();
        __syncwarp();
        if (el) { asm volatile("cp.async.bulk.wait_group 0;" ::: "memory"); mbar_arrive(bars + B_GATE3); }
        const uint32_t tag = epoch * 2 + L + 1;
        asm volatile("" : "+r"(lane));
#pragma unroll 1
        for (int b = 0; b < 8; b++) {
          if (!(b & 3)) {
            const int mb = b >> 2;
            mbar_wait(bars + B_ZS + mb * 8, L);
            pause<ZD1>(Q.zero);
            TRC(el && !mb, 2, L * 16 + 8);
            uint4 v;
#pragma unroll 1
            for (int it = 0; it < (1 << 22); it++) {
              v = ll_ld128(Q.ZST + ((rb * 2 + mb) * 8 + (lane >> 2)) * 32 + 4 * j + (lane & 3));
              if (__all_sync(~0u, max(max(v.x, v.y), max(v.z, v.w)) != ~0u)) break;
            }
            const bool o = lane & 16;
            float ss = __uint_as_float(o ? v.y : v.x) + __shfl_xor_sync(~0u, __uint_as_float(o ? v.x : v.y), 16), sq = __uint_as_float(o ? v.w : v.z) + __shfl_xor_sync(~0u, __uint_as_float(o ? v.z : v.w), 16);
            ss += __shfl_xor_sync(~0u, ss, 4); sq += __shfl_xor_sync(~0u, sq, 4); ss += __shfl_xor_sync(~0u, ss, 8); sq += __shfl_xor_sync(~0u, sq, 8);
            const float mean = ss * (1.f / FH), rs = blo(pack2(rsq_fast(fmaxf(fmaf(sq, 1.f / FH, -mean * mean), 0.f) + 4.f * GA * GA * LN_EPS), 0.f));
            if (!(lane & 12)) ll_st64(Q.RT + (mb * 16 + rb) * 64 + 8 * j + 2 * (lane & 3) + (lane >> 4), pack2(rs, rs * (mean - blo(lds32(sb + SM_OFF)))), tag);
            TRC(el && !mb, 2, L * 16 + 10);
            pause<ZD2>(Q.zero);
          }
          uint4 v[4];
#pragma unroll 1
          for (int it = 0; it < (1 << 22); it++) {
            bool ok = true;
#pragma unroll
            for (int u = 0; u < 4; u++) { v[u] = ll_ld128((const uint4*)Q.RT + b * 128 + u * 32 + lane); ok = ok && v[u].y == tag && v[u].w == tag; }
            if (__all_sync(~0u, ok)) break;
          }
#pragma unroll
          for (int u = 0; u < 4; u++) {
            const uint32_t rt = sb + SM_RT + b * 512 + u * 128, ro = (lane >> 3) * 32 + (lane & 3) * 8 + ((lane >> 2) & 1) * 2;
            sts32(rt + 4096 + lane * 4, __byte_perm(v[u].x, v[u].z, 0x7632));
            asm volatile("st.shared.u16 [%0], %1;\nst.shared.u16 [%0 + 4], %2;" ::"r"(rt + ro), "h"((uint16_t)v[u].x), "h"((uint16_t)v[u].z) : "memory");
          }
          __syncwarp();
          if (el && (b & 1)) mbar_arrive(bars + B_RT + (b - 1) * 4);
          TRC(el && b < 2, 2, L * 16 + 11 + b);
        }
        TRC(el, 2, L * 16 + 9);
        mbar_wait(bars + B_EVT + EV_Z1 * 8, L);
        mbar_wait(bars + B_EVT + (EV_N + EV_Z1) * 8, L);
        fence_gpu();
        if (el) mbar_arrive(bars + B_Z1);
      }
    }
  } else {
    int w = wid >> 2, q = wid & 3, rb = bid & 15, j = bid >> 4;
    int g = lane >> 2, t = lane & 3;
#define PHASE asm volatile("" : "+r"(w), "+r"(q), "+r"(rb), "+r"(j))
#define stg (sb + SM_STG + w * 9216)
    const bool tr = (tid & 127) == 0;
    (void)tr;
    Cur c{0, 0};
    const uint32_t ebar = mapa(bars + B_EMPTY, (bid & 1) ^ (lane & 1));
    auto release = [&](uint32_t s) { if (lane < 2) mbar_arrive_cluster(ebar + s * 8); };
    uint32_t ia = 0;
    auto wait_ab = [&]() { mbar_wait_c(bars + B_FULL + c.s * 8, c.ph); mbar_wait_c(bars + B_FULLA + w * 32 + c.s * 8, (ia >> c.s) & 1); ia ^= 1u << c.s; };
    uint32_t lagph = 0;
    auto yield = [&](int left, int lag) { if (w == 1 && left == lag) mbar_wait_c(bars + B_LAG, lagph); };
    auto yield_done = [&]() { if (w == 0 && lane == 0) mbar_arrive(bars + B_LAG); };
    uint32_t rp = 0;
    auto check = [&](auto n, uint32_t dst, const uint8_t* src) {
      const uint32_t a = dst + lane * 32 + (lane >> 2) * 4;
#pragma unroll 1
      for (int it = 0; it < (1 << 16); it++) {
        uint32_t x = lds32(a);
#pragma unroll
        for (int e = 1; e < n.value; e++) x = max(x, lds32(a + e * 1024));
        if (!__any_sync(~0u, x == ~0u)) break;
        fence_async_s();
        __syncwarp();
        expect_tx_p(lane == 0, bars + B_RB + q * 8, n.value * 1024);
        bulk_load_p(lane == 0, dst, src, n.value * 1024, bars + B_RB + q * 8);
        mbar_wait_c(bars + B_RB + q * 8, rp & 1);
        rp++;
      }
    };
    auto signal = [&](int e) { __syncwarp(); if (lane == 0) mbar_arrive(bars + B_EVT + w * EV_N * 8 + e * 8); };
    TRC(tr, w, 0);

    {
      uint8_t* dst = Q.WQ + j * WQ_SL + rb * 3456 + tid * 16;
#pragma unroll
      for (int u = 0; u < 5; u++) {
        stg128_if((u < 4 || rb < 8) && tid < 216, dst + u * (16 * 3456), wv[u].x, wv[u].y, wv[u].z, wv[u].w);
        if (u == 0) TRC(tr, w, 60);
      }
      if (Q.zero == 0) {
        float s[8];
#pragma unroll
        for (int u = 0; u < 5; u++) {
          const uint32_t x[4] = {wv[u].x, wv[u].y, wv[u].z, wv[u].w};
#pragma unroll
          for (int e = 0; e < 4; e++) { s[2 * e] = u ? s[2 * e] + blo(x[e]) : blo(x[e]); s[2 * e + 1] = u ? s[2 * e + 1] + bhi(x[e]) : bhi(x[e]); }
        }
#pragma unroll
        for (int m = 4; m; m >>= 1) {
#pragma unroll
          for (int e = 0; e < m; e++) s[e] = ((tid & m) ? s[e + m] : s[e]) + __shfl_xor_sync(~0u, (tid & m) ? s[e] : s[e + m], m);
        }
        stg32_if(tid < 216, Q.CSP + bid * 216 + tid, __float_as_uint(s[0]));
      }
      __syncwarp();
      if (lane == 0) mbar_arrive(bars + B_IMG);
    }
    reg_alloc<224>();
    auto fetch_wo = [&]() {
#pragma unroll 1
      for (int u = tid; u < 328; u += 256) {
        const int m = min(41 * rb + (u >> 3), 647), k8 = m / 9;
        cp_async16(sb + SM_WOI + u * 16, (const uint8_t*)Q.wo + (8 * k8 + (u & 7)) * (DM * 2) + (72 * j + 8 * (m - k8 * 9)) * 2);
      }
    };
    const uint32_t epoch = ldcg32(Q.flags + (rb * 2 + w) * 32 + FR_EP + j);
    TRC(tr, w, 1);

#pragma unroll 1
    for (int L = 0; L < 2; L++) {
      const int tb = 2 + L * 24;
      asm volatile("" : "+r"(lane), "+r"(g), "+r"(t));
      if (PHM & 1) PHASE;
      (void)tb;
      const uint32_t tag = epoch * 2 + L + 1;
      {
        uint32_t Pk[27][2];
        float rk[2][2], sc[2][2];
        const bool up0 = 2 * t > g, up1 = 2 * t + 1 > g;
        constexpr int HA_[6] = {0, 2, 4, 7, 12, 15}, HC_[6] = {6, 9, 10, 11, 14, 17};
        const bool remote = q == 0 && rb > 0;
        uint4* hp = Q.HALO + ((((rb - (q == 0)) * 2 + w) * 8 + j) * 6) * 32 + lane;
        const uint32_t att = 2 * ST_BYTES + w * 8192 + lane * 16;
        const uint8_t* hs = remote ? (const uint8_t*)hp : smem_raw + att + (q == 3 ? ST_BYTES : q == 2 ? 3072 : 0);
        uint8_t* od = z1_block(rb, (q >> 1) ^ 1, 0) + (9 * j) * 1024 + (4 * (q & 1) + w) * 128 + lane * 4;
        ACLK_INIT;
        {
          float acc[108];
#pragma unroll
          for (int i = 0; i < 108; i++) acc[i] = 0.f;
          float sx[2] = {0.f, 0.f}, sq[2] = {0.f, 0.f};
          uint32_t prev = 0;
#pragma unroll 1
          for (int kb = 0; kb < 7; kb++) {
            wait_ab();
            TRC(tr && kb == 0, w, tb + 0);
            PCLK(kb * 4);
            const uint32_t st = sb + c.s * ST_BYTES, da = dlo(st + w * 8192, 16), db = dlo(st + ST_B, 3456);
            wgmma_fence();
#pragma unroll
            for (int kk = 0; kk < 4; kk++) {
              wgmma_ss_n216(acc, dsc<1024, 1>(da, kk * 32), dsc<128, 0>(db, kk * 6912), 1);
              if (kk == 0) { wgmma_commit(); wgmma_wait<1>(); if (kb > 0) release(prev); }
              if (kk == 3) wgmma_commit();
              if (kk == XK1) {
            if (kb >= KS && kb < KS + 3) {
              mbar_wait_c(bars + B_WT + w * 8, 0);
#pragma unroll
              for (int u = 0; u < 3; u++) {
                const uint2 x = lds64(stg + (2 * q + (lane >> 4)) * 1152 + (lane & 15) * 8 + (kb - KS) * 384 + u * 128);
                sx[0] += blo(x.x) + bhi(x.x); sx[1] += blo(x.y) + bhi(x.y);
                sq[0] = fmaf(blo(x.x), blo(x.x), fmaf(bhi(x.x), bhi(x.x), sq[0])); sq[1] = fmaf(blo(x.y), blo(x.y), fmaf(bhi(x.y), bhi(x.y), sq[1]));
              }
            }
            if (kb == KS + 3) {
              const bool o = lane & 1;
              float v = (o ? sq[0] + sq[1] : sx[0] + sx[1]) + __shfl_xor_sync(~0u, o ? sx[0] + sx[1] : sq[0] + sq[1], 1);
              v += __shfl_xor_sync(~0u, v, 2); v += __shfl_xor_sync(~0u, v, 4); v += __shfl_xor_sync(~0u, v, 8);
              const float m = v * (-1.f / DM), r = rsq_fast(fmaxf(fmaf(__shfl_xor_sync(~0u, v, 1), 1.f / DM, -m * m), 0.f) + LN_EPS);
              ll_st128_if(!(lane & 15), Q.XST + (rb * 2 + w) * 128 + 16 * j + 4 * q + (lane >> 3), m, r, tag);
            }
              }
              if (kk == XK2 && L == 0) {
            if (kb == 0) fetch_wo();
            if (kb == 3) {
              asm volatile("cp.async.wait_all;" ::: "memory");
              fence_async_s();
              __syncwarp();
              if (lane == 0) mbar_arrive(bars + B_WOI);
            }
              }
            }
            prev = c.s; c.next();
          }
          const uint32_t ls = sb + L * (3 * ST_BYTES), cs = ls + SM_CSQ + t * 8;
          float2 cv[27];
          mbar_wait_c(bars + B_XRW + 8, L);
#pragma unroll
          for (int kb = 7; kb < 9; kb++) {
            wait_ab();
            yield(9 - kb, LAG1);
            PCLK(kb * 4);
            const uint32_t st = sb + c.s * ST_BYTES, da = dlo(st + w * 8192, 16), db = dlo(st + ST_B, 3456);
            wgmma_fence();
#pragma unroll
            for (int kk = 0; kk < 4; kk++) {
              wgmma_ss_n216(acc, dsc<1024, 1>(da, kk * 32), dsc<128, 0>(db, kk * 6912), 1);
              if (kk == 0) { wgmma_commit(); wgmma_wait<1>(); release(prev); }
              if (kb == 7 && kk < 3) {
#pragma unroll
                for (int G = 9 * kk; G < 9 * kk + 9; G++) cv[G] = lds64f(cs + G * 32);
                wgmma_fence();
              }
            }
            wgmma_commit();
            prev = c.s; c.next();
          }
          yield_done();
          mbar_wait_c(bars + B_CSQ, L);
          const uint32_t xs = ls + SM_XST + w * 768 + 256 + q * 128;
          const float2 n0 = lds64f(xs + g * 8), n1 = lds64f(xs + g * 8 + 64);
          const float m0 = n0.x, m1 = n1.x;
#pragma unroll
          for (int u = 0; u < 4; u++) {
            rk[u >> 1][u & 1] = __uint_as_float(lds32(xs + t * 16 + ((u & 1 ? up1 : up0) ? -64 : 0) + (u & 1) * 8 + (u >> 1) * 64 + 4));
            sc[u >> 1][u & 1] = rk[u >> 1][u & 1] * ((u >> 1 ? n1.y : n0.y) * (0.23570226039551584f * 1.4426950408889634f));
          }
          PCLK(36);
          wgmma_wait<0>();
          PCLK(37);
          release(prev);
          lagph ^= 1;
          TRC(tr, w, tb + 1);
          ACLK(0);
#pragma unroll
          for (int G = 9; G < 27; G++) Pk[G][1] = pack2(fmaf(m1, cv[G].x, acc[4 * G + 2]), fmaf(m1, cv[G].y, acc[4 * G + 3]));
          if (q < 3) {
#pragma unroll
            for (int i = 0; i < 6; i++) sts128(sb + att + (q >> 1) * ST_BYTES + (q & 1) * 3072 + i * 512, Pk[9 + HA_[i]][1], Pk[10 + HA_[i]][1], tag, Pk[9 + HC_[i]][1]);
          } else if (rb < 15) {
#pragma unroll
            for (int i = 0; i < 6; i++) ll_st128(hp + i * 32, __uint_as_float(Pk[9 + HA_[i]][1]), __uint_as_float(Pk[10 + HA_[i]][1]), tag, __uint_as_float(Pk[9 + HC_[i]][1]));
          }
#pragma unroll
          for (int G = 0; G < 27; G++) {
            Pk[G][0] = pack2(fmaf(m0, cv[G].x, acc[4 * G]), fmaf(m0, cv[G].y, acc[4 * G + 1]));
            if (G < 9) Pk[G][1] = pack2(fmaf(m1, cv[G].x, acc[4 * G + 2]), fmaf(m1, cv[G].y, acc[4 * G + 3]));
          }
        }
        ACLK(1);
        constexpr int GA_[4] = {0, 2, 4, 7}, GB_[4] = {1, 3, 5, 8}, GC_[4] = {2, 4, 6, 6};
        float S1[4][4], S2[4][4];
        uint32_t qa[4][2], qc[4][2];
#pragma unroll
        for (int h = 0; h < 4; h++) {
#pragma unroll
          for (int r = 0; r < 2; r++) {
            qa[h][r] = (h == 0 || h == 3 || t >= h) ? Pk[GA_[h]][r] : 0u;
            qc[h][r] = (h == 3 ? t == 3 : t <= h) ? Pk[GC_[h]][r] : 0u;
          }
#pragma unroll
          for (int i = 0; i < 4; i++) S1[h][i] = S2[h][i] = 0.f;
          mma16(S1[h], qa[h][0], qa[h][1], Pk[GB_[h]][0], Pk[GB_[h]][1], Pk[9 + GA_[h]][0], Pk[9 + GB_[h]][0]);
          mma16(S2[h], qa[h][0], qa[h][1], Pk[GB_[h]][0], Pk[GB_[h]][1], Pk[9 + GA_[h]][1], Pk[9 + GB_[h]][1]);
        }
#pragma unroll
        for (int h = 0; h < 4; h++) {
          mma8(S1[h], qc[h][0], qc[h][1], Pk[9 + GC_[h]][0]);
          mma8(S2[h], qc[h][0], qc[h][1], Pk[9 + GC_[h]][1]);
        }
        uint32_t V1[9], V2[9];
#pragma unroll
        for (int i = 0; i < 9; i++) { V1[i] = movm(Pk[18 + i][0]); V2[i] = movm(Pk[18 + i][1]); }
        uint4 hv[6];
#pragma unroll
        for (int i = 0; i < 6; i++) hv[i] = ll_ld128g(hs + i * 512);
        const uint32_t mup = (up0 ? 0xffffu : 0u) | (up1 ? 0xffff0000u : 0u);
        auto finish = [&](const float (&x0)[4], const float (&x1)[4], const uint32_t (&Vb)[9], uint32_t ma, int hi) {
          uint32_t p[4], n[4];
          float rs[4];
#pragma unroll
          for (int h = 0; h < 4; h++) {
            const float m = qmax(fmaxf(x0[h], x1[h])), e0 = ex2(x0[h] - m), e1 = ex2(x1[h] - m);
            n[h] = pack2(e0, e1);
            p[h] = pack2(e0 * rk[hi][0], e1 * rk[hi][1]);
          }
#pragma unroll
          for (int h = 0; h < 4; h += 2) {
            float D[4] = {0.f, 0.f, 0.f, 0.f};
            mma8(D, n[h], n[h + 1], 0x3f803f80u);
            rs[h] = rcp_fast(D[0]); rs[h + 1] = rcp_fast(D[2]);
          }
#pragma unroll
          for (int i = 0; i < 9; i++) {
            const int h = i < 4 ? 0 : i == 4 ? 1 : 2;
            const bool nx = (i == 2 || i == 4 || i == 6) ? 2 * t >= i : i == 3 || i > 6;
            float O[4] = {0.f, 0.f, 0.f, 0.f};
            mma16(O, p[h] & ma, p[h + 1] & ma, p[h] & ~ma, p[h + 1] & ~ma, V1[i], Vb[i]);
            const float r = nx ? rs[h + 1] : rs[h];
            stg32(od + i * 1024 + hi * 256, pack2((nx ? O[2] : O[0]) * r, (nx ? O[3] : O[1]) * r));
          }
        };
        {
          float x0[4], x1[4];
#pragma unroll
          for (int h = 0; h < 4; h++) { x0[h] = (up0 ? S1[h][2] : S2[h][2]) * sc[1][0]; x1[h] = (up1 ? S1[h][3] : S2[h][3]) * sc[1][1]; }
          finish(x0, x1, V2, mup, 1);
        }
        ACLK(2);
        bar_sync(1 + w, 128);
#pragma unroll 1
        for (int it = 0; it < (1 << 20); it++) {
          if (remote) {
            bool ok = true;
#pragma unroll
            for (int i = 0; i < 6; i++) ok = ok && hv[i].z == tag;
            if (__all_sync(~0u, ok)) break;
          }
#pragma unroll
          for (int i = 0; i < 6; i++) hv[i] = ll_ld128g(hs + i * 512);
          if (!remote) break;
        }
        uint32_t H[18];
#pragma unroll
        for (int i = 0; i < 6; i++) { H[HA_[i]] = hv[i].x; H[HA_[i] + 1] = hv[i].y; H[HC_[i]] = hv[i].w; }
        float S0[4][4];
#pragma unroll
        for (int h = 0; h < 4; h++) {
#pragma unroll
          for (int i = 0; i < 4; i++) S0[h][i] = 0.f;
          mma16(S0[h], qa[h][0], qa[h][1], Pk[GB_[h]][0], Pk[GB_[h]][1], H[GA_[h]], H[GB_[h]]);
        }
#pragma unroll
        for (int h = 0; h < 4; h++) mma8(S0[h], qc[h][0], qc[h][1], H[GC_[h]]);
        uint32_t V0[9];
#pragma unroll
        for (int i = 0; i < 9; i++) V0[i] = movm(H[9 + i]);
        ACLK(3);
        {
          const bool nohalo = (rb | q) == 0;
          const float b0 = up0 && nohalo ? -INFINITY : 0.f, b1 = up1 && nohalo ? -INFINITY : 0.f;
          float x0[4], x1[4];
#pragma unroll
          for (int h = 0; h < 4; h++) { x0[h] = fmaf(up0 ? S0[h][0] : S1[h][0], sc[0][0], b0); x1[h] = fmaf(up1 ? S0[h][1] : S1[h][1], sc[0][1], b1); }
          finish(x0, x1, V0, ~mup, 0);
        }
        ACLK(4);
        __syncwarp();
        if (lane == 0) mbar_arrive(bars + B_EVT + (EV_N * (q < 2) + EV_O) * 8);
        ACLK_OUT;
        TRC(tr, w, tb + 2);
      }
      if (c.s) { c.s = 0; c.ph ^= 1; }
      if (PHM & 2) PHASE;
      {
        float acc[36];
        const int hw = rb * 2 + w;
        const uint32_t xt = stg + (8 * q + g) * 144 + t * 4;
        uint32_t xm = sb + SM_STG + 9216 + (8 * q + (lane & 7)) * 144 + (lane & 8) * 576 + (lane & 16);
        uint8_t* xn = xn_block(hw) + j * 9216 + q * 256 + lane * 4;
        uint32_t* sp = (uint32_t*)(Q.ST1 + (hw * 8 + j) * 32 + 8 * q) + lane;
        const uint4* sg = Q.ST1 + (hw * 8 + t) * 32 + 8 * q + g;
        asm volatile("" : "+r"(xm), "+l"(xn), "+l"(sp), "+l"(sg));
        mbar_wait_c(bars + B_RES + w * 8, L);
        TRC(tr, w, tb + 21);
#pragma unroll
        for (int i = 0; i < 18; i++) { const uint32_t x = lds32(xt + (i >> 1) * 16 + (i & 1) * 4608); acc[2 * i] = blo(x); acc[2 * i + 1] = bhi(x); asm volatile("" : "+f"(acc[2 * i]), "+f"(acc[2 * i + 1])); }
        mbar_wait_c(bars + B_WF, L);
        const uint32_t db = dlo(sb, 1152), of = bars + (w ? B_OF + 40 : B_AV + 96);
        uint32_t da[5];
#pragma unroll
        for (int e = 0; e < 5; e++) da[e] = __shfl_sync(~0u, dlo(sb + o_place(w, e), 1024), 0);
        if (w) {
#pragma unroll 1
          for (int kb = q ^ 2; kb < 9; kb += 4) {
            const uint32_t e = (kb + 1) >> 1;
            mbar_wait_c(bars + B_OF + e * 8, L);
            check(Int<8>{}, sb + o_place(0, e) + (kb && !(kb & 1)) * 8192, z1_block(rb, 0, 0) + kb * 8192);
            if (lane <= !kb) mbar_arrive(bars + B_AV + (12 + e) * 8);
          }
          bar_sync(7, 256);
        }
        mbar_wait_c(of, L & w);
        TRC(tr, w, tb + 3);
        wgmma_fence();
#pragma unroll
        for (int kk = 0; kk < 4; kk++) wgmma_ss_n72(acc, dsc<128, 0>(da[0], kk * 2048), dsc<128, 0>(db, kk * 2304), 1);
        wgmma_commit();
#pragma unroll 1
        for (int h = 0; h < 2; h++) {
#pragma unroll
          for (int u = 0; u < 4; u++) {
            if (!(u & 1)) { mbar_wait_c(of + 8 + h * 16 + u * 4, 1 + 2 * h + (u >> 1) < SPL ? L & w : L); wgmma_fence(); }
            if (u == 3 && h && !w) bar_arrive(7, 256);
#pragma unroll
            for (int kk = 0; kk < 4; kk++) wgmma_ss_n72(acc, dsc<128, 0>(da[1 + (u >> 1)], (u & 1) * 8192 + kk * 2048), dsc<128, 0>(db + h * 2304, (1 + u) * 9216 + kk * 2304), 1);
            if (u != 2) wgmma_commit();
            if (u == 0) { wgmma_wait<1>(); if (lane + w == 0 && h) mbar_arrive(bars + B_X3); }
          }
          da[1] = da[3]; da[2] = da[4];
        }
        RCLK_INIT;
        wgmma_wait<0>();
        RCLK(0);
        if (lane < 2) mbar_arrive_cluster(ebar + B_XD - B_EMPTY + w * 8);
        TRC(tr && P5TRACE != 5, w, tb + 4);
        {
          float s0 = 0.f, s1 = 0.f, q0 = 0.f, q1 = 0.f;
#pragma unroll
          for (int i = 0; i < 36; i++) {
            if (i & 2) { s1 += acc[i]; q1 = fmaf(acc[i], acc[i], q1); } else { s0 += acc[i]; q0 = fmaf(acc[i], acc[i], q0); }
          }
          const bool o1 = t & 1, o2 = t & 2;
          const float ss = (o1 ? s1 : s0) + __shfl_xor_sync(~0u, o1 ? s0 : s1, 1), sq = (o1 ? q1 : q0) + __shfl_xor_sync(~0u, o1 ? q0 : q1, 1);
          const float v = (o2 ? sq : ss) + __shfl_xor_sync(~0u, o2 ? ss : sq, 2);
          asm volatile("st.relaxed.gpu.global.u32 [%0], %1;" ::"l"(sp), "r"(__float_as_uint(v)) : "memory");
        }
        RCLK(1);
        RCLK(2);
        pause<PDEL>(Q.zero);
        uint4 pa, pb;
        auto there = [&](const uint4& a, const uint4& b) { return __all_sync(~0u, max(max(max(a.x, a.y), max(a.z, a.w)), max(max(b.x, b.y), max(b.z, b.w))) != ~0u); };
#pragma unroll 1
        for (int it = 0; it < (1 << 20); it++) {
          pa = ll_ld128(sg); pb = ll_ld128(sg + 128);
          if (there(pa, pb)) break;
        }
        RCLK(3);
        float mean0 = qsum(__uint_as_float(pa.x) + __uint_as_float(pb.x)) * (-1.f / DM), mean1 = qsum(__uint_as_float(pa.y) + __uint_as_float(pb.y)) * (-1.f / DM);
        const float rs0 = GA * rsq_fast(fmaxf(fmaf(qsum(__uint_as_float(pa.z) + __uint_as_float(pb.z)), 1.f / DM, -mean0 * mean0), 0.f) + LN_EPS);
        const float rs1 = GA * rsq_fast(fmaxf(fmaf(qsum(__uint_as_float(pa.w) + __uint_as_float(pb.w)), 1.f / DM, -mean1 * mean1), 0.f) + LN_EPS);
        mean0 *= rs0; mean1 *= rs1;
#pragma unroll
        for (int i = 0; i < 18; i++) {
          const float a = (i & 1) ? rs1 : rs0, b = (i & 1) ? mean1 : mean0;
          stg32(xn + (i >> 1) * 1024 + (i & 1) * 128, pack2(fmaf(acc[2 * i], a, b), fmaf(acc[2 * i + 1], a, b)));
        }
        signal(EV_X1);
        RCLK(4);
        if (w) {
#pragma unroll 1
          for (int u = q; u < 24; u += 4) {
            const uint32_t mb = u < 2 * SPL ? u >= SPL : u & 1, k = u < 2 * SPL ? u - mb * SPL : u >> 1;
            mbar_wait_c(bars + B_AF3 + mb * 96 + k * 8, L);
            SCLK3(u);
            check(Int<6>{}, sb + k * 12288 + mb * 6144, xn_block(rb * 2 + mb) + k * 6144);
            SCLK3(24 + u);
            if (lane <= (u < 2 * SPL)) mbar_arrive(bars + B_AV + (u < SPL ? 12 + k : k) * 8);
          }
          TRVI(lane == 0 && P5TRACE != 5, 5, 56 + L * 4 + q, rp);
          mbar_wait_c(bars + B_S5, L);
        }
#pragma unroll
        for (int u = 0; u < 4; u++)
          stsm4(xm + u * 32, pack2(acc[8 * u], acc[8 * u + 1]), pack2(acc[8 * u + 2], acc[8 * u + 3]), pack2(acc[8 * u + 4], acc[8 * u + 5]), pack2(acc[8 * u + 6], acc[8 * u + 7]));
        asm volatile("stmatrix.sync.aligned.m8n8.x2.shared.b16 [%0], {%1,%2};" ::"r"(xm + 128), "r"(pack2(acc[32], acc[33])), "r"(pack2(acc[34], acc[35])) : "memory");
        fence_async_s();
        signal(EV_XS);
        RCLK(5);
        TRC(tr, w, tb + 5);
        RCLK(6);
        RCLK_OUT;
      }
      if (PHM & 4) PHASE;
      {
      float acc[160];
#pragma unroll
      for (int i = 0; i < 160; i++) acc[i] = 0.f;
      float s[2] = {0.f, 0.f}, qq[2] = {0.f, 0.f}, zo = 0.f;
      const uint32_t zp = sb + SM_ZP3 + (tid & 127) * 4;
      auto zstat = [&](int mb, bool on) {
        const bool o1 = t & 1, o2 = t & 2;
        const float ss = ((o1 ? s[1] : s[0]) + __shfl_xor_sync(~0u, o1 ? s[0] : s[1], 1)) * 0x1p60f, sq = (o1 ? qq[1] : qq[0]) + __shfl_xor_sync(~0u, o1 ? qq[0] : qq[1], 1);
        const uint32_t v = __float_as_uint((o2 ? sq : ss) + zo + __shfl_xor_sync(~0u, o2 ? ss : sq, 2));
        asm volatile("{\n.reg .pred p, q, r;\nsetp.eq.u32 p, %4, 1;\nsetp.eq.u32 q, %4, 2;\nsetp.eq.and.u32 r, %5, 0, q;\n@p st.shared.u32 [%0], %2;\n@p bar.arrive 13, 256;\n"
                     "@q st.relaxed.gpu.global.u32 [%1], %2;\n@r mbarrier.arrive.shared::cta.b64 _, [%3];\n}" ::"r"(zp + mb * 512), "l"((uint32_t*)(Q.ZST + ((rb * 2 + mb) * 8 + j) * 32) + (tid & 127)),
                     "r"(v), "r"(bars + B_ZS + mb * 8), "r"(on ? 1 + w : 0), "r"(lane) : "memory");
        s[0] = s[1] = qq[0] = qq[1] = 0.f;
      };
      const uint32_t ebar3 = ebar + (B_E3 - B_EMPTY);
#pragma unroll 1
      for (int half = 0; half < 2; half++) {
        const bool big = half != w;
        auto rel3 = [&](int p) { if (lane < 2) mbar_arrive_cluster(ebar3 + p * 8); };
        auto pass = [&](auto nk) {
          constexpr int NK = nk.value;
          uint32_t d0 = dlo(sb, 1024), ph = half & ~w, af = bars + B_AV;
          const uint32_t db = dlo(sb + SM_B3, NK == 3 ? 6144 : 2048);
          const bool lead = NK == 3 && !half;
          if (lead) {
#pragma unroll
            for (int u = 0; u < 2 * SPL; u++) {
              const int mb = u / SPL, p = u % SPL;
              if (!mb) mbar_wait_c(bars + B_F3 + p * 8, 0);
              mbar_wait_c(af + (mb ? p : 12 + p) * 8, mb || p > 4 ? L : 1);
              TRC(tr && u == 0, w, tb + 6);
              SCLK2(u);
              if (p == 0) SCLK(mb * 4);
              wgmma_fence();
#pragma unroll
              for (int kk = 0; kk < 3; kk++) {
                wgmma_ss_n128(acc + mb * 80, dsc<128, 0>(d0, p * 12288 + kk * 2048 + mb * 6144), dsc<1024, 1>(db, p * 12288 + kk * 2048), p + kk > 0);
                if (kk == 0 && u > SPL) { wgmma_commit(); wgmma_wait<1>(); rel3(p - 1); }
              }
              wgmma_commit();
            }
          }
#pragma unroll 1
          for (int it = 0; it < 6 / NK; it++) {
#pragma unroll
            for (int p = 0; p < 6; p++) {
              if (p < SPL && lead && it == 0) continue;
              if (NK == 3) mbar_wait_c(af + p * 8, L);
              if (p == 0 && it == 0) bar_sync(6 + w, 256);
              mbar_wait_c(bars + B_F3 + p * 8, ph);
              TRC(tr && p == 0 && it == 0, w, tb + 6 + half * 4);
              if (lead) SCLK2(12 + it * 6 + p);
              if (NK == 2 ? !(p & 1) : p % 3 == 0) SCLK(half * 11 + (NK == 2 ? it * 3 + p / 2 : it * 2 + p / 3));
              wgmma_fence();
#pragma unroll
              for (int u = 0; u < 2 * NK; u++) {
                const int kk = u >> 1, mb = u & 1, e = p * NK + kk;
                const uint64_t da = dsc<128, 0>(d0, (e / 3) * 12288 + (e % 3) * 2048 + mb * 6144);
                if (NK == 3) wgmma_ss_n128(acc + mb * 80, da, dsc<1024, 1>(db, p * 12288 + kk * 2048), e > 0 || it > 0);
                else wgmma_ss_n160(acc + mb * 80, da, dsc<1024, 1>(db, p * 12288 + kk * 6144), e > 0 || it > 0);
                if (u == 0) { wgmma_commit(); wgmma_wait<1>(); if (p > 0 || it > 0) rel3((p + 5) % 6); }
                if (p * 8 + u == (NK == 2 ? HO3 : HO4) && it == 6 / NK - 1) bar_arrive(7 - w, 256);
              }
              wgmma_commit();
            }
            d0 += NK * 1536; af += 48;
            ph ^= 1;
          }
        };
        if (big) pass(Int<2>{}); else pass(Int<3>{});
        if (w) { bar_sync(13, 256); zo = __uint_as_float(lds32(zp + half * 512)); }
        if (half) zstat(1, true);
        const uint32_t off2 = lds32(sb + SM_OFF);
        const int go = (j & 1) ? (big ? 0 : 20) : (big ? 16 : 0);
        const float* gbp = (const float*)(smem_raw + SM_OFF + 8);
        asm volatile("" : "+l"(gbp));
        uint8_t* zd = half ? z1_block(rb, 0, j) + go * 1024 + (q & 1) * 2048 + 1024 + (q >> 1) * 512 + lane * 16 : z2_block(rb, j) + q * 9216 + go * 128 + ((g & 3) * 2 + (g >> 2)) * 16 + t * 4;
        wgmma_wait<0>();
        SCLK(half * 11 + 9);
        rel3(5);
        TRC(tr, w, tb + 7 + half * 4);
        auto gelu = [&](auto z2) {
          constexpr int NC = z2.value ? NC2 : NC1;
          float gate[NC], gb = GB, gn = GB;
          uint32_t qa[2][3] = {{0, 0, 0}, {0, 0, 0}};
#pragma unroll
          for (int e = 0; e < NC; e++) gate[e] = GB;
#pragma unroll
          for (int G = 0; G < 20; G++) {
            if (G == 16 && !big) break;
            if (G % (z2.value ? LD2 : LD1) == 0) { gb = gn; if (G < 20 - (z2.value ? LD2 : LD1)) asm volatile("ld.f32 %0, [%1];" : "=f"(gn) : "l"(gbp) : "memory"); }
#pragma unroll
            for (int r = 0; r < 2; r++) {
              float z[2];
              float& gt = gate[(G * 2 + r) % NC];
#pragma unroll
              for (int e = 0; e < 2; e++) {
                const float v = acc[4 * G + 2 * r + e];
                z[e] = fmaf(v, tanh_fast(v * fmaf(v, v, gt)), v);
                if (z2.value) { s[r] = fmaf(z[e], 0x1p-60f, s[r]); qq[r] = fmaf(z[e], z[e], qq[r]); }
              }
              const uint32_t pk = pack2(z[0], z[1]);
              if (z2.value) {
                stg32(zd + G * 128 + r * 4608, hsub2(pk, off2));
                gt = fmaf(qq[r], s[r], gb);
              } else {
                gt = fmaf(__uint_as_float(pk), 0x1p-60f, gb);
                if ((G & 3) == 3) stg128(zd + (G >> 2) * 4096 + r * (8 * ZB), qa[r][0], qa[r][1], qa[r][2], pk);
                else qa[r][G & 3] = pk;
              }
            }
          }
        };
#pragma unroll 1
        for (int mb = 0;; mb++) {
          if (half) gelu(Int<0>{}); else gelu(Int<1>{});
          if (mb) break;
          zstat(0, !half);
#pragma unroll
          for (int i = 0; i < 80; i++) acc[i] = acc[80 + i];
          zd += half ? -1024 : (int)(128 * ZB);
        }
        mbar_wait_c(bars + B_GATE3, L);
        signal(half ? EV_Z1 : EV_ZN);
        SCLK(half * 11 + 10);
        TRC(tr, w, tb + 8 + half * 4);
      }
      }
      if (PHM & 8) PHASE;
      const uint32_t aoff = (w * 64 + q * 16 + (lane & 15)) * 128 + (((lane >> 4) ^ (lane & 7)) << 4);
      uint32_t hA[18][4];
      {
        float acc[144];
        {
          const uint32_t c16 = lds32(sb + SM_OFF + 12), a[4] = {c16, c16, c16, c16};
          wgmma_fence();
          wgmma_rs_n144(acc, a, dsc<0, 0>(dlo(sb + SM_CV + 512, 0), 0), 0);
          wgmma_rs_n144(acc + 72, a, dsc<0, 0>(dlo(sb + SM_CV + 512, 0), 128), 0);
          wgmma_commit();
        }
        uint32_t prev = 0;
        auto stage = [&](int kb, bool odd) {
          mbar_wait_c(bars + B_FULL + c.s * 8, c.ph);
          TRC(tr && kb == 0, w, tb + 13);
          SCLK(22 + kb);
          const uint32_t st = sb + c.s * ST_BYTES, db = dlo(st + ST_B, 4608), rt = sb + SM_RT + kb * 128 + t * 8;
          uint32_t a[4][4];
#pragma unroll
          for (int kk = 0; kk < 4; kk++) {
            uint32_t r[4];
            ldsm4(r, st + (aoff ^ (kk << 5)));
            const uint2 sc = lds64(rt + kk * 32);
            a[kk][0] = hmul2(__byte_perm(r[0], r[2], 0x5410), sc.x); a[kk][2] = hmul2(__byte_perm(r[0], r[2], 0x7632), sc.y);
            a[kk][1] = hmul2(__byte_perm(r[1], r[3], 0x5410), sc.x); a[kk][3] = hmul2(__byte_perm(r[1], r[3], 0x7632), sc.y);
          }
          if (!odd && kb + w == 0) bar_sync(6, 256);
          wgmma_fence();
#pragma unroll
          for (int i = 0; i < 8; i++) {
            const int kk = i & 3, hf = i >> 2;
            wgmma_rs_n144(acc + hf * 72, a[kk], dsc<128, 0>(db, kk * 9216 + hf * 2304), 1);
            if (i == 0) { wgmma_commit(); wgmma_wait<1>(); if (kb) release(prev); }
            if (i == 3) wgmma_commit();
          }
          wgmma_commit();
          prev = c.s; c.next();
        };
#pragma unroll 1
        for (int kb = 0; kb < 32; kb += 2) {
          if (!(kb & 7)) mbar_wait_c(bars + B_RT + kb, L);
          stage(kb, false);
          stage(kb + 1, true);
        }
        mbar_wait_c(bars + B_CV + w * 8, L);
        const float gk = 0.5f / GA;
        const float c1 = __uint_as_float(lds32(sb + SM_OFF + 4));
        const float gb0 = -gk * (c1 + __uint_as_float(lds32(sb + SM_CV + w * 256 + (16 * q + g) * 4))), gb1 = -gk * (c1 + __uint_as_float(lds32(sb + SM_CV + w * 256 + (16 * q + g + 8) * 4)));
        if (w == 1) { mbar_wait_c(bars + B_FULL + c.s * 8, c.ph); release(c.s); c.next(); }
        mbar_wait_c(bars + B_FULL + c.s * 8, c.ph);
        const uint32_t zs = sb + c.s * ST_BYTES + ST_B + (tid & 127) * 16;
        uint4 zl, zh;
#pragma unroll
        for (int u = 0; u < 18; u++) {
          if (u == 0) wgmma_wait<1>();
          if (u == 9) {
            wgmma_wait<0>();
            release(prev);
            if (L == 0) signal(EV_PT);
            if (EARR && w == 1) bar_arrive(6, 256);
            TRC(tr, w, tb + 14);
            SCLK(54);
          }
          if (!(u & 1)) { zl = lds128(zs + u * 2048); zh = lds128(zs + u * 2048 + 2048); }
          const uint4 z = (u & 1) ? make_uint4(zl.z, zh.z, zl.w, zh.w) : make_uint4(zl.x, zh.x, zl.y, zh.y);
          hA[u][0] = hmul2(z.x, pack2(fmaf(acc[8 * u], gk, gb0), fmaf(acc[8 * u + 1], gk, gb0)));
          hA[u][1] = hmul2(z.y, pack2(fmaf(acc[8 * u + 2], gk, gb1), fmaf(acc[8 * u + 3], gk, gb1)));
          hA[u][2] = hmul2(z.z, pack2(fmaf(acc[8 * u + 4], gk, gb0), fmaf(acc[8 * u + 5], gk, gb0)));
          hA[u][3] = hmul2(z.w, pack2(fmaf(acc[8 * u + 6], gk, gb1), fmaf(acc[8 * u + 7], gk, gb1)));
        }
        __syncwarp();
        release(c.s);
        c.next();
        if (w == 0) { mbar_wait_c(bars + B_FULL + c.s * 8, c.ph); release(c.s); c.next(); }
        TRC(tr, w, tb + 15);
      }
      {
        CLK_INIT;
        if (!EARR && w == 1) bar_arrive(6, 256);
        uint4 v[4];
#pragma unroll
        for (int u = 0; u < 4; u++) v[u] = make_uint4(0u, 0u, 0u, 0u);
        uint32_t rl = sb + SM_STG + w * 8192 + q * 2048 + (lane >> 3) * 128 + (((lane & 7) ^ (lane >> 3)) << 4);
        uint8_t* rd = Q.out + (128 * rb + 32 * q + 2 * (lane >> 3) + w) * (DM * 2) + j * 128 + (lane & 7) * 16;
        asm volatile("" : "+r"(rl), "+l"(rd));
        auto send = [&](int u0, int u1) {
#pragma unroll
          for (int u = u0; u < u1; u++)
            asm volatile("red.relaxed.gpu.global.add.noftz.v4.bf16x2 [%0], {%1,%2,%3,%4};" ::"l"(rd + u * (8 * DM * 2)), "r"(v[u].x), "r"(v[u].y), "r"(v[u].z), "r"(v[u].w) : "memory");
        };
#pragma unroll 1
        for (int p = 0; p < 9; p++) {
          float acc[32];
          CLK(0);
          mbar_wait_c(bars + B_FULL + c.s * 8, c.ph);
          const uint32_t db = dlo(sb + c.s * ST_BYTES + ST_B, 0);
          CLK(1);
          bar_sync(6 + w, 256);
          CLK(2);
          wgmma_fence();
#pragma unroll
          for (int kk = 0; kk < 18; kk++) {
            wgmma_rs_n64(acc, hA[kk], dsc<1024, 1>(db, kk * 2048), kk != 0);
            if (kk == PPK && (w == 0 || p < 8)) bar_arrive(7 - w, 256);
          }
          wgmma_commit();
          CLK(3);
          if (p > 0) { send(NOW, 4); rd += p + j == 9 ? -1024 : 128; }
          CLK(5);
          wgmma_wait<0>();
          CLK(4);
          if (L == 0 || p < 5) release(c.s);
          c.next();
          TRC(tr && p == 8, w, tb + 16);
#pragma unroll
          for (int u = 0; u < 4; u++)
            stsm4(sb + SM_STG + (aoff ^ (u << 5)), pack2(acc[8 * u], acc[8 * u + 1]), pack2(acc[8 * u + 2], acc[8 * u + 3]), pack2(acc[8 * u + 4], acc[8 * u + 5]), pack2(acc[8 * u + 6], acc[8 * u + 7]));
          __syncwarp();
#pragma unroll
          for (int u = 0; u < 4; u++) v[u] = lds128(rl + u * 512 ^ (u & 1) << 6);
          send(0, NOW);
        }
        send(NOW, 4);
        TRC(tr, w, tb + 17);
        if (L == 0) signal(EV_PT);
        CLK_OUT;
        TRC(tr, w, tb + 18);
      }
    }
    if ((tid & 127) == 0) Q.flags[(rb * 2 + w) * 32 + FR_EP + j] = epoch + 1;
    if (tid == 0) Q.flags[FJ + j * 32 + FJ_EP + rb] = epoch + 1;
  }
}

typedef CUresult (*EncodeFn)(CUtensorMap*, CUtensorMapDataType, cuuint32_t, void*, const cuuint64_t*, const cuuint64_t*, const cuuint32_t*,
                             const cuuint32_t*, CUtensorMapInterleave, CUtensorMapSwizzle, CUtensorMapL2promotion, CUtensorMapFloatOOBfill);

static void make_map(EncodeFn fn, CUtensorMap* m, const void* ptr, int rank, uint64_t d0, uint64_t d1, uint64_t d2, uint64_t s1, uint64_t s2,
                     uint32_t b0, uint32_t b1, uint32_t b2, CUtensorMapSwizzle swz) {
  cuuint64_t dims[3] = {d0, d1, d2}, strides[2] = {s1, s2};
  cuuint32_t box[3] = {b0, b1, b2}, es[3] = {1, 1, 1};
  fn(m, CU_TENSOR_MAP_DATA_TYPE_BFLOAT16, rank, const_cast<void*>(ptr), dims, strides, box, es, CU_TENSOR_MAP_INTERLEAVE_NONE, swz,
     CU_TENSOR_MAP_L2_PROMOTION_L2_128B, CU_TENSOR_MAP_FLOAT_OOB_FILL_NONE);
}

}

extern "C" void kernel_launch(void* const* d_in, const int* in_sizes, int n_in, void* d_out, int out_size) {
  using namespace mk;
  (void)in_sizes; (void)n_in; (void)out_size;
  static EncodeFn fn = nullptr;
  static Scratch* sc = nullptr;
  if (!fn) {
    cudaDriverEntryPointQueryResult qr;
    cudaGetDriverEntryPoint("cuTensorMapEncodeTiled", (void**)&fn, cudaEnableDefault, &qr);
    cudaGetSymbolAddress((void**)&sc, g_scratch);
    cudaFuncSetAttribute(mega_kernel, cudaFuncAttributeMaxDynamicSharedMemorySize, SM_TOTAL);
  }
  Params p;
  Ptrs a;
  a.x = (const uint8_t*)d_in[0];
  a.wqkv = (const __nv_bfloat16*)d_in[1];
  a.wo = (const __nv_bfloat16*)d_in[2];
  a.w_in = (const __nv_bfloat16*)d_in[4];
  a.w_sp = (const __nv_bfloat16*)d_in[5];
  a.b_sp = (const __nv_bfloat16*)d_in[6];
  a.out = (uint8_t*)d_out;
  a.zero = 0;
  a.WQ = sc->WQ; a.flags = sc->flags; a.CSP = sc->CSP; a.XST = sc->XST; a.HALO = sc->HALO; a.ST1 = sc->ST1; a.ZST = sc->ZST; a.RT = sc->RT; a.Z = sc->Z; a.WO = sc->WO;
  make_map(fn, &p.wsp, a.w_sp, 3, 2048, 1024, 2, 8192, 4096, 64, 64, 2, CU_TENSOR_MAP_SWIZZLE_128B);
  for (int i = 0; i < 2; i++) {
    make_map(fn, &p.act[i], i ? a.out : a.x, 3, DM, 1024, 2, 2304, 1152, 64, 64, 1, CU_TENSOR_MAP_SWIZZLE_128B);
    make_map(fn, &p.row[i], i ? a.out : a.x, 3, 192, 6, 1024, 384, 2304, 192, 3, 8, CU_TENSOR_MAP_SWIZZLE_NONE);
    make_map(fn, &p.res[i], i ? a.out : a.x, 3, DM, 1024, 2, 2304, 1152, 72, 32, 2, CU_TENSOR_MAP_SWIZZLE_NONE);
  }
  for (int i = 0; i < 2; i++) make_map(fn, &p.winb[i], a.w_in + 32 * i, 3, 64, 576, 72 - i, 9216, 128, 64, 16, 3, CU_TENSOR_MAP_SWIZZLE_128B);
  make_map(fn, &p.wins, a.w_in, 3, 64, 576, 72, 9216, 128, 64, 48, 1, CU_TENSOR_MAP_SWIZZLE_128B);
  make_map(fn, &p.wout, d_in[7], 2, 576, 2304, 1, 1152, 0, 64, 144, 1, CU_TENSOR_MAP_SWIZZLE_128B);
  mega_kernel<<<NGRID, 384, SM_TOTAL, cudaStreamPerThread>>>(a, p);
}
```

```cpp
#include <cuda_runtime.h>
#include <cuda.h>
#include <cuda_bf16.h>
#include <stdint.h>

#define MK_TRACE 0
#define MK_DBG 0
#define P5TRACE 0
#define LAG1 1
#define C0S 32.f
#define OFM 0x10u
#define NC2 2
#define NC1 8
#define PDEL 8
#define LD1 4
#define LD2 2
#define ZD1 8
#define ZD2 20
#define WPF 1
#define YPACE 2
#define SPL 3
#define XP0 10
#define EFM 0x23333022
#define EF(i) ((((EFM >> (4 * (i))) & 3) == 3) || (((EFM >> (4 * (i))) >> L) & 1))
#define AEP 2
#define PZI 4
#define KS 1
#define RFI 3
#define XK1 1
#define XK2 2
#define SDEL 10
#define FD3 14
#define FD4 0
#define FD5 0
#define PHM 15
#define NOW 2
#define WTI 12
#define APACE 7
#define HO3 41
#define HO4 41
#define PPK 17

namespace mk {

constexpr int SEQ = 2048, DM = 576, FH = 2304;
constexpr int NCTA = 128;
constexpr int NGRID = 132;
constexpr uint32_t ZB = 36864;
constexpr uint32_t WQ_SL = 72 * 3456;
constexpr uint32_t WO_SL = 72 * 1152;
constexpr float LN_EPS = 1e-5f;
constexpr float GA = 0.3292034911525734f, GB = 2.423681954311584f;

constexpr uint32_t ST_BYTES = 53248, ST_B = 16384, NST = 4;
constexpr uint32_t SM_STG = NST * ST_BYTES;
constexpr uint32_t SM_BAR = SM_STG + 2 * 9216, B_OFF = 896;
constexpr uint32_t SM_OFF = SM_BAR + B_OFF;
constexpr uint32_t SM_TOTAL = SM_BAR + 1024;
constexpr uint32_t SM_RT = SM_STG + 9216, SM_CV = SM_STG + 17408, SM_WT = SM_STG;
constexpr uint32_t SM_WOI = 44032, SM_CSQ = 49280, SM_XST = 50176;
enum { EV_PT = 0, EV_O = 1, EV_X1 = 2, EV_ZN = 3, EV_Z1 = 4, EV_XS = 5, EV_N = 6 };
constexpr uint32_t B_FULL = 0, B_FULLA = 32, B_RES = 96, B_WT = 112, B_GATE3 = 128, B_Z1 = 136, B_ZOK = 144, B_CV = 152, B_XRW = 168, B_F3 = 184, B_WF = 232, B_OF = 240,
                   B_RT = 320, B_AF3 = 352, B_RB = 544,
                   B_AD = 576, B_S5 = 608, B_AV = 616, B_CSQ = 760,
                   B_LAG = 768, B_X3 = 776, B_ZS = 784, B_EVT = 800,
                   B_IMG = 912, B_WOI = 920, B_E3 = 928, B_XD = 976,
                   B_EMPTY = 992;
constexpr uint32_t SM_B3 = 9 * 16384, SM_ZP3 = SM_STG + 8192;

enum { FR_X2 = 0, FR_O = 1, FR_XR = 5, FR_OL = 7, FR_PZ = 9, FR_EP = 16, FJ = 32 * 32, FJ_WQ = 0, FJ_WO = 1, FJ_ZN = 3, FJ_P4 = 5, FJ_EP = 16, F_N = FJ + 8 * 32 };

struct Scratch {
  alignas(1024) uint32_t flags[F_N];
  alignas(1024) float CSP[2 * NCTA * 216];
  alignas(1024) uint2 RT[SEQ];
  alignas(1024) uint4 XST[2 * SEQ];
  alignas(1024) uint4 ST1[SEQ * 4];
  alignas(1024) uint4 ZST[SEQ * 4];
  alignas(1024) uint4 HALO[32 * 8 * 6 * 32];
  alignas(1024) uint8_t WO[8 * WO_SL];
  alignas(1024) uint8_t WQ[8 * WQ_SL];
  alignas(1024) uint8_t Z[576 * ZB];
};
__device__ Scratch g_scratch;

struct Ptrs {
  const __nv_bfloat16* wqkv;
  uint8_t* WQ;
  uint32_t* flags;
  float* CSP;
  const uint8_t* x;
  uint32_t zero;
  uint4 *XST, *HALO, *ST1, *ZST;
  uint2* RT;
  uint8_t *Z, *WO, *out;
  const __nv_bfloat16 *wo, *w_in, *w_sp, *b_sp;
};
struct Params {
  CUtensorMap wsp, winb[2], wins, wout;
  CUtensorMap act[2];
  CUtensorMap res[2];
  CUtensorMap row[2];
};

__device__ __forceinline__ uint32_t smem_u32(const void* p) { return (uint32_t)__cvta_generic_to_shared(p); }
__device__ __forceinline__ void mbar_init(uint32_t bar, uint32_t cnt) { asm volatile("mbarrier.init.shared::cta.b64 [%0], %1;" ::"r"(bar), "r"(cnt)); }
__device__ __forceinline__ void mbar_arrive(uint32_t bar) { asm volatile("mbarrier.arrive.shared::cta.b64 _, [%0];" ::"r"(bar) : "memory"); }
__device__ __forceinline__ void mbar_wait(uint32_t bar, uint32_t parity) {
  asm volatile(
      "{\n.reg .pred p;\n.reg .u32 c;\nmov.u32 c, 0;\nLAB_WAIT:\n"
      "mbarrier.try_wait.parity.shared::cta.b64 p, [%0], %1;\n@p bra LAB_DONE;\n"
      "add.u32 c, c, 1;\nsetp.lt.u32 p, c, 0x100000;\n@p bra LAB_WAIT;\ntrap;\nLAB_DONE:\n}" ::"r"(bar), "r"(parity)
      : "memory");
}
__device__ __forceinline__ void mbar_wait_c(uint32_t bar, uint32_t parity) {
  asm volatile("{\n.reg .pred p;\nLAB_WAIT:\nmbarrier.try_wait.parity.shared::cta.b64 p, [%0], %1;\n@!p bra LAB_WAIT;\n}" ::"r"(bar), "r"(parity) : "memory");
}
__device__ __forceinline__ void flag_wait(const uint32_t* f, uint32_t target) {
  asm volatile(
      "{\n.reg .pred p;\n.reg .u32 c, v;\nmov.u32 c, 0;\nLAB_WAIT:\n"
      "ld.relaxed.gpu.global.u32 v, [%0];\nsub.u32 v, v, %1;\nsetp.ge.s32 p, v, 0;\n@p bra LAB_DONE;\n"
      "add.u32 c, c, 1;\nsetp.lt.u32 p, c, 0x400000;\n@p bra LAB_WAIT;\ntrap;\nLAB_DONE:\nfence.acquire.gpu;\n}" ::"l"(f), "r"(target)
      : "memory");
}
__device__ __forceinline__ void fence_gpu() { asm volatile("fence.acq_rel.gpu;" ::: "memory"); }
__device__ __forceinline__ void fence_async_g() { asm volatile("fence.proxy.async.global;" ::: "memory"); }
__device__ __forceinline__ void fence_async_s() { asm volatile("fence.proxy.async.shared::cta;" ::: "memory"); }
__device__ __forceinline__ uint32_t elect_one() {
  uint32_t p; asm volatile("{\n.reg .pred P;\nelect.sync _|P, 0xffffffff;\nselp.u32 %0, 1, 0, P;\n}" : "=r"(p)); return p;
}
__device__ __forceinline__ void expect_tx_p(uint32_t el, uint32_t bar, uint32_t bytes) {
  asm volatile("{\n.reg .pred P;\nsetp.ne.u32 P, %2, 0;\n@P mbarrier.arrive.expect_tx.shared::cta.b64 _, [%0], %1;\n}" ::"r"(bar), "r"(bytes), "r"(el) : "memory");
}
__device__ __forceinline__ void bulk_load_p(uint32_t el, uint32_t dst, const void* src, uint32_t bytes, uint32_t bar) {
  asm volatile("{\n.reg .pred P;\nsetp.ne.u32 P, %4, 0;\n@P cp.async.bulk.shared::cluster.global.mbarrier::complete_tx::bytes [%0], [%1], %2, [%3];\n}" ::"r"(dst), "l"(src), "r"(bytes), "r"(bar), "r"(el) : "memory");
}
__device__ __forceinline__ uint64_t policy_evict_first() { uint64_t p; asm("createpolicy.fractional.L2::evict_first.b64 %0, 1.0;" : "=l"(p)); return p; }
__device__ __forceinline__ void bulk_load_h(uint32_t el, uint32_t dst, const void* src, uint32_t bytes, uint32_t bar, bool ef, uint64_t pol) {
  if (ef) {
    asm volatile("{\n.reg .pred P;\nsetp.ne.u32 P, %4, 0;\n@P cp.async.bulk.shared::cluster.global.mbarrier::complete_tx::bytes.L2::cache_hint [%0], [%1], %2, [%3], %5;\n}" ::"r"(dst), "l"(src), "r"(bytes), "r"(bar), "r"(el), "l"(pol) : "memory");
  } else {
    asm volatile("{\n.reg .pred P;\nsetp.ne.u32 P, %4, 0;\n@P cp.async.bulk.shared::cluster.global.mbarrier::complete_tx::bytes [%0], [%1], %2, [%3];\n}" ::"r"(dst), "l"(src), "r"(bytes), "r"(bar), "r"(el) : "memory");
  }
}
__device__ __forceinline__ void bulk_mc_h(uint32_t el, uint32_t dst, const void* src, uint32_t bytes, uint32_t bar, bool ef, uint64_t pol) {
  if (ef) {
    asm volatile("{\n.reg .pred P;\nsetp.ne.u32 P, %4, 0;\n@P cp.async.bulk.shared::cluster.global.mbarrier::complete_tx::bytes.multicast::cluster.L2::cache_hint [%0], [%1], %2, [%3], %5, %6;\n}" ::"r"(dst), "l"(src), "r"(bytes), "r"(bar), "r"(el), "h"((uint16_t)3), "l"(pol) : "memory");
  } else {
    asm volatile("{\n.reg .pred P;\nsetp.ne.u32 P, %4, 0;\n@P cp.async.bulk.shared::cluster.global.mbarrier::complete_tx::bytes.multicast::cluster [%0], [%1], %2, [%3], %5;\n}" ::"r"(dst), "l"(src), "r"(bytes), "r"(bar), "r"(el), "h"((uint16_t)3) : "memory");
  }
}
__device__ __forceinline__ void tma3d_h(uint32_t el, uint32_t dst, const CUtensorMap* m, int c0, int c1, int c2, uint32_t bar, bool ef, uint64_t pol) {
  if (ef) {
    asm volatile("{\n.reg .pred P;\nsetp.ne.u32 P, %6, 0;\n@P cp.async.bulk.tensor.3d.shared::cluster.global.mbarrier::complete_tx::bytes.L2::cache_hint [%0], [%1, {%3, %4, %5}], [%2], %7;\n}" ::"r"(dst), "l"(m), "r"(bar), "r"(c0), "r"(c1), "r"(c2), "r"(el), "l"(pol) : "memory");
  } else {
    asm volatile("{\n.reg .pred P;\nsetp.ne.u32 P, %6, 0;\n@P cp.async.bulk.tensor.3d.shared::cluster.global.mbarrier::complete_tx::bytes [%0], [%1, {%3, %4, %5}], [%2];\n}" ::"r"(dst), "l"(m), "r"(bar), "r"(c0), "r"(c1), "r"(c2), "r"(el) : "memory");
  }
}
__device__ __forceinline__ void tma2d_mc_h(uint32_t el, uint32_t dst, const CUtensorMap* m, int c0, int c1, uint32_t bar, bool ef, uint64_t pol) {
  if (ef) {
    asm volatile("{\n.reg .pred P;\nsetp.ne.u32 P, %5, 0;\n@P cp.async.bulk.tensor.2d.shared::cluster.global.mbarrier::complete_tx::bytes.multicast::cluster.L2::cache_hint [%0], [%1, {%3, %4}], [%2], %6, %7;\n}" ::"r"(dst), "l"(m), "r"(bar), "r"(c0), "r"(c1), "r"(el), "h"((uint16_t)3), "l"(pol) : "memory");
  } else {
    asm volatile("{\n.reg .pred P;\nsetp.ne.u32 P, %5, 0;\n@P cp.async.bulk.tensor.2d.shared::cluster.global.mbarrier::complete_tx::bytes.multicast::cluster [%0], [%1, {%3, %4}], [%2], %6;\n}" ::"r"(dst), "l"(m), "r"(bar), "r"(c0), "r"(c1), "r"(el), "h"((uint16_t)3) : "memory");
  }
}
__device__ __forceinline__ void tma3d_mc_h(uint32_t el, uint32_t dst, const CUtensorMap* m, int c0, int c1, int c2, uint32_t bar, bool ef, uint64_t pol) {
  if (ef) {
    asm volatile("{\n.reg .pred P;\nsetp.ne.u32 P, %6, 0;\n@P cp.async.bulk.tensor.3d.shared::cluster.global.mbarrier::complete_tx::bytes.multicast::cluster.L2::cache_hint [%0], [%1, {%3, %4, %5}], [%2], %7, %8;\n}" ::"r"(dst), "l"(m), "r"(bar), "r"(c0), "r"(c1), "r"(c2), "r"(el), "h"((uint16_t)3), "l"(pol) : "memory");
  } else {
    asm volatile("{\n.reg .pred P;\nsetp.ne.u32 P, %6, 0;\n@P cp.async.bulk.tensor.3d.shared::cluster.global.mbarrier::complete_tx::bytes.multicast::cluster [%0], [%1, {%3, %4, %5}], [%2], %7;\n}" ::"r"(dst), "l"(m), "r"(bar), "r"(c0), "r"(c1), "r"(c2), "r"(el), "h"((uint16_t)3) : "memory");
  }
}
__device__ __forceinline__ void mbar_arrive_cluster(uint32_t addr) { asm volatile("mbarrier.arrive.shared::cluster.b64 _, [%0];" ::"r"(addr) : "memory"); }
__device__ __forceinline__ uint32_t mapa(uint32_t addr, uint32_t rank) { uint32_t r; asm("mapa.shared::cluster.u32 %0, %1, %2;" : "=r"(r) : "r"(addr), "r"(rank)); return r; }
__device__ __forceinline__ void bulk_store_p(uint32_t el, void* dst, uint32_t src, uint32_t bytes) {
  asm volatile("{\n.reg .pred P;\nsetp.ne.u32 P, %3, 0;\n@P cp.async.bulk.global.shared::cta.bulk_group [%0], [%1], %2;\n}" ::"l"(dst), "r"(src), "r"(bytes), "r"(el) : "memory");
}
__device__ __forceinline__ void flag_release_p(uint32_t el, uint32_t* f) {
  asm volatile("{\n.reg .pred P;\nsetp.ne.u32 P, %1, 0;\nfence.proxy.async;\n@P red.relaxed.gpu.global.add.u32 [%0], 1;\n}" ::"l"(f), "r"(el) : "memory");
}
__device__ __forceinline__ void flag_add_p(uint32_t el, uint32_t* f) {
  asm volatile("{\n.reg .pred P;\nsetp.ne.u32 P, %1, 0;\n@P red.relaxed.gpu.global.add.u32 [%0], 1;\n}" ::"l"(f), "r"(el) : "memory");
}
__device__ __forceinline__ void prefetch_l2(const void* src, uint32_t bytes) { asm volatile("cp.async.bulk.prefetch.L2.global [%0], %1;" ::"l"(src), "r"(bytes) : "memory"); }
__device__ __forceinline__ void prefetch_map(const CUtensorMap* m) { asm volatile("prefetch.tensormap [%0];" ::"l"(m) : "memory"); }
__device__ __forceinline__ void wgmma_fence() { asm volatile("wgmma.fence.sync.aligned;" ::: "memory"); }
__device__ __forceinline__ void wgmma_commit() { asm volatile("wgmma.commit_group.sync.aligned;" ::: "memory"); }
template <int N> __device__ __forceinline__ void wgmma_wait() { asm volatile("wgmma.wait_group.sync.aligned %0;" ::"n"(N) : "memory"); }
__device__ __forceinline__ uint32_t dlo(uint32_t addr, uint32_t lbo) { return ((addr & 0x3FFFF) >> 4) + ((lbo >> 4) << 16); }
template <uint32_t SBO, uint32_t SWZ> __device__ __forceinline__ uint64_t dsc(uint32_t lo, uint32_t off) {
  uint64_t d; asm("mov.b64 %0, {%1, %2};" : "=l"(d) : "r"(lo + (off >> 4)), "n"((SBO >> 4) | (SWZ << 30))); return d;
}
template <int R> __device__ __forceinline__ void reg_alloc() { asm volatile("setmaxnreg.inc.sync.aligned.u32 %0;" ::"n"(R)); }
template <int R> __device__ __forceinline__ void reg_dealloc() { asm volatile("setmaxnreg.dec.sync.aligned.u32 %0;" ::"n"(R)); }
__device__ __forceinline__ void bar_sync(int id, int n) { asm volatile("bar.sync %0, %1;" ::"r"(id), "r"(n) : "memory"); }
__device__ __forceinline__ void bar_arrive(int id, int n) { asm volatile("bar.arrive %0, %1;" ::"r"(id), "r"(n) : "memory"); }
__device__ __forceinline__ void ldsm4(uint32_t* r, uint32_t addr) {
  asm volatile("ldmatrix.sync.aligned.m8n8.x4.shared.b16 {%0,%1,%2,%3}, [%4];" : "=r"(r[0]), "=r"(r[1]), "=r"(r[2]), "=r"(r[3]) : "r"(addr) : "memory");
}
__device__ __forceinline__ uint32_t movm(uint32_t a) { uint32_t d; asm volatile("movmatrix.sync.aligned.m8n8.trans.b16 %0, %1;" : "=r"(d) : "r"(a)); return d; }
__device__ __forceinline__ void mma16(float* c, uint32_t a0, uint32_t a1, uint32_t a2, uint32_t a3, uint32_t b0, uint32_t b1) {
  asm volatile("mma.sync.aligned.m16n8k16.row.col.f32.bf16.bf16.f32 {%0,%1,%2,%3}, {%4,%5,%6,%7}, {%8,%9}, {%0,%1,%2,%3};"
               : "+f"(c[0]), "+f"(c[1]), "+f"(c[2]), "+f"(c[3]) : "r"(a0), "r"(a1), "r"(a2), "r"(a3), "r"(b0), "r"(b1));
}
__device__ __forceinline__ void mma8(float* c, uint32_t a0, uint32_t a1, uint32_t b0) {
  asm volatile("mma.sync.aligned.m16n8k8.row.col.f32.bf16.bf16.f32 {%0,%1,%2,%3}, {%4,%5}, {%6}, {%0,%1,%2,%3};"
               : "+f"(c[0]), "+f"(c[1]), "+f"(c[2]), "+f"(c[3]) : "r"(a0), "r"(a1), "r"(b0));
}
__device__ __forceinline__ uint32_t pack2(float lo, float hi) { uint32_t r; asm("cvt.rn.bf16x2.f32 %0, %1, %2;" : "=r"(r) : "f"(hi), "f"(lo)); return r; }
__device__ __forceinline__ float blo(uint32_t v) { return __uint_as_float(v << 16); }
__device__ __forceinline__ float bhi(uint32_t v) { return __uint_as_float(v & 0xffff0000u); }
__device__ __forceinline__ float tanh_fast(float x) { float y; asm("tanh.approx.f32 %0, %1;" : "=f"(y) : "f"(x)); return y; }
__device__ __forceinline__ float rcp_fast(float x) { float y; asm("rcp.approx.ftz.f32 %0, %1;" : "=f"(y) : "f"(x)); return y; }
__device__ __forceinline__ float rsq_fast(float x) { float y; asm("rsqrt.approx.ftz.f32 %0, %1;" : "=f"(y) : "f"(x)); return y; }
__device__ __forceinline__ float ex2(float x) { float y; asm("ex2.approx.ftz.f32 %0, %1;" : "=f"(y) : "f"(x)); return y; }
__device__ __forceinline__ float qsum(float v) { v += __shfl_xor_sync(~0u, v, 1); v += __shfl_xor_sync(~0u, v, 2); return v; }
__device__ __forceinline__ float qmax(float v) { v = fmaxf(v, __shfl_xor_sync(~0u, v, 1)); v = fmaxf(v, __shfl_xor_sync(~0u, v, 2)); return v; }
__device__ __forceinline__ void stg32(void* p, uint32_t v) { asm volatile("st.global.u32 [%0], %1;" ::"l"(p), "r"(v) : "memory"); }
__device__ __forceinline__ void stg128(void* p, uint32_t a, uint32_t b, uint32_t c, uint32_t d) { asm volatile("st.global.v4.u32 [%0], {%1,%2,%3,%4};" ::"l"(p), "r"(a), "r"(b), "r"(c), "r"(d) : "memory"); }
__device__ __forceinline__ uint32_t ldcg32(const void* p) { uint32_t v; asm volatile("ld.global.L1::no_allocate.u32 %0, [%1];" : "=r"(v) : "l"(p) : "memory"); return v; }
__device__ __forceinline__ void stg128_if(bool c, void* p, uint32_t a, uint32_t b, uint32_t cc, uint32_t d) {
  asm volatile("{\n.reg .pred P;\nsetp.ne.u32 P, %5, 0;\n@P st.global.v4.u32 [%0], {%1,%2,%3,%4};\n}" ::"l"(p), "r"(a), "r"(b), "r"(cc), "r"(d), "r"((uint32_t)c) : "memory");
}
__device__ __forceinline__ uint2 lds64(uint32_t a) { uint2 v; asm volatile("ld.shared.v2.u32 {%0,%1}, [%2];" : "=r"(v.x), "=r"(v.y) : "r"(a) : "memory"); return v; }
__device__ __forceinline__ uint4 ldcg128(const void* p) { uint4 v; asm volatile("ld.global.cg.v4.u32 {%0,%1,%2,%3}, [%4];" : "=r"(v.x), "=r"(v.y), "=r"(v.z), "=r"(v.w) : "l"(p) : "memory"); return v; }
__device__ __forceinline__ uint32_t ldnc16(const void* p) { uint16_t v; asm volatile("ld.global.nc.u16 %0, [%1];" : "=h"(v) : "l"(p)); return v; }
__device__ __forceinline__ uint4 ldnc128(const void* p) { uint4 v; asm volatile("ld.global.nc.v4.u32 {%0,%1,%2,%3}, [%4];" : "=r"(v.x), "=r"(v.y), "=r"(v.z), "=r"(v.w) : "l"(p)); return v; }
__device__ __forceinline__ void cp_async16(uint32_t dst, const void* src) { asm volatile("cp.async.cg.shared.global [%0], [%1], 16;" ::"r"(dst), "l"(src) : "memory"); }
__device__ __forceinline__ uint32_t hsub2(uint32_t a, uint32_t b) { uint32_t d; asm("sub.rn.bf16x2 %0, %1, %2;" : "=r"(d) : "r"(a), "r"(b)); return d; }
__device__ __forceinline__ void stg32_if(bool c, void* p, uint32_t v) {
  asm volatile("{\n.reg .pred P;\nsetp.ne.u32 P, %2, 0;\n@P st.global.u32 [%0], %1;\n}" ::"l"(p), "r"(v), "r"((uint32_t)c) : "memory");
}
__device__ __forceinline__ float wsum(float v) { for (int o = 16; o; o >>= 1) v += __shfl_xor_sync(~0u, v, o); return v; }
__device__ __forceinline__ uint32_t hmul2(uint32_t a, uint32_t b) { uint32_t d; asm("mul.rn.bf16x2 %0, %1, %2;" : "=r"(d) : "r"(a), "r"(b)); return d; }
__device__ __forceinline__ void sts32(uint32_t a, uint32_t v) { asm volatile("st.shared.u32 [%0], %1;" ::"r"(a), "r"(v) : "memory"); }
__device__ __forceinline__ uint32_t lds32(uint32_t a) { uint32_t v; asm volatile("ld.shared.u32 %0, [%1];" : "=r"(v) : "r"(a) : "memory"); return v; }
__device__ __forceinline__ void sts128(uint32_t a, uint32_t x, uint32_t y, uint32_t z, uint32_t w) { asm volatile("st.shared.v4.u32 [%0], {%1,%2,%3,%4};" ::"r"(a), "r"(x), "r"(y), "r"(z), "r"(w) : "memory"); }
__device__ __forceinline__ uint4 lds128(uint32_t a) { uint4 v; asm volatile("ld.shared.v4.u32 {%0,%1,%2,%3}, [%4];" : "=r"(v.x), "=r"(v.y), "=r"(v.z), "=r"(v.w) : "r"(a) : "memory"); return v; }
__device__ __forceinline__ void ll_st64(uint2* p, uint32_t v, uint32_t tag) {
  asm volatile("{\n.reg .b64 r;\nmov.b64 r, {%1,%2};\nst.relaxed.gpu.global.b64 [%0], r;\n}" ::"l"(p), "r"(v), "r"(tag) : "memory");
}
__device__ __forceinline__ uint2 ll_ld64(const uint2* p) {
  uint2 v; asm volatile("{\n.reg .b64 r;\nld.relaxed.gpu.global.b64 r, [%2];\nmov.b64 {%0,%1}, r;\n}" : "=r"(v.x), "=r"(v.y) : "l"(p) : "memory"); return v;
}
__device__ __forceinline__ void ll_st128(uint4* p, float a, float b, uint32_t tag, float c = 0.f) {
  asm volatile("{\n.reg .b128 r;\n.reg .b64 lo, hi;\nmov.b64 lo, {%1,%2};\nmov.b64 hi, {%3,%4};\nmov.b128 r, {lo, hi};\nst.relaxed.gpu.global.b128 [%0], r;\n}" ::"l"(p), "r"(__float_as_uint(a)), "r"(__float_as_uint(b)), "r"(tag), "r"(__float_as_uint(c)) : "memory");
}
__device__ __forceinline__ uint4 ll_ld128g(const void* p) {
  uint4 v; asm volatile("{\n.reg .b128 r;\n.reg .b64 lo, hi;\nld.relaxed.gpu.b128 r, [%4];\nmov.b128 {lo, hi}, r;\nmov.b64 {%0,%1}, lo;\nmov.b64 {%2,%3}, hi;\n}" : "=r"(v.x), "=r"(v.y), "=r"(v.z), "=r"(v.w) : "l"(p) : "memory"); return v;
}
__device__ __forceinline__ uint4 ll_ld128(const uint4* p) {
  uint4 v; asm volatile("{\n.reg .b128 r;\n.reg .b64 lo, hi;\nld.relaxed.gpu.global.b128 r, [%4];\nmov.b128 {lo, hi}, r;\nmov.b64 {%0,%1}, lo;\nmov.b64 {%2,%3}, hi;\n}" : "=r"(v.x), "=r"(v.y), "=r"(v.z), "=r"(v.w) : "l"(p) : "memory"); return v;
}
__device__ __forceinline__ void publish_p(uint32_t el, uint32_t* f) {
  asm volatile("{\n.reg .pred P;\nsetp.ne.u32 P, %1, 0;\n@P cp.async.bulk.commit_group;\n@P cp.async.bulk.wait_group 0;\n@P red.release.gpu.global.add.u32 [%0], 1;\n}" ::"l"(f), "r"(el) : "memory");
}
__device__ __forceinline__ void stsm4(uint32_t addr, uint32_t a, uint32_t b, uint32_t c, uint32_t d) {
  asm volatile("stmatrix.sync.aligned.m8n8.x4.shared.b16 [%0], {%1,%2,%3,%4};" ::"r"(addr), "r"(a), "r"(b), "r"(c), "r"(d) : "memory");
}
__device__ __forceinline__ void sts64(uint32_t a, uint32_t x, uint32_t y) { asm volatile("st.shared.v2.u32 [%0], {%1,%2};" ::"r"(a), "r"(x), "r"(y) : "memory"); }
__device__ __forceinline__ void ll_st128_if(bool on, uint4* p, float a, float b, uint32_t tag) {
  asm volatile("{\n.reg .pred P;\n.reg .b128 r;\n.reg .b64 lo, hi;\nsetp.ne.u32 P, %4, 0;\nmov.b64 lo, {%1,%2};\nmov.b64 hi, {%3,%3};\nmov.b128 r, {lo, hi};\n@P st.relaxed.gpu.global.b128 [%0], r;\n}" ::"l"(p), "r"(__float_as_uint(a)), "r"(__float_as_uint(b)), "r"(tag), "r"((uint32_t)on) : "memory");
}
__device__ __forceinline__ uint4 ldnc128_if(bool c, const void* p) {
  uint4 v = make_uint4(0u, 0u, 0u, 0u);
  asm volatile("{\n.reg .pred P;\nsetp.ne.u32 P, %5, 0;\n@P ld.global.nc.v4.u32 {%0,%1,%2,%3}, [%4];\n}" : "+r"(v.x), "+r"(v.y), "+r"(v.z), "+r"(v.w) : "l"(p), "r"((uint32_t)c));
  return v;
}
__device__ __forceinline__ uint32_t hfma2(uint32_t a, uint32_t b, uint32_t c) { uint32_t d; asm("fma.rn.bf16x2 %0, %1, %2, %3;" : "=r"(d) : "r"(a), "r"(b), "r"(c)); return d; }
__device__ __forceinline__ float2 lds64f(uint32_t a) { float2 v; asm volatile("ld.shared.v2.f32 {%0,%1}, [%2];" : "=f"(v.x), "=f"(v.y) : "r"(a) : "memory"); return v; }
#define TRC(cond, role, idx) do {} while (0)
#define TRV(role, idx, v) do {} while (0)
#define TRVI(c, role, idx, v) do {} while (0)

#define ACLK_INIT do {} while (0)
#define ACLK(i) do {} while (0)
#define ACLK_OUT do {} while (0)
#define QCLK(i) do {} while (0)
#define PH 1
#define RCLK(i) do {} while (0)
#define RCLK_INIT do {} while (0)
#define RCLK_OUT do {} while (0)
#define SCLK(i) do {} while (0)
#define SCLK2(i) do {} while (0)
#define SCLK3(i) do {} while (0)
#define PL 1
#define PCLK(i) do {} while (0)
#define PQ 1
#define CLK_INIT do {} while (0)
#define CLK(i) do {} while (0)
#define CLK_OUT do {} while (0)

__device__ __forceinline__ void wgmma_ss_n216(float* d, uint64_t da, uint64_t db, int scaleD) {
  asm volatile("{\n.reg .pred p;\nsetp.ne.b32 p, %110, 0;\nwgmma.mma_async.sync.aligned.m64n216k16.f32.bf16.bf16 "
    "{%0,%1,%2,%3,%4,%5,%6,%7,%8,%9,%10,%11,%12,%13,%14,%15,%16,%17,%18,%19,%20,%21,%22,%23,%24,%25,%26,%27,%28,%29,%30,%31,%32,%33,%34,%35,%36,%37,%38,%39,%40,%41,%42,%43,%44,%45,%46,%47,%48,%49,%50,%51,%52,%53,%54,%55,%56,%57,%58,%59,%60,%61,%62,%63,%64,%65,%66,%67,%68,%69,%70,%71,%72,%73,%74,%75,%76,%77,%78,%79,%80,%81,%82,%83,%84,%85,%86,%87,%88,%89,%90,%91,%92,%93,%94,%95,%96,%97,%98,%99,%100,%101,%102,%103,%104,%105,%106,%107}, "
    "%108, %109, p, 1, 1, 0, 1;\n}\n"
    : "+f"(d[0]), "+f"(d[1]), "+f"(d[2]), "+f"(d[3]), "+f"(d[4]), "+f"(d[5]), "+f"(d[6]), "+f"(d[7]), "+f"(d[8]), "+f"(d[9]), "+f"(d[10]), "+f"(d[11]), "+f"(d[12]), "+f"(d[13]), "+f"(d[14]), "+f"(d[15]), "+f"(d[16]), "+f"(d[17]), "+f"(d[18]), "+f"(d[19]), "+f"(d[20]), "+f"(d[21]), "+f"(d[22]), "+f"(d[23]), "+f"(d[24]), "+f"(d[25]), "+f"(d[26]), "+f"(d[27]), "+f"(d[28]), "+f"(d[29]), "+f"(d[30]), "+f"(d[31]), "+f"(d[32]), "+f"(d[33]), "+f"(d[34]), "+f"(d[35]), "+f"(d[36]), "+f"(d[37]), "+f"(d[38]), "+f"(d[39]), "+f"(d[40]), "+f"(d[41]), "+f"(d[42]), "+f"(d[43]), "+f"(d[44]), "+f"(d[45]), "+f"(d[46]), "+f"(d[47]), "+f"(d[48]), "+f"(d[49]), "+f"(d[50]), "+f"(d[51]), "+f"(d[52]), "+f"(d[53]), "+f"(d[54]), "+f"(d[55]), "+f"(d[56]), "+f"(d[57]), "+f"(d[58]), "+f"(d[59]), "+f"(d[60]), "+f"(d[61]), "+f"(d[62]), "+f"(d[63]), "+f"(d[64]), "+f"(d[65]), "+f"(d[66]), "+f"(d[67]), "+f"(d[68]), "+f"(d[69]), "+f"(d[70]), "+f"(d[71]), "+f"(d[72]), "+f"(d[73]), "+f"(d[74]), "+f"(d[75]), "+f"(d[76]), "+f"(d[77]), "+f"(d[78]), "+f"(d[79]), "+f"(d[80]), "+f"(d[81]), "+f"(d[82]), "+f"(d[83]), "+f"(d[84]), "+f"(d[85]), "+f"(d[86]), "+f"(d[87]), "+f"(d[88]), "+f"(d[89]), "+f"(d[90]), "+f"(d[91]), "+f"(d[92]), "+f"(d[93]), "+f"(d[94]), "+f"(d[95]), "+f"(d[96]), "+f"(d[97]), "+f"(d[98]), "+f"(d[99]), "+f"(d[100]), "+f"(d[101]), "+f"(d[102]), "+f"(d[103]), "+f"(d[104]), "+f"(d[105]), "+f"(d[106]), "+f"(d[107])
    : "l"(da), "l"(db), "r"(scaleD));
}
__device__ __forceinline__ void wgmma_ss_n72(float* d, uint64_t da, uint64_t db, int scaleD) {
  asm volatile("{\n.reg .pred p;\nsetp.ne.b32 p, %38, 0;\nwgmma.mma_async.sync.aligned.m64n72k16.f32.bf16.bf16 "
    "{%0,%1,%2,%3,%4,%5,%6,%7,%8,%9,%10,%11,%12,%13,%14,%15,%16,%17,%18,%19,%20,%21,%22,%23,%24,%25,%26,%27,%28,%29,%30,%31,%32,%33,%34,%35}, "
    "%36, %37, p, 1, 1, 0, 1;\n}\n"
    : "+f"(d[0]), "+f"(d[1]), "+f"(d[2]), "+f"(d[3]), "+f"(d[4]), "+f"(d[5]), "+f"(d[6]), "+f"(d[7]), "+f"(d[8]), "+f"(d[9]), "+f"(d[10]), "+f"(d[11]), "+f"(d[12]), "+f"(d[13]), "+f"(d[14]), "+f"(d[15]), "+f"(d[16]), "+f"(d[17]), "+f"(d[18]), "+f"(d[19]), "+f"(d[20]), "+f"(d[21]), "+f"(d[22]), "+f"(d[23]), "+f"(d[24]), "+f"(d[25]), "+f"(d[26]), "+f"(d[27]), "+f"(d[28]), "+f"(d[29]), "+f"(d[30]), "+f"(d[31]), "+f"(d[32]), "+f"(d[33]), "+f"(d[34]), "+f"(d[35])
    : "l"(da), "l"(db), "r"(scaleD));
}
__device__ __forceinline__ void wgmma_ss_n128(float* d, uint64_t da, uint64_t db, int scaleD) {
  asm volatile("{\n.reg .pred p;\nsetp.ne.b32 p, %66, 0;\nwgmma.mma_async.sync.aligned.m64n128k16.f32.bf16.bf16 "
    "{%0,%1,%2,%3,%4,%5,%6,%7,%8,%9,%10,%11,%12,%13,%14,%15,%16,%17,%18,%19,%20,%21,%22,%23,%24,%25,%26,%27,%28,%29,%30,%31,%32,%33,%34,%35,%36,%37,%38,%39,%40,%41,%42,%43,%44,%45,%46,%47,%48,%49,%50,%51,%52,%53,%54,%55,%56,%57,%58,%59,%60,%61,%62,%63}, "
    "%64, %65, p, 1, 1, 0, 1;\n}\n"
    : "+f"(d[0]), "+f"(d[1]), "+f"(d[2]), "+f"(d[3]), "+f"(d[4]), "+f"(d[5]), "+f"(d[6]), "+f"(d[7]), "+f"(d[8]), "+f"(d[9]), "+f"(d[10]), "+f"(d[11]), "+f"(d[12]), "+f"(d[13]), "+f"(d[14]), "+f"(d[15]), "+f"(d[16]), "+f"(d[17]), "+f"(d[18]), "+f"(d[19]), "+f"(d[20]), "+f"(d[21]), "+f"(d[22]), "+f"(d[23]), "+f"(d[24]), "+f"(d[25]), "+f"(d[26]), "+f"(d[27]), "+f"(d[28]), "+f"(d[29]), "+f"(d[30]), "+f"(d[31]), "+f"(d[32]), "+f"(d[33]), "+f"(d[34]), "+f"(d[35]), "+f"(d[36]), "+f"(d[37]), "+f"(d[38]), "+f"(d[39]), "+f"(d[40]), "+f"(d[41]), "+f"(d[42]), "+f"(d[43]), "+f"(d[44]), "+f"(d[45]), "+f"(d[46]), "+f"(d[47]), "+f"(d[48]), "+f"(d[49]), "+f"(d[50]), "+f"(d[51]), "+f"(d[52]), "+f"(d[53]), "+f"(d[54]), "+f"(d[55]), "+f"(d[56]), "+f"(d[57]), "+f"(d[58]), "+f"(d[59]), "+f"(d[60]), "+f"(d[61]), "+f"(d[62]), "+f"(d[63])
    : "l"(da), "l"(db), "r"(scaleD));
}
__device__ __forceinline__ void wgmma_ss_n160(float* d, uint64_t da, uint64_t db, int scaleD) {
  asm volatile("{\n.reg .pred p;\nsetp.ne.b32 p, %82, 0;\nwgmma.mma_async.sync.aligned.m64n160k16.f32.bf16.bf16 "
    "{%0,%1,%2,%3,%4,%5,%6,%7,%8,%9,%10,%11,%12,%13,%14,%15,%16,%17,%18,%19,%20,%21,%22,%23,%24,%25,%26,%27,%28,%29,%30,%31,%32,%33,%34,%35,%36,%37,%38,%39,%40,%41,%42,%43,%44,%45,%46,%47,%48,%49,%50,%51,%52,%53,%54,%55,%56,%57,%58,%59,%60,%61,%62,%63,%64,%65,%66,%67,%68,%69,%70,%71,%72,%73,%74,%75,%76,%77,%78,%79}, "
    "%80, %81, p, 1, 1, 0, 1;\n}\n"
    : "+f"(d[0]), "+f"(d[1]), "+f"(d[2]), "+f"(d[3]), "+f"(d[4]), "+f"(d[5]), "+f"(d[6]), "+f"(d[7]), "+f"(d[8]), "+f"(d[9]), "+f"(d[10]), "+f"(d[11]), "+f"(d[12]), "+f"(d[13]), "+f"(d[14]), "+f"(d[15]), "+f"(d[16]), "+f"(d[17]), "+f"(d[18]), "+f"(d[19]), "+f"(d[20]), "+f"(d[21]), "+f"(d[22]), "+f"(d[23]), "+f"(d[24]), "+f"(d[25]), "+f"(d[26]), "+f"(d[27]), "+f"(d[28]), "+f"(d[29]), "+f"(d[30]), "+f"(d[31]), "+f"(d[32]), "+f"(d[33]), "+f"(d[34]), "+f"(d[35]), "+f"(d[36]), "+f"(d[37]), "+f"(d[38]), "+f"(d[39]), "+f"(d[40]), "+f"(d[41]), "+f"(d[42]), "+f"(d[43]), "+f"(d[44]), "+f"(d[45]), "+f"(d[46]), "+f"(d[47]), "+f"(d[48]), "+f"(d[49]), "+f"(d[50]), "+f"(d[51]), "+f"(d[52]), "+f"(d[53]), "+f"(d[54]), "+f"(d[55]), "+f"(d[56]), "+f"(d[57]), "+f"(d[58]), "+f"(d[59]), "+f"(d[60]), "+f"(d[61]), "+f"(d[62]), "+f"(d[63]), "+f"(d[64]), "+f"(d[65]), "+f"(d[66]), "+f"(d[67]), "+f"(d[68]), "+f"(d[69]), "+f"(d[70]), "+f"(d[71]), "+f"(d[72]), "+f"(d[73]), "+f"(d[74]), "+f"(d[75]), "+f"(d[76]), "+f"(d[77]), "+f"(d[78]), "+f"(d[79])
    : "l"(da), "l"(db), "r"(scaleD));
}
__device__ __forceinline__ void wgmma_rs_n144(float* d, const uint32_t* a, uint64_t db, int scaleD) {
  asm volatile("{\n.reg .pred p;\nsetp.ne.b32 p, %77, 0;\nwgmma.mma_async.sync.aligned.m64n144k16.f32.bf16.bf16 "
    "{%0,%1,%2,%3,%4,%5,%6,%7,%8,%9,%10,%11,%12,%13,%14,%15,%16,%17,%18,%19,%20,%21,%22,%23,%24,%25,%26,%27,%28,%29,%30,%31,%32,%33,%34,%35,%36,%37,%38,%39,%40,%41,%42,%43,%44,%45,%46,%47,%48,%49,%50,%51,%52,%53,%54,%55,%56,%57,%58,%59,%60,%61,%62,%63,%64,%65,%66,%67,%68,%69,%70,%71}, "
    "{%72,%73,%74,%75}, %76, p, 1, 1, 1;\n}\n"
    : "+f"(d[0]), "+f"(d[1]), "+f"(d[2]), "+f"(d[3]), "+f"(d[4]), "+f"(d[5]), "+f"(d[6]), "+f"(d[7]), "+f"(d[8]), "+f"(d[9]), "+f"(d[10]), "+f"(d[11]), "+f"(d[12]), "+f"(d[13]), "+f"(d[14]), "+f"(d[15]), "+f"(d[16]), "+f"(d[17]), "+f"(d[18]), "+f"(d[19]), "+f"(d[20]), "+f"(d[21]), "+f"(d[22]), "+f"(d[23]), "+f"(d[24]), "+f"(d[25]), "+f"(d[26]), "+f"(d[27]), "+f"(d[28]), "+f"(d[29]), "+f"(d[30]), "+f"(d[31]), "+f"(d[32]), "+f"(d[33]), "+f"(d[34]), "+f"(d[35]), "+f"(d[36]), "+f"(d[37]), "+f"(d[38]), "+f"(d[39]), "+f"(d[40]), "+f"(d[41]), "+f"(d[42]), "+f"(d[43]), "+f"(d[44]), "+f"(d[45]), "+f"(d[46]), "+f"(d[47]), "+f"(d[48]), "+f"(d[49]), "+f"(d[50]), "+f"(d[51]), "+f"(d[52]), "+f"(d[53]), "+f"(d[54]), "+f"(d[55]), "+f"(d[56]), "+f"(d[57]), "+f"(d[58]), "+f"(d[59]), "+f"(d[60]), "+f"(d[61]), "+f"(d[62]), "+f"(d[63]), "+f"(d[64]), "+f"(d[65]), "+f"(d[66]), "+f"(d[67]), "+f"(d[68]), "+f"(d[69]), "+f"(d[70]), "+f"(d[71])
    : "r"(a[0]), "r"(a[1]), "r"(a[2]), "r"(a[3]), "l"(db), "r"(scaleD));
}
__device__ __forceinline__ void wgmma_rs_n64(float* d, const uint32_t* a, uint64_t db, int scaleD) {
  asm volatile("{\n.reg .pred p;\nsetp.ne.b32 p, %37, 0;\nwgmma.mma_async.sync.aligned.m64n64k16.f32.bf16.bf16 "
    "{%0,%1,%2,%3,%4,%5,%6,%7,%8,%9,%10,%11,%12,%13,%14,%15,%16,%17,%18,%19,%20,%21,%22,%23,%24,%25,%26,%27,%28,%29,%30,%31}, "
    "{%32,%33,%34,%35}, %36, p, 1, 1, 1;\n}\n"
    : "+f"(d[0]), "+f"(d[1]), "+f"(d[2]), "+f"(d[3]), "+f"(d[4]), "+f"(d[5]), "+f"(d[6]), "+f"(d[7]), "+f"(d[8]), "+f"(d[9]), "+f"(d[10]), "+f"(d[11]), "+f"(d[12]), "+f"(d[13]), "+f"(d[14]), "+f"(d[15]), "+f"(d[16]), "+f"(d[17]), "+f"(d[18]), "+f"(d[19]), "+f"(d[20]), "+f"(d[21]), "+f"(d[22]), "+f"(d[23]), "+f"(d[24]), "+f"(d[25]), "+f"(d[26]), "+f"(d[27]), "+f"(d[28]), "+f"(d[29]), "+f"(d[30]), "+f"(d[31])
    : "r"(a[0]), "r"(a[1]), "r"(a[2]), "r"(a[3]), "l"(db), "r"(scaleD));
}

template <int V> struct Int { static constexpr int value = V; };
struct Cur {
  uint32_t s, ph;
  __device__ __forceinline__ void next() { if (++s == NST) { s = 0; ph ^= 1; } }
};

__device__ __forceinline__ uint32_t o_place(uint32_t w, uint32_t e) { return (((w ? 0xd5310u : 0xa8d57u) >> (4 * e)) & 15) * 8192 + 90112; }
#define z1_block(rb, w, j) (Q.Z + ((rb) * 16 + (w) * 8 + (j)) * ZB)
#define xn_block(hw) (Q.Z + (512 + (hw) * 2) * ZB)
#define z2_block(kb, j) (Q.Z + (256 + (kb) * 8 + (j)) * ZB)
template <int N> __device__ __forceinline__ void pause(uint32_t zero) {
  if (N <= 0) return;
  uint32_t z = clock() + threadIdx.x;
  do {
#pragma unroll (N > 8 ? 1 : 8)
    for (int i = 0; i < N; i++) asm volatile("shfl.sync.bfly.b32 %0, %0, 1, 0x1f, 0xffffffff;" : "+r"(z)::"memory");
  } while (__any_sync(~0u, z & zero));
}

__global__ void __cluster_dims__(2, 1, 1) __launch_bounds__(384, 1) mega_kernel(const Ptrs Q, const __grid_constant__ Params P) {
  extern __shared__ __align__(1024) uint8_t smem_raw[];
  const uint32_t sb = smem_u32(smem_raw);
  const uint32_t bars = sb + SM_BAR;
  const int tid = threadIdx.x;
  int lane = tid & 31;
  const int wid = __shfl_sync(~0u, tid >> 5, 0);
  const int cl = blockIdx.x >> 1;
  const int bid = (cl < 4 ? cl * 8 + 32 : cl - 4 + (max(cl - 29, 0) * 37 >> 8)) * 2 + (blockIdx.x & 1);
  const int rb = bid & 15, j = bid >> 4;
  uint4 wv[5];
  {
    const int n8 = min(tid >> 3, 26), part = n8 / 9;
    const uint8_t* src = (const uint8_t*)Q.wqkv + (8 * rb + (tid & 7)) * (3 * DM * 2) + (part * (DM - 72) + 72 * j + 8 * n8) * 2;
#pragma unroll
    for (int u = 0; u < 5; u++) wv[u] = ldnc128_if(tid < 216 && cl < 64 && (u < 4 || rb < 8), src + u * (128 * 3 * DM * 2));
  }
  if (cl >= 64) return;
  if (wid >= 7 && lane == 0) {
    if (wid < 10) {
#pragma unroll
      for (uint32_t b = 0; b < B_AD / 3; b += 8) mbar_init(bars + (wid - 7) * (B_AD / 3) + b, 1);
    } else if (wid == 10) {
#pragma unroll
      for (uint32_t b = B_AD; b < B_EVT; b += 8) mbar_init(bars + b, b < B_LAG ? 2 : 4);
    } else {
#pragma unroll
      for (uint32_t b = B_EVT; b < 1024; b += 8) if (b < B_OFF || b >= B_IMG) mbar_init(bars + b, b < B_IMG ? 4 : b < B_EMPTY ? 8 : 16);
    }
    asm volatile("fence.mbarrier_init.release.cluster;" ::: "memory");
  }
  __syncthreads();

  if (wid >= 8) {
    reg_dealloc<56>();
    const uint32_t el = elect_one();
    const uint64_t pol = policy_evict_first();
    uint32_t* const fj = Q.flags + FJ + j * 32;
    if (wid == 8) {
      if (el) { prefetch_map(&P.wsp); prefetch_map(&P.winb[j & 1]); prefetch_map(&P.wins); prefetch_map(&P.wout); prefetch_map(&P.act[1]); prefetch_map(&P.res[0]); prefetch_map(&P.res[1]); prefetch_map(&P.row[1]); }
      const uint32_t epoch = ldcg32(fj + FJ_EP + rb);
      Cur c{0, 1};
      const uint32_t rk = bid & 1;
      uint32_t st, full;
      auto slot = [&](uint32_t bytes) {
        st = sb + c.s * ST_BYTES; full = bars + B_FULL + c.s * 8;
        mbar_wait(full, c.ph);
        expect_tx_p(el, full, bytes);
        mbar_wait(full - B_FULL + B_EMPTY, c.ph);
      };
#pragma unroll 1
      for (int L = 0; L < 2; L++) {
#pragma unroll 1
        for (int i = 0; i < 9; i++) {
          if (L == 0 && i == 0) {
            flag_wait(fj + FJ_WQ, (epoch + 1) * 16);
            fence_async_g();
            TRC(el, 2, 45);
          }
          slot(27648);
          bulk_mc_h(el, st + ST_B + rk * 13824, Q.WQ + j * WQ_SL + i * 27648 + rk * 13824, 13824, full, EF(0), pol);
          c.next();
        }
        if (L == 0) {
          flag_wait(fj + FJ_WO, (epoch + 1) * 16);
          fence_async_g();
          TRC(el, 2, 46);
        }
#pragma unroll 1
        while (c.s) {
          mbar_wait(bars + B_EMPTY + c.s * 8, c.ph);
          if (el) { mbar_arrive(bars + B_FULL + c.s * 8); asm volatile("mbarrier.arrive.shared::cta.b64 _, [%0], 16;" ::"r"(bars + B_EMPTY + c.s * 8) : "memory"); }
          c.next();
        }
        expect_tx_p(el, bars + B_WF, WO_SL);
        mbar_wait(bars + B_EMPTY, c.ph);
        mbar_wait(bars + B_EMPTY + 8, c.ph);
        bulk_mc_h(el, sb + rk * (WO_SL / 2), Q.WO + j * WO_SL + rk * (WO_SL / 2), WO_SL / 2, bars + B_WF, EF(1), pol);
#pragma unroll 1
        for (int r = 0; r < 10; r++) {
          const bool big = r >= 2 && r < 8;
          const int a0 = (r < 5 ? 36 : 0) + ((9 * j) >> 1) + (big ? 2 - 2 * (j & 1) : 3 * (j & 1) + rk), ks = big ? 32 : 48;
          int k = big ? (r < 5 ? r - 2 : r - 5) * 192 + rk * 16 : (r & 1) * 288;
          const CUtensorMap* m = big ? &P.winb[j & 1] : &P.wins;
          const uint32_t dst = sb + SM_B3 + rk * 6144;
#pragma unroll
          for (int p = 0; p < 6; p++, k += ks) {
            if (!(p & 3) && r == 0) mbar_wait(bars + B_XD + p * 2, L);
            if (p) mbar_wait_c(bars + B_E3 + p * 8, ~r & 1); else mbar_wait(bars + B_E3, ~r & 1);
            expect_tx_p(el, bars + B_F3 + p * 8, 12288);
            tma3d_mc_h(el, dst + p * 12288, m, 0, k, a0, bars + B_F3 + p * 8, EF(2), pol);
          }
        }
        TRC(el, 2, L * 16 + 6);
        mbar_wait(bars + B_ZOK, L);
        fence_async_g();
        TRC(el, 2, L * 16 + 7);
        const uint8_t* src = z2_block(0, j) + rk * 18432;
#pragma unroll 1
        for (int r = 0; r < 8; r++) {
          const int k = (r & 3) * 512 + ((r >> 2) ^ 1) * 64;
#pragma unroll
          for (int p = 0; p < 4; p++, src += 8 * ZB) {
            if ((p == 1 || p == 2) && r == 0) mbar_wait(bars + B_E3 - 8 + p * 24, 1);
            mbar_wait_c(bars + B_AD + p * 8, ~r & 1);
            if (p) mbar_wait_c(bars + B_EMPTY + p * 8, c.ph); else mbar_wait(bars + B_EMPTY, c.ph);
            expect_tx_p(el, bars + B_FULL + p * 8, ST_BYTES);
            bulk_mc_h(el, sb + p * ST_BYTES + ST_B + rk * 18432, src, 18432, bars + B_FULL + p * 8, EF(4), pol);
            tma3d_h(el, sb + p * ST_BYTES, &P.wsp, k + p * 128, rb * 64, 0, bars + B_FULL + p * 8, EF(3), pol);
          }
          c.ph ^= 1;
        }
        mbar_wait(bars + B_Z1, L);
        fence_async_g();
#pragma unroll 1
        for (int i = 0; i < 11; i++) {
          const int cb = i - 2 + j;
          if (i < 4) mbar_wait(bars + B_AD + c.s * 8, 1);
          slot(ZB);
          if (i < 2) bulk_load_h(el, st + ST_B, z1_block(rb, i, j), ZB, full, true, pol);
          else tma2d_mc_h(el, st + ST_B + rk * 18432, &P.wout, (cb >= 9 ? cb - 9 : cb) * 64, 288 * j + rk * 144, full, EF(5), pol);
          c.next();
        }
      }
    } else if (wid < 11) {
      uint32_t id = bid * 2 + wid - 9;
#define AGENT_IDS asm volatile("" : "+r"(lane), "+r"(id)); const uint32_t w = id & 1, hw = id & 31, rb = hw >> 1, j = id >> 5, ev = bars + B_EVT + w * EV_N * 8; \
      uint32_t* const fr = Q.flags + hw * 32; uint32_t* const fj = Q.flags + FJ + j * 32; (void)fr; (void)fj; (void)ev; (void)rb
      uint32_t t8 = 0;
      Cur c{0, 1};
#pragma unroll 1
      for (int L = 0; L < 2; L++) {
        if (L) {
          AGENT_IDS;
          const uint32_t full = bars + B_FULLA + w * 32 + c.s * 8, dst = sb + c.s * ST_BYTES + w * 8192;
          expect_tx_p(el, full, 8192);
          mbar_wait_c(ev + EV_PT * 8, 1);
          TRC(el, 3, w * 32 + 16);
          flag_release_p(el, fr + FR_X2);
          TRC(el, 3, w * 32 + 17);
          mbar_wait_c(bars + B_EMPTY + c.s * 8, c.ph);
          flag_wait(fr + FR_X2, t8);
          fence_async_g();
          tma3d_h(el, dst, &P.act[1], 0, rb * 64, w, full, false, pol);
          c.next();
          TRC(el, 3, w * 32 + 18);
        }
#pragma unroll 1
        for (int i = L; i < 9; i++) {
          AGENT_IDS;
          const uint32_t full = bars + B_FULLA + w * 32 + c.s * 8, dst = sb + c.s * ST_BYTES + w * 8192;
          if (L == 0 && i == AEP) t8 = (ldcg32(fr + FR_EP + j) + 1) * 8;
          mbar_wait_c(bars + B_EMPTY + c.s * 8, c.ph);
          expect_tx_p(el, full, 8192);
          tma3d_h(el, dst, &P.act[L], i * 64, rb * 64, w, full, false, pol);
          c.next();
          if (i == PZI || i == PZI + 1) {
            uint8_t* d = (i == PZI ? xn_block(hw) : z1_block(rb, 0, 0) + w * 4608) + j * 9216 + lane * 16;
#pragma unroll 1
            for (int u = i == PZI ? 0 : 3; u < 6; u++, d += 1536) { stg128(d, ~0u, ~0u, ~0u, ~0u); stg128(d + 512, ~0u, ~0u, ~0u, ~0u); stg128(d + 1024, ~0u, ~0u, ~0u, ~0u); }
          }
          if (i == PZI) { stg128(Q.ST1 + (hw * 8 + j) * 32 + lane, ~0u, ~0u, ~0u, ~0u); stg128(Q.ZST + (hw * 8 + j) * 32 + lane, ~0u, ~0u, ~0u, ~0u); }
          if (i == RFI) {
            expect_tx_p(el, bars + B_WT + w * 8, 9216);
            tma3d_h(el, sb + SM_STG + w * 9216, &P.row[L], 0, 3 * w, rb * 64 + 8 * j, bars + B_WT + w * 8, false, pol);
          }
          if (i == 4 && L > w) {
            expect_tx_p(el, bars + B_XRW + 8, 864);
            bulk_load_p(el, sb + 3 * ST_BYTES + SM_CSQ, Q.CSP + (NCTA + (id >> 1)) * 216, 864, bars + B_XRW + 8);
          }
        }
        if (c.s) { c.s = 0; c.ph ^= 1; }
        {
          AGENT_IDS;
          const uint32_t tag = (t8 >> 2) - 1 + L;
          uint4* const xs = Q.XST + hw * 128;
          const uint32_t tab = sb + L * (3 * ST_BYTES) + SM_XST + w * 768 + lane * 8;
          TRC(el, 3, w * 32 + L * 16 + 13);
#pragma unroll 1
          for (int it = 0; it < (1 << 22); it++) {
            const uint4 a = ll_ld128(xs + 2 * lane), b = ll_ld128(xs + 64 + 2 * lane), h = ll_ld128(xs - (rb ? 192 : 0) + 2 * (lane | 24));
            if (__all_sync(~0u, a.z == tag && b.z == tag && h.z == tag)) { sts64(tab, h.x, h.y); sts64(tab + 256, a.x, a.y); sts64(tab + 512, b.x, b.y); break; }
          }
          __syncwarp();
          if (el) mbar_arrive(bars + B_CSQ);
          TRC(el, 3, w * 32 + L * 16 + 14);
          uint32_t* f = Q.flags + rb * 64 + FR_PZ + L;
          flag_release_p(el, f);
          expect_tx_p(el, bars + B_RES + w * 8, 9216);
          tma3d_h(el, sb + SM_STG + w * 9216, &P.res[L], j * 72, (hw ^ 1) * 32, 0, bars + B_RES + w * 8, !L, pol);
          pause<FD3>(Q.zero);
          flag_wait(f, t8 * 2);
          fence_async_g();
          TRC(el, 3, w * 32 + L * 16 + 15);
        }
        {
          AGENT_IDS;
          uint32_t* f = Q.flags + rb * 64 + FR_O + L;
#pragma unroll 1
          for (int e = 0; e < 5; e++) {
            const uint32_t nb = e ? 16384 : 8192, full = bars + B_OF + w * 40 + e * 8, dst = sb + o_place(w, e);
            const uint8_t* src = z1_block(rb, w, 0) + (e ? e * 16384 - 8192 : 0);
            expect_tx_p(el, full, nb);
            if (e == 0) {
              mbar_wait_c(ev + EV_O * 8, L);
              TRC(el, 3, w * 32 + L * 16 + 3);
              if (!w) flag_add_p(el, f);
              flag_wait(f + w * (FR_OL - FR_O), t8);
              if (w) fence_async_g();
            }
            if (w && (e == 0 || e == 3)) mbar_wait_c(bars + (e ? B_X3 : B_OF + YPACE * 8), L);
            bulk_load_h(el, dst, src, nb, full, EF(6), pol);
            TRC(el && e == 0, 3, w * 32 + L * 16 + 5);
          }
        }
        {
          AGENT_IDS;
          const uint8_t* src = xn_block(hw);
          uint32_t full = bars + B_AF3 + w * 96, dst = sb + w * 6144;
          if (L) flag_wait(fj + FJ_P4, t8 * 4);
          mbar_wait_c(bars + B_XD + 8, L);
          mbar_wait_c(ev + EV_X1 * 8, L);
          TRC(el, 3, w * 32 + L * 16 + 6);
          pause<SDEL>(Q.zero);
#pragma unroll 1
          for (int k = 0; k < 12; k++, src += 6144, dst += 12288, full += 8) {
            expect_tx_p(el, full, 6144);
            if (k >= APACE) mbar_wait_c(full - APACE * 8, L);
            bulk_load_h(el, dst, src, 6144, full, EF(7), pol);
            TRC(el && k == 0, 3, w * 32 + L * 16 + 8);
          }
        }
        if (wid == 10) {
          AGENT_IDS;
          mbar_wait_c(ev - (EV_N - EV_ZN) * 8, L);
          mbar_wait_c(ev + EV_ZN * 8, L);
          asm volatile("fence.release.gpu;" ::: "memory");
          flag_add_p(el, fj + FJ_ZN + L);
          flag_add_p(el, fr - 32 + FR_XR + L);
          pause<FD4>(Q.zero);
          flag_wait(fj + FJ_ZN + L, t8 * 2);
          flag_wait(fr - 32 + FR_XR + L, t8);
          if (el) mbar_arrive(bars + B_ZOK);
        } else if (WPF) {
          AGENT_IDS;
          mbar_wait_c(ev + EV_ZN * 8, L);
          if (el) asm volatile("cp.async.bulk.prefetch.tensor.3d.L2.global [%0, {%1, %2, %3}];" ::"l"(&P.wsp), "r"(j * 128 + 64), "r"(rb * 64), "r"(0) : "memory");

        }
        float cv;
        {
        AGENT_IDS;
        cv = (lane & 3) ? 0.f : -blo(ldnc16(Q.b_sp + 128 * rb + 16 * j + 2 * (lane >> 2) + w));
        const uint32_t ro = (w * 64 + 8 * j + (lane >> 2)) * 128, x0 = ((lane & 3) * 2) ^ (lane >> 2);
#pragma unroll 1
        for (int i = 0; i < 32; i++) {
          const bool tail = (i >> 1) == 12;
          const int kb = tail ? i + 6 : i < 24 ? i : i - 2;
          if (!(i & 7)) mbar_wait_c(bars + B_RT + i, L);
          if (i == 24) mbar_wait_c(bars + B_WT + w * 8, 1);
          if (!tail) mbar_wait(bars + B_FULL + c.s * 8, c.ph ^ 1);
          uint4 x[2];
#pragma unroll
          for (int e = 0; e < 2; e++) x[e] = lds128(!tail ? sb + c.s * ST_BYTES + ro + ((x0 ^ e) << 4) : sb + SM_WT + w * 3200 + (lane >> 2) * 400 + (i - 24) * 256 + (lane & 3) * 32 + e * 16);
          if (!tail) {
            __syncwarp();
            if (el) mbar_arrive(bars + B_AD + c.s * 8);
            c.next();
          }
#pragma unroll
          for (int e = 0; e < 2; e++) {
            const uint4 a = x[e], m = lds128(sb + SM_RT + 4096 + kb * 128 + (lane & 3) * 32 + e * 16);
            cv = fmaf(blo(a.x), blo(m.x), fmaf(bhi(a.x), bhi(m.x), fmaf(blo(a.y), blo(m.y), fmaf(bhi(a.y), bhi(m.y), cv))));
            cv = fmaf(blo(a.z), blo(m.z), fmaf(bhi(a.z), bhi(m.z), fmaf(blo(a.w), blo(m.w), fmaf(bhi(a.w), bhi(m.w), cv))));
          }
          if (i == WTI) {
            uint32_t id2 = id;
            asm volatile("" : "+r"(id2));
            expect_tx_p(el, bars + B_WT + w * 8, 3072);
#pragma unroll 1
            for (int r = 0; r < 8; r++)
              bulk_load_p(el, sb + SM_WT + w * 3200 + r * 400, (const uint8_t*)Q.w_sp + (64 * (id2 & 30) + 16 * (id2 >> 5) + 2 * r + w) * (SEQ * 2) + 28 * 128, 384, bars + B_WT + w * 8);
          }
        }
        }
        AGENT_IDS;
        TRC(el, 3, w * 32 + L * 16 + 11);
        asm volatile("" : "+r"(t8));
        const uint32_t tag = (t8 >> 2) - 1 + L;
        cv = qsum(cv);
        uint2* const cs = (uint2*)(Q.XST + hw * 128 + 1);
        if ((lane & 3) == 0) ll_st64(cs + 32 * j + (lane >> 2) * 4, __float_as_uint(cv), tag);
        pause<FD5>(Q.zero);
#pragma unroll 1
        for (int it = 0; it < (1 << 22); it++) {
          const uint2 a = ll_ld64(cs + 4 * lane), b = ll_ld64(cs + 128 + 4 * lane);
          if (__all_sync(~0u, a.y == tag && b.y == tag)) { sts32(sb + SM_CV + w * 256 + lane * 4, a.x); sts32(sb + SM_CV + w * 256 + 128 + lane * 4, b.x); break; }
        }
        __syncwarp();
        if (el) mbar_arrive(bars + B_CV + w * 8);
        TRC(el, 3, w * 32 + L * 16 + 12);
#pragma unroll 1
        for (int kb = 30; kb < 32; kb++) {
          mbar_wait_c(bars + B_FULL + c.s * 8, c.ph ^ 1);
          if (el) mbar_arrive(bars + B_AD + c.s * 8);
          c.next();
        }
        c.ph ^= ((c.s + 11) >> 2) & 1; c.s = (c.s + 11) & 3;
        if (L == 0) {
          mbar_wait_c(ev + EV_PT * 8, 0);
          flag_add_p(el, fj + FJ_P4);
        }
      }
    } else {
      const uint32_t epoch = ldcg32(fj + FJ_EP + rb);
      mbar_wait(bars + B_IMG, 0);
      TRC(el, 2, 41);
      flag_release_p(el, fj + FJ_WQ);
      TRC(el, 2, 42);
#pragma unroll 1
      for (int L = 0; L < 2; L++) {
        float* const csf = Q.CSP + (NCTA + bid) * 216;
        if (L == 0) {
          flag_wait(fj + FJ_WQ, (epoch + 1) * 16);
          fence_async_g();
          expect_tx_p(el, bars + B_XRW, 13824);
          bulk_load_p(el, sb + ST_BYTES + SM_WOI, Q.CSP + j * 16 * 216, 6912, bars + B_XRW);
          bulk_load_p(el, sb + 2 * ST_BYTES + SM_WOI, Q.CSP + (j * 16 + 8) * 216, 6912, bars + B_XRW);
          mbar_wait(bars + B_XRW, 0);
#pragma unroll 1
          for (int f = lane; f < 54; f += 32) {
            float s[4] = {0.f, 0.f, 0.f, 0.f};
#pragma unroll 2
            for (int r = 0; r < 16; r++) {
              const uint4 v = lds128(sb + ST_BYTES + SM_WOI + (r >> 3) * ST_BYTES + (r & 7) * 864 + f * 16);
              s[0] += __uint_as_float(v.x); s[1] += __uint_as_float(v.y); s[2] += __uint_as_float(v.z); s[3] += __uint_as_float(v.w);
            }
            sts128(sb + SM_CSQ + f * 16, __float_as_uint(s[0]), __float_as_uint(s[1]), __float_as_uint(s[2]), __float_as_uint(s[3]));
            stg128(csf + f * 4, __float_as_uint(s[0]), __float_as_uint(s[1]), __float_as_uint(s[2]), __float_as_uint(s[3]));
          }
          __syncwarp();
          if (el) mbar_arrive(bars + B_XRW + 8);
          TRC(el, 2, 43);
          mbar_wait(bars + B_WOI, 0);
          bulk_store_p(el, Q.WO + j * WO_SL + rb * (41 * 128), sb + SM_WOI, (rb < 15 ? 41 : 33) * 128);
          publish_p(el, fj + FJ_WO);
          TRC(el, 2, 44);
          if (el) prefetch_l2((const uint8_t*)Q.w_in + bid * 41472, 41472);
          float o0 = 0.f, o1 = 0.f;
#pragma unroll 1
          for (int u = 0; u < 2; u++) {
            const uint8_t* src = (u ? (const uint8_t*)Q.w_sp + 500 * (SEQ * 2) + 2048 : (const uint8_t*)Q.w_in + 100 * (2 * FH * 2) + FH * 2) + lane * 16;
            const uint4 a = ldnc128(src), b = ldnc128(src + 300 * (2 * FH * 2) + 2048);
            const uint32_t x[8] = {a.x, a.y, a.z, a.w, b.x, b.y, b.z, b.w};
            float sq = 0.f;
#pragma unroll
            for (int e = 0; e < 8; e++) sq = fmaf(blo(x[e]), blo(x[e]), fmaf(bhi(x[e]), bhi(x[e]), sq));
            o0 = o1;
            asm("sqrt.approx.f32 %0, %1;" : "=f"(o1) : "f"(wsum(sq) * (u ? C0S * C0S * SEQ / 512.f : 2.f * GA * GA * DM / 512.f)));
          }
          const uint32_t off = (__float_as_uint(o0) & 0x7f800000u) >> 16 | 0x8000u | OFM;
          const uint32_t c0 = min(max(__float_as_uint(o1) & 0x7f800000u, 0x04000000u), 0x7e000000u) | 0x00400000u;
          if (el) sts128(sb + SM_OFF, off * 0x10001u, c0, __float_as_uint(GB), ((c0 >> 16) - 0x200u) * 0x10001u);
        }
        mbar_wait(bars + B_EVT + EV_O * 8, L);
        mbar_wait(bars + B_EVT + (EV_N + EV_O) * 8, L);
        flag_release_p(el, Q.flags + rb * 64 + FR_OL + L);
#pragma unroll 1
        for (int w = 0; w < 2; w++) {
          mbar_wait(bars + B_EVT + (w * EV_N + EV_XS) * 8, L);
          if (!w) mbar_wait(bars + B_AF3 + 96 + XP0 * 8, L);
          if (el) asm volatile("cp.async.bulk.tensor.3d.global.shared::cta.tile.bulk_group [%0, {%2, %3, %4}], [%1];\ncp.async.bulk.commit_group;\ncp.async.bulk.wait_group.read 0;" ::"l"(&P.res[1]), "r"(sb + SM_STG + 9216), "r"(j * 72), "r"(rb * 64 + (w ^ 1) * 32), "r"(0) : "memory");
          __syncwarp();
          if (lane < 2 && !w) mbar_arrive(bars + B_S5);
        }
        sts64(sb + SM_CV + 512 + lane * 8, 0x3f803f80u, 0x3f803f80u);
        fence_async_s();
        __syncwarp();
        if (el) { asm volatile("cp.async.bulk.wait_group 0;" ::: "memory"); mbar_arrive(bars + B_GATE3); }
        const uint32_t tag = epoch * 2 + L + 1;
        asm volatile("" : "+r"(lane));
#pragma unroll 1
        for (int b = 0; b < 8; b++) {
          if (!(b & 3)) {
            const int mb = b >> 2;
            mbar_wait(bars + B_ZS + mb * 8, L);
            pause<ZD1>(Q.zero);
            TRC(el && !mb, 2, L * 16 + 8);
            uint4 v;
#pragma unroll 1
            for (int it = 0; it < (1 << 22); it++) {
              v = ll_ld128(Q.ZST + ((rb * 2 + mb) * 8 + (lane >> 2)) * 32 + 4 * j + (lane & 3));
              if (__all_sync(~0u, max(max(v.x, v.y), max(v.z, v.w)) != ~0u)) break;
            }
            const bool o = lane & 16;
            float ss = __uint_as_float(o ? v.y : v.x) + __shfl_xor_sync(~0u, __uint_as_float(o ? v.x : v.y), 16), sq = __uint_as_float(o ? v.w : v.z) + __shfl_xor_sync(~0u, __uint_as_float(o ? v.z : v.w), 16);
            ss += __shfl_xor_sync(~0u, ss, 4); sq += __shfl_xor_sync(~0u, sq, 4); ss += __shfl_xor_sync(~0u, ss, 8); sq += __shfl_xor_sync(~0u, sq, 8);
            const float mean = ss * (1.f / FH), rs = blo(pack2(rsq_fast(fmaxf(fmaf(sq, 1.f / FH, -mean * mean), 0.f) + 4.f * GA * GA * LN_EPS), 0.f));
            if (!(lane & 12)) ll_st64(Q.RT + (mb * 16 + rb) * 64 + 8 * j + 2 * (lane & 3) + (lane >> 4), pack2(rs, rs * (mean - blo(lds32(sb + SM_OFF)))), tag);
            TRC(el && !mb, 2, L * 16 + 10);
            pause<ZD2>(Q.zero);
          }
          uint4 v[4];
#pragma unroll 1
          for (int it = 0; it < (1 << 22); it++) {
            bool ok = true;
#pragma unroll
            for (int u = 0; u < 4; u++) { v[u] = ll_ld128((const uint4*)Q.RT + b * 128 + u * 32 + lane); ok = ok && v[u].y == tag && v[u].w == tag; }
            if (__all_sync(~0u, ok)) break;
          }
#pragma unroll
          for (int u = 0; u < 4; u++) {
            const uint32_t rt = sb + SM_RT + b * 512 + u * 128, ro = (lane >> 3) * 32 + (lane & 3) * 8 + ((lane >> 2) & 1) * 2;
            sts32(rt + 4096 + lane * 4, __byte_perm(v[u].x, v[u].z, 0x7632));
            asm volatile("st.shared.u16 [%0], %1;\nst.shared.u16 [%0 + 4], %2;" ::"r"(rt + ro), "h"((uint16_t)v[u].x), "h"((uint16_t)v[u].z) : "memory");
          }
          __syncwarp();
          if (el && (b & 1)) mbar_arrive(bars + B_RT + (b - 1) * 4);
          TRC(el && b < 2, 2, L * 16 + 11 + b);
        }
        TRC(el, 2, L * 16 + 9);
        mbar_wait(bars + B_EVT + EV_Z1 * 8, L);
        mbar_wait(bars + B_EVT + (EV_N + EV_Z1) * 8, L);
        fence_gpu();
        if (el) mbar_arrive(bars + B_Z1);
      }
    }
  } else {
    int w = wid >> 2, q = wid & 3, rb = bid & 15, j = bid >> 4;
    int g = lane >> 2, t = lane & 3;
#define PHASE asm volatile("" : "+r"(w), "+r"(q), "+r"(rb), "+r"(j))
#define stg (sb + SM_STG + w * 9216)
    const bool tr = (tid & 127) == 0;
    (void)tr;
    Cur c{0, 0};
    const uint32_t ebar = mapa(bars + B_EMPTY, (bid & 1) ^ (lane & 1));
    auto release = [&](uint32_t s) { if (lane < 2) mbar_arrive_cluster(ebar + s * 8); };
    uint32_t ia = 0;
    auto wait_ab = [&]() { mbar_wait_c(bars + B_FULL + c.s * 8, c.ph); mbar_wait_c(bars + B_FULLA + w * 32 + c.s * 8, (ia >> c.s) & 1); ia ^= 1u << c.s; };
    uint32_t lagph = 0;
    auto yield = [&](int left, int lag) { if (w == 1 && left == lag) mbar_wait_c(bars + B_LAG, lagph); };
    auto yield_done = [&]() { if (w == 0 && lane == 0) mbar_arrive(bars + B_LAG); };
    uint32_t rp = 0;
    auto check = [&](auto n, uint32_t dst, const uint8_t* src) {
      const uint32_t a = dst + lane * 32 + (lane >> 2) * 4;
#pragma unroll 1
      for (int it = 0; it < (1 << 16); it++) {
        uint32_t x = lds32(a);
#pragma unroll
        for (int e = 1; e < n.value; e++) x = max(x, lds32(a + e * 1024));
        if (!__any_sync(~0u, x == ~0u)) break;
        fence_async_s();
        __syncwarp();
        expect_tx_p(lane == 0, bars + B_RB + q * 8, n.value * 1024);
        bulk_load_p(lane == 0, dst, src, n.value * 1024, bars + B_RB + q * 8);
        mbar_wait_c(bars + B_RB + q * 8, rp & 1);
        rp++;
      }
    };
    auto signal = [&](int e) { __syncwarp(); if (lane == 0) mbar_arrive(bars + B_EVT + w * EV_N * 8 + e * 8); };
    TRC(tr, w, 0);

    {
      uint8_t* dst = Q.WQ + j * WQ_SL + rb * 3456 + tid * 16;
#pragma unroll
      for (int u = 0; u < 5; u++) {
        stg128_if((u < 4 || rb < 8) && tid < 216, dst + u * (16 * 3456), wv[u].x, wv[u].y, wv[u].z, wv[u].w);
        if (u == 0) TRC(tr, w, 60);
      }
      if (Q.zero == 0) {
        float s[8];
#pragma unroll
        for (int u = 0; u < 5; u++) {
          const uint32_t x[4] = {wv[u].x, wv[u].y, wv[u].z, wv[u].w};
#pragma unroll
          for (int e = 0; e < 4; e++) { s[2 * e] = u ? s[2 * e] + blo(x[e]) : blo(x[e]); s[2 * e + 1] = u ? s[2 * e + 1] + bhi(x[e]) : bhi(x[e]); }
        }
#pragma unroll
        for (int m = 4; m; m >>= 1) {
#pragma unroll
          for (int e = 0; e < m; e++) s[e] = ((tid & m) ? s[e + m] : s[e]) + __shfl_xor_sync(~0u, (tid & m) ? s[e] : s[e + m], m);
        }
        stg32_if(tid < 216, Q.CSP + bid * 216 + tid, __float_as_uint(s[0]));
      }
      __syncwarp();
      if (lane == 0) mbar_arrive(bars + B_IMG);
    }
    reg_alloc<224>();
    auto fetch_wo = [&]() {
#pragma unroll 1
      for (int u = tid; u < 328; u += 256) {
        const int m = min(41 * rb + (u >> 3), 647), k8 = m / 9;
        cp_async16(sb + SM_WOI + u * 16, (const uint8_t*)Q.wo + (8 * k8 + (u & 7)) * (DM * 2) + (72 * j + 8 * (m - k8 * 9)) * 2);
      }
    };
    const uint32_t epoch = ldcg32(Q.flags + (rb * 2 + w) * 32 + FR_EP + j);
    TRC(tr, w, 1);

#pragma unroll 1
    for (int L = 0; L < 2; L++) {
      const int tb = 2 + L * 24;
      asm volatile("" : "+r"(lane), "+r"(g), "+r"(t));
      if (PHM & 1) PHASE;
      (void)tb;
      const uint32_t tag = epoch * 2 + L + 1;
      {
        uint32_t Pk[27][2];
        float rk[2][2], sc[2][2];
        const bool up0 = 2 * t > g, up1 = 2 * t + 1 > g;
        constexpr int HA_[6] = {0, 2, 4, 7, 12, 15}, HC_[6] = {6, 9, 10, 11, 14, 17};
        const bool remote = q == 0 && rb > 0;
        uint4* hp = Q.HALO + ((((rb - (q == 0)) * 2 + w) * 8 + j) * 6) * 32 + lane;
        const uint32_t att = 2 * ST_BYTES + w * 8192 + lane * 16;
        const uint8_t* hs = remote ? (const uint8_t*)hp : smem_raw + att + (q == 3 ? ST_BYTES : q == 2 ? 3072 : 0);
        uint8_t* od = z1_block(rb, (q >> 1) ^ 1, 0) + (9 * j) * 1024 + (4 * (q & 1) + w) * 128 + lane * 4;
        ACLK_INIT;
        {
          float acc[108];
#pragma unroll
          for (int i = 0; i < 108; i++) acc[i] = 0.f;
          float sx[2] = {0.f, 0.f}, sq[2] = {0.f, 0.f};
          uint32_t prev = 0;
#pragma unroll 1
          for (int kb = 0; kb < 7; kb++) {
            wait_ab();
            TRC(tr && kb == 0, w, tb + 0);
            PCLK(kb * 4);
            const uint32_t st = sb + c.s * ST_BYTES, da = dlo(st + w * 8192, 16), db = dlo(st + ST_B, 3456);
            wgmma_fence();
#pragma unroll
            for (int kk = 0; kk < 4; kk++) {
              wgmma_ss_n216(acc, dsc<1024, 1>(da, kk * 32), dsc<128, 0>(db, kk * 6912), 1);
              if (kk == 0) { wgmma_commit(); wgmma_wait<1>(); if (kb > 0) release(prev); }
              if (kk == 3) wgmma_commit();
              if (kk == XK1) {
            if (kb >= KS && kb < KS + 3) {
              mbar_wait_c(bars + B_WT + w * 8, 0);
#pragma unroll
              for (int u = 0; u < 3; u++) {
                const uint2 x = lds64(stg + (2 * q + (lane >> 4)) * 1152 + (lane & 15) * 8 + (kb - KS) * 384 + u * 128);
                sx[0] += blo(x.x) + bhi(x.x); sx[1] += blo(x.y) + bhi(x.y);
                sq[0] = fmaf(blo(x.x), blo(x.x), fmaf(bhi(x.x), bhi(x.x), sq[0])); sq[1] = fmaf(blo(x.y), blo(x.y), fmaf(bhi(x.y), bhi(x.y), sq[1]));
              }
            }
            if (kb == KS + 3) {
              const bool o = lane & 1;
              float v = (o ? sq[0] + sq[1] : sx[0] + sx[1]) + __shfl_xor_sync(~0u, o ? sx[0] + sx[1] : sq[0] + sq[1], 1);
              v += __shfl_xor_sync(~0u, v, 2); v += __shfl_xor_sync(~0u, v, 4); v += __shfl_xor_sync(~0u, v, 8);
              const float m = v * (-1.f / DM), r = rsq_fast(fmaxf(fmaf(__shfl_xor_sync(~0u, v, 1), 1.f / DM, -m * m), 0.f) + LN_EPS);
              ll_st128_if(!(lane & 15), Q.XST + (rb * 2 + w) * 128 + 16 * j + 4 * q + (lane >> 3), m, r, tag);
            }
              }
              if (kk == XK2 && L == 0) {
            if (kb == 0) fetch_wo();
            if (kb == 3) {
              asm volatile("cp.async.wait_all;" ::: "memory");
              fence_async_s();
              __syncwarp();
              if (lane == 0) mbar_arrive(bars + B_WOI);
            }
              }
            }
            prev = c.s; c.next();
          }
          const uint32_t ls = sb + L * (3 * ST_BYTES), cs = ls + SM_CSQ + t * 8;
          float2 cv[27];
          mbar_wait_c(bars + B_XRW + 8, L);
#pragma unroll
          for (int kb = 7; kb < 9; kb++) {
            wait_ab();
            yield(9 - kb, LAG1);
            PCLK(kb * 4);
            const uint32_t st = sb + c.s * ST_BYTES, da = dlo(st + w * 8192, 16), db = dlo(st + ST_B, 3456);
            wgmma_fence();
#pragma unroll
            for (int kk = 0; kk < 4; kk++) {
              wgmma_ss_n216(acc, dsc<1024, 1>(da, kk * 32), dsc<128, 0>(db, kk * 6912), 1);
              if (kk == 0) { wgmma_commit(); wgmma_wait<1>(); release(prev); }
              if (kb == 7 && kk < 3) {
#pragma unroll
                for (int G = 9 * kk; G < 9 * kk + 9; G++) cv[G] = lds64f(cs + G * 32);
                wgmma_fence();
              }
            }
            wgmma_commit();
            prev = c.s; c.next();
          }
          yield_done();
          mbar_wait_c(bars + B_CSQ, L);
          const uint32_t xs = ls + SM_XST + w * 768 + 256 + q * 128;
          const float2 n0 = lds64f(xs + g * 8), n1 = lds64f(xs + g * 8 + 64);
          const float m0 = n0.x, m1 = n1.x;
#pragma unroll
          for (int u = 0; u < 4; u++) {
            rk[u >> 1][u & 1] = __uint_as_float(lds32(xs + t * 16 + ((u & 1 ? up1 : up0) ? -64 : 0) + (u & 1) * 8 + (u >> 1) * 64 + 4));
            sc[u >> 1][u & 1] = rk[u >> 1][u & 1] * ((u >> 1 ? n1.y : n0.y) * (0.23570226039551584f * 1.4426950408889634f));
          }
          PCLK(36);
          wgmma_wait<0>();
          PCLK(37);
          release(prev);
          lagph ^= 1;
          TRC(tr, w, tb + 1);
          ACLK(0);
#pragma unroll
          for (int G = 9; G < 27; G++) Pk[G][1] = pack2(fmaf(m1, cv[G].x, acc[4 * G + 2]), fmaf(m1, cv[G].y, acc[4 * G + 3]));
          if (q < 3) {
#pragma unroll
            for (int i = 0; i < 6; i++) sts128(sb + att + (q >> 1) * ST_BYTES + (q & 1) * 3072 + i * 512, Pk[9 + HA_[i]][1], Pk[10 + HA_[i]][1], tag, Pk[9 + HC_[i]][1]);
          } else if (rb < 15) {
#pragma unroll
            for (int i = 0; i < 6; i++) ll_st128(hp + i * 32, __uint_as_float(Pk[9 + HA_[i]][1]), __uint_as_float(Pk[10 + HA_[i]][1]), tag, __uint_as_float(Pk[9 + HC_[i]][1]));
          }
#pragma unroll
          for (int G = 0; G < 27; G++) {
            Pk[G][0] = pack2(fmaf(m0, cv[G].x, acc[4 * G]), fmaf(m0, cv[G].y, acc[4 * G + 1]));
            if (G < 9) Pk[G][1] = pack2(fmaf(m1, cv[G].x, acc[4 * G + 2]), fmaf(m1, cv[G].y, acc[4 * G + 3]));
          }
        }
        ACLK(1);
        constexpr int GA_[4] = {0, 2, 4, 7}, GB_[4] = {1, 3, 5, 8}, GC_[4] = {2, 4, 6, 6};
        float S1[4][4], S2[4][4];
        uint32_t qa[4][2], qc[4][2];
#pragma unroll
        for (int h = 0; h < 4; h++) {
#pragma unroll
          for (int r = 0; r < 2; r++) {
            qa[h][r] = (h == 0 || h == 3 || t >= h) ? Pk[GA_[h]][r] : 0u;
            qc[h][r] = (h == 3 ? t == 3 : t <= h) ? Pk[GC_[h]][r] : 0u;
          }
#pragma unroll
          for (int i = 0; i < 4; i++) S1[h][i] = S2[h][i] = 0.f;
          mma16(S1[h], qa[h][0], qa[h][1], Pk[GB_[h]][0], Pk[GB_[h]][1], Pk[9 + GA_[h]][0], Pk[9 + GB_[h]][0]);
          mma16(S2[h], qa[h][0], qa[h][1], Pk[GB_[h]][0], Pk[GB_[h]][1], Pk[9 + GA_[h]][1], Pk[9 + GB_[h]][1]);
        }
#pragma unroll
        for (int h = 0; h < 4; h++) {
          mma8(S1[h], qc[h][0], qc[h][1], Pk[9 + GC_[h]][0]);
          mma8(S2[h], qc[h][0], qc[h][1], Pk[9 + GC_[h]][1]);
        }
        uint32_t V1[9], V2[9];
#pragma unroll
        for (int i = 0; i < 9; i++) { V1[i] = movm(Pk[18 + i][0]); V2[i] = movm(Pk[18 + i][1]); }
        uint4 hv[6];
#pragma unroll
        for (int i = 0; i < 6; i++) hv[i] = ll_ld128g(hs + i * 512);
        const uint32_t mup = (up0 ? 0xffffu : 0u) | (up1 ? 0xffff0000u : 0u);
        auto finish = [&](const float (&x0)[4], const float (&x1)[4], const uint32_t (&Vb)[9], uint32_t ma, int hi) {
          uint32_t p[4], n[4];
          float rs[4];
#pragma unroll
          for (int h = 0; h < 4; h++) {
            const float m = qmax(fmaxf(x0[h], x1[h])), e0 = ex2(x0[h] - m), e1 = ex2(x1[h] - m);
            n[h] = pack2(e0, e1);
            p[h] = pack2(e0 * rk[hi][0], e1 * rk[hi][1]);
          }
#pragma unroll
          for (int h = 0; h < 4; h += 2) {
            float D[4] = {0.f, 0.f, 0.f, 0.f};
            mma8(D, n[h], n[h + 1], 0x3f803f80u);
            rs[h] = rcp_fast(D[0]); rs[h + 1] = rcp_fast(D[2]);
          }
#pragma unroll
          for (int i = 0; i < 9; i++) {
            const int h = i < 4 ? 0 : i == 4 ? 1 : 2;
            const bool nx = (i == 2 || i == 4 || i == 6) ? 2 * t >= i : i == 3 || i > 6;
            float O[4] = {0.f, 0.f, 0.f, 0.f};
            mma16(O, p[h] & ma, p[h + 1] & ma, p[h] & ~ma, p[h + 1] & ~ma, V1[i], Vb[i]);
            const float r = nx ? rs[h + 1] : rs[h];
            stg32(od + i * 1024 + hi * 256, pack2((nx ? O[2] : O[0]) * r, (nx ? O[3] : O[1]) * r));
          }
        };
        {
          float x0[4], x1[4];
#pragma unroll
          for (int h = 0; h < 4; h++) { x0[h] = (up0 ? S1[h][2] : S2[h][2]) * sc[1][0]; x1[h] = (up1 ? S1[h][3] : S2[h][3]) * sc[1][1]; }
          finish(x0, x1, V2, mup, 1);
        }
        ACLK(2);
        bar_sync(1 + w, 128);
#pragma unroll 1
        for (int it = 0; it < (1 << 20); it++) {
          if (remote) {
            bool ok = true;
#pragma unroll
            for (int i = 0; i < 6; i++) ok = ok && hv[i].z == tag;
            if (__all_sync(~0u, ok)) break;
          }
#pragma unroll
          for (int i = 0; i < 6; i++) hv[i] = ll_ld128g(hs + i * 512);
          if (!remote) break;
        }
        uint32_t H[18];
#pragma unroll
        for (int i = 0; i < 6; i++) { H[HA_[i]] = hv[i].x; H[HA_[i] + 1] = hv[i].y; H[HC_[i]] = hv[i].w; }
        float S0[4][4];
#pragma unroll
        for (int h = 0; h < 4; h++) {
#pragma unroll
          for (int i = 0; i < 4; i++) S0[h][i] = 0.f;
          mma16(S0[h], qa[h][0], qa[h][1], Pk[GB_[h]][0], Pk[GB_[h]][1], H[GA_[h]], H[GB_[h]]);
        }
#pragma unroll
        for (int h = 0; h < 4; h++) mma8(S0[h], qc[h][0], qc[h][1], H[GC_[h]]);
        uint32_t V0[9];
#pragma unroll
        for (int i = 0; i < 9; i++) V0[i] = movm(H[9 + i]);
        ACLK(3);
        {
          const bool nohalo = (rb | q) == 0;
          const float b0 = up0 && nohalo ? -INFINITY : 0.f, b1 = up1 && nohalo ? -INFINITY : 0.f;
          float x0[4], x1[4];
#pragma unroll
          for (int h = 0; h < 4; h++) { x0[h] = fmaf(up0 ? S0[h][0] : S1[h][0], sc[0][0], b0); x1[h] = fmaf(up1 ? S0[h][1] : S1[h][1], sc[0][1], b1); }
          finish(x0, x1, V0, ~mup, 0);
        }
        ACLK(4);
        __syncwarp();
        if (lane == 0) mbar_arrive(bars + B_EVT + (EV_N * (q < 2) + EV_O) * 8);
        ACLK_OUT;
        TRC(tr, w, tb + 2);
      }
      if (c.s) { c.s = 0; c.ph ^= 1; }
      if (PHM & 2) PHASE;
      {
        float acc[36];
        const int hw = rb * 2 + w;
        const uint32_t xt = stg + (8 * q + g) * 144 + t * 4;
        uint32_t xm = sb + SM_STG + 9216 + (8 * q + (lane & 7)) * 144 + (lane & 8) * 576 + (lane & 16);
        uint8_t* xn = xn_block(hw) + j * 9216 + q * 256 + lane * 4;
        uint32_t* sp = (uint32_t*)(Q.ST1 + (hw * 8 + j) * 32 + 8 * q) + lane;
        const uint4* sg = Q.ST1 + (hw * 8 + t) * 32 + 8 * q + g;
        asm volatile("" : "+r"(xm), "+l"(xn), "+l"(sp), "+l"(sg));
        mbar_wait_c(bars + B_RES + w * 8, L);
        TRC(tr, w, tb + 21);
#pragma unroll
        for (int i = 0; i < 18; i++) { const uint32_t x = lds32(xt + (i >> 1) * 16 + (i & 1) * 4608); acc[2 * i] = blo(x); acc[2 * i + 1] = bhi(x); asm volatile("" : "+f"(acc[2 * i]), "+f"(acc[2 * i + 1])); }
        mbar_wait_c(bars + B_WF, L);
        const uint32_t db = dlo(sb, 1152), of = bars + (w ? B_OF + 40 : B_AV + 96);
        uint32_t da[5];
#pragma unroll
        for (int e = 0; e < 5; e++) da[e] = __shfl_sync(~0u, dlo(sb + o_place(w, e), 1024), 0);
        if (w) {
#pragma unroll 1
          for (int kb = q ^ 2; kb < 9; kb += 4) {
            const uint32_t e = (kb + 1) >> 1;
            mbar_wait_c(bars + B_OF + e * 8, L);
            check(Int<8>{}, sb + o_place(0, e) + (kb && !(kb & 1)) * 8192, z1_block(rb, 0, 0) + kb * 8192);
            if (lane <= !kb) mbar_arrive(bars + B_AV + (12 + e) * 8);
          }
          bar_sync(7, 256);
        }
        mbar_wait_c(of, L & w);
        TRC(tr, w, tb + 3);
        wgmma_fence();
#pragma unroll
        for (int kk = 0; kk < 4; kk++) wgmma_ss_n72(acc, dsc<128, 0>(da[0], kk * 2048), dsc<128, 0>(db, kk * 2304), 1);
        wgmma_commit();
#pragma unroll 1
        for (int h = 0; h < 2; h++) {
#pragma unroll
          for (int u = 0; u < 4; u++) {
            if (!(u & 1)) { mbar_wait_c(of + 8 + h * 16 + u * 4, 1 + 2 * h + (u >> 1) < SPL ? L & w : L); wgmma_fence(); }
            if (u == 3 && h && !w) bar_arrive(7, 256);
#pragma unroll
            for (int kk = 0; kk < 4; kk++) wgmma_ss_n72(acc, dsc<128, 0>(da[1 + (u >> 1)], (u & 1) * 8192 + kk * 2048), dsc<128, 0>(db + h * 2304, (1 + u) * 9216 + kk * 2304), 1);
            if (u != 2) wgmma_commit();
            if (u == 0) { wgmma_wait<1>(); if (lane + w == 0 && h) mbar_arrive(bars + B_X3); }
          }
          da[1] = da[3]; da[2] = da[4];
        }
        RCLK_INIT;
        wgmma_wait<0>();
        RCLK(0);
        if (lane < 2) mbar_arrive_cluster(ebar + B_XD - B_EMPTY + w * 8);
        TRC(tr && P5TRACE != 5, w, tb + 4);
        {
          float s0 = 0.f, s1 = 0.f, q0 = 0.f, q1 = 0.f;
#pragma unroll
          for (int i = 0; i < 36; i++) {
            if (i & 2) { s1 += acc[i]; q1 = fmaf(acc[i], acc[i], q1); } else { s0 += acc[i]; q0 = fmaf(acc[i], acc[i], q0); }
          }
          const bool o1 = t & 1, o2 = t & 2;
          const float ss = (o1 ? s1 : s0) + __shfl_xor_sync(~0u, o1 ? s0 : s1, 1), sq = (o1 ? q1 : q0) + __shfl_xor_sync(~0u, o1 ? q0 : q1, 1);
          const float v = (o2 ? sq : ss) + __shfl_xor_sync(~0u, o2 ? ss : sq, 2);
          asm volatile("st.relaxed.gpu.global.u32 [%0], %1;" ::"l"(sp), "r"(__float_as_uint(v)) : "memory");
        }
        RCLK(1);
        RCLK(2);
        pause<PDEL>(Q.zero);
        uint4 pa, pb;
        auto there = [&](const uint4& a, const uint4& b) { return __all_sync(~0u, max(max(max(a.x, a.y), max(a.z, a.w)), max(max(b.x, b.y), max(b.z, b.w))) != ~0u); };
#pragma unroll 1
        for (int it = 0; it < (1 << 20); it++) {
          pa = ll_ld128(sg); pb = ll_ld128(sg + 128);
          if (there(pa, pb)) break;
        }
        RCLK(3);
        float mean0 = qsum(__uint_as_float(pa.x) + __uint_as_float(pb.x)) * (-1.f / DM), mean1 = qsum(__uint_as_float(pa.y) + __uint_as_float(pb.y)) * (-1.f / DM);
        const float rs0 = GA * rsq_fast(fmaxf(fmaf(qsum(__uint_as_float(pa.z) + __uint_as_float(pb.z)), 1.f / DM, -mean0 * mean0), 0.f) + LN_EPS);
        const float rs1 = GA * rsq_fast(fmaxf(fmaf(qsum(__uint_as_float(pa.w) + __uint_as_float(pb.w)), 1.f / DM, -mean1 * mean1), 0.f) + LN_EPS);
        mean0 *= rs0; mean1 *= rs1;
#pragma unroll
        for (int i = 0; i < 18; i++) {
          const float a = (i & 1) ? rs1 : rs0, b = (i & 1) ? mean1 : mean0;
          stg32(xn + (i >> 1) * 1024 + (i & 1) * 128, pack2(fmaf(acc[2 * i], a, b), fmaf(acc[2 * i + 1], a, b)));
        }
        signal(EV_X1);
        RCLK(4);
        if (w) {
#pragma unroll 1
          for (int u = q; u < 24; u += 4) {
            const uint32_t mb = u < 2 * SPL ? u >= SPL : u & 1, k = u < 2 * SPL ? u - mb * SPL : u >> 1;
            mbar_wait_c(bars + B_AF3 + mb * 96 + k * 8, L);
            SCLK3(u);
            check(Int<6>{}, sb + k * 12288 + mb * 6144, xn_block(rb * 2 + mb) + k * 6144);
            SCLK3(24 + u);
            if (lane <= (u < 2 * SPL)) mbar_arrive(bars + B_AV + (u < SPL ? 12 + k : k) * 8);
          }
          TRVI(lane == 0 && P5TRACE != 5, 5, 56 + L * 4 + q, rp);
          mbar_wait_c(bars + B_S5, L);
        }
#pragma unroll
        for (int u = 0; u < 4; u++)
          stsm4(xm + u * 32, pack2(acc[8 * u], acc[8 * u + 1]), pack2(acc[8 * u + 2], acc[8 * u + 3]), pack2(acc[8 * u + 4], acc[8 * u + 5]), pack2(acc[8 * u + 6], acc[8 * u + 7]));
        asm volatile("stmatrix.sync.aligned.m8n8.x2.shared.b16 [%0], {%1,%2};" ::"r"(xm + 128), "r"(pack2(acc[32], acc[33])), "r"(pack2(acc[34], acc[35])) : "memory");
        fence_async_s();
        signal(EV_XS);
        RCLK(5);
        TRC(tr, w, tb + 5);
        RCLK(6);
        RCLK_OUT;
      }
      if (PHM & 4) PHASE;
      {
      float acc[160];
#pragma unroll
      for (int i = 0; i < 160; i++) acc[i] = 0.f;
      float s[2] = {0.f, 0.f}, qq[2] = {0.f, 0.f}, zo = 0.f;
      const uint32_t zp = sb + SM_ZP3 + (tid & 127) * 4;
      auto zstat = [&](int mb, bool on) {
        const bool o1 = t & 1, o2 = t & 2;
        const float ss = ((o1 ? s[1] : s[0]) + __shfl_xor_sync(~0u, o1 ? s[0] : s[1], 1)) * 0x1p60f, sq = (o1 ? qq[1] : qq[0]) + __shfl_xor_sync(~0u, o1 ? qq[0] : qq[1], 1);
        const uint32_t v = __float_as_uint((o2 ? sq : ss) + zo + __shfl_xor_sync(~0u, o2 ? ss : sq, 2));
        asm volatile("{\n.reg .pred p, q, r;\nsetp.eq.u32 p, %4, 1;\nsetp.eq.u32 q, %4, 2;\nsetp.eq.and.u32 r, %5, 0, q;\n@p st.shared.u32 [%0], %2;\n@p bar.arrive 13, 256;\n"
                     "@q st.relaxed.gpu.global.u32 [%1], %2;\n@r mbarrier.arrive.shared::cta.b64 _, [%3];\n}" ::"r"(zp + mb * 512), "l"((uint32_t*)(Q.ZST + ((rb * 2 + mb) * 8 + j) * 32) + (tid & 127)),
                     "r"(v), "r"(bars + B_ZS + mb * 8), "r"(on ? 1 + w : 0), "r"(lane) : "memory");
        s[0] = s[1] = qq[0] = qq[1] = 0.f;
      };
      const uint32_t ebar3 = ebar + (B_E3 - B_EMPTY);
#pragma unroll 1
      for (int half = 0; half < 2; half++) {
        const bool big = half != w;
        auto rel3 = [&](int p) { if (lane < 2) mbar_arrive_cluster(ebar3 + p * 8); };
        auto pass = [&](auto nk) {
          constexpr int NK = nk.value;
          uint32_t d0 = dlo(sb, 1024), ph = half & ~w, af = bars + B_AV;
          const uint32_t db = dlo(sb + SM_B3, NK == 3 ? 6144 : 2048);
          const bool lead = NK == 3 && !half;
          if (lead) {
#pragma unroll
            for (int u = 0; u < 2 * SPL; u++) {
              const int mb = u / SPL, p = u % SPL;
              if (!mb) mbar_wait_c(bars + B_F3 + p * 8, 0);
              mbar_wait_c(af + (mb ? p : 12 + p) * 8, mb || p > 4 ? L : 1);
              TRC(tr && u == 0, w, tb + 6);
              SCLK2(u);
              if (p == 0) SCLK(mb * 4);
              wgmma_fence();
#pragma unroll
              for (int kk = 0; kk < 3; kk++) {
                wgmma_ss_n128(acc + mb * 80, dsc<128, 0>(d0, p * 12288 + kk * 2048 + mb * 6144), dsc<1024, 1>(db, p * 12288 + kk * 2048), p + kk > 0);
                if (kk == 0 && u > SPL) { wgmma_commit(); wgmma_wait<1>(); rel3(p - 1); }
              }
              wgmma_commit();
            }
          }
#pragma unroll 1
          for (int it = 0; it < 6 / NK; it++) {
#pragma unroll
            for (int p = 0; p < 6; p++) {
              if (p < SPL && lead && it == 0) continue;
              if (NK == 3) mbar_wait_c(af + p * 8, L);
              if (p == 0 && it == 0) bar_sync(6 + w, 256);
              mbar_wait_c(bars + B_F3 + p * 8, ph);
              TRC(tr && p == 0 && it == 0, w, tb + 6 + half * 4);
              if (lead) SCLK2(12 + it * 6 + p);
              if (NK == 2 ? !(p & 1) : p % 3 == 0) SCLK(half * 11 + (NK == 2 ? it * 3 + p / 2 : it * 2 + p / 3));
              wgmma_fence();
#pragma unroll
              for (int u = 0; u < 2 * NK; u++) {
                const int kk = u >> 1, mb = u & 1, e = p * NK + kk;
                const uint64_t da = dsc<128, 0>(d0, (e / 3) * 12288 + (e % 3) * 2048 + mb * 6144);
                if (NK == 3) wgmma_ss_n128(acc + mb * 80, da, dsc<1024, 1>(db, p * 12288 + kk * 2048), e > 0 || it > 0);
                else wgmma_ss_n160(acc + mb * 80, da, dsc<1024, 1>(db, p * 12288 + kk * 6144), e > 0 || it > 0);
                if (u == 0) { wgmma_commit(); wgmma_wait<1>(); if (p > 0 || it > 0) rel3((p + 5) % 6); }
                if (p * 8 + u == (NK == 2 ? HO3 : HO4) && it == 6 / NK - 1) bar_arrive(7 - w, 256);
              }
              wgmma_commit();
            }
            d0 += NK * 1536; af += 48;
            ph ^= 1;
          }
        };
        if (big) pass(Int<2>{}); else pass(Int<3>{});
        if (w) { bar_sync(13, 256); zo = __uint_as_float(lds32(zp + half * 512)); }
        if (half) zstat(1, true);
        const uint32_t off2 = lds32(sb + SM_OFF);
        const int go = (j & 1) ? (big ? 0 : 20) : (big ? 16 : 0);
        const float* gbp = (const float*)(smem_raw + SM_OFF + 8);
        asm volatile("" : "+l"(gbp));
        uint8_t* zd = half ? z1_block(rb, 0, j) + go * 1024 + (q & 1) * 2048 + 1024 + (q >> 1) * 512 + lane * 16 : z2_block(rb, j) + q * 9216 + go * 128 + ((g & 3) * 2 + (g >> 2)) * 16 + t * 4;
        wgmma_wait<0>();
        SCLK(half * 11 + 9);
        rel3(5);
        TRC(tr, w, tb + 7 + half * 4);
        auto gelu = [&](auto z2) {
          constexpr int NC = z2.value ? NC2 : NC1;
          float gate[NC], gb = GB, gn = GB;
          uint32_t qa[2][3] = {{0, 0, 0}, {0, 0, 0}};
#pragma unroll
          for (int e = 0; e < NC; e++) gate[e] = GB;
#pragma unroll
          for (int G = 0; G < 20; G++) {
            if (G == 16 && !big) break;
            if (G % (z2.value ? LD2 : LD1) == 0) { gb = gn; if (G < 20 - (z2.value ? LD2 : LD1)) asm volatile("ld.f32 %0, [%1];" : "=f"(gn) : "l"(gbp) : "memory"); }
#pragma unroll
            for (int r = 0; r < 2; r++) {
              float z[2];
              float& gt = gate[(G * 2 + r) % NC];
#pragma unroll
              for (int e = 0; e < 2; e++) {
                const float v = acc[4 * G + 2 * r + e];
                z[e] = fmaf(v, tanh_fast(v * fmaf(v, v, gt)), v);
                if (z2.value) { s[r] = fmaf(z[e], 0x1p-60f, s[r]); qq[r] = fmaf(z[e], z[e], qq[r]); }
              }
              const uint32_t pk = pack2(z[0], z[1]);
              if (z2.value) {
                stg32(zd + G * 128 + r * 4608, hsub2(pk, off2));
                gt = fmaf(qq[r], s[r], gb);
              } else {
                gt = fmaf(__uint_as_float(pk), 0x1p-60f, gb);
                if ((G & 3) == 3) stg128(zd + (G >> 2) * 4096 + r * (8 * ZB), qa[r][0], qa[r][1], qa[r][2], pk);
                else qa[r][G & 3] = pk;
              }
            }
          }
        };
#pragma unroll 1
        for (int mb = 0;; mb++) {
          if (half) gelu(Int<0>{}); else gelu(Int<1>{});
          if (mb) break;
          zstat(0, !half);
#pragma unroll
          for (int i = 0; i < 80; i++) acc[i] = acc[80 + i];
          zd += half ? -1024 : (int)(128 * ZB);
        }
        mbar_wait_c(bars + B_GATE3, L);
        signal(half ? EV_Z1 : EV_ZN);
        SCLK(half * 11 + 10);
        TRC(tr, w, tb + 8 + half * 4);
      }
      }
      if (PHM & 8) PHASE;
      const uint32_t aoff = (w * 64 + q * 16 + (lane & 15)) * 128 + (((lane >> 4) ^ (lane & 7)) << 4);
      uint32_t hA[18][4];
      {
        float acc[144];
        {
          const uint32_t c16 = lds32(sb + SM_OFF + 12), a[4] = {c16, c16, c16, c16};
          wgmma_fence();
          wgmma_rs_n144(acc, a, dsc<0, 0>(dlo(sb + SM_CV + 512, 0), 0), 0);
          wgmma_rs_n144(acc + 72, a, dsc<0, 0>(dlo(sb + SM_CV + 512, 0), 128), 0);
          wgmma_commit();
        }
        uint32_t prev = 0;
        auto stage = [&](int kb, bool odd) {
          mbar_wait_c(bars + B_FULL + c.s * 8, c.ph);
          TRC(tr && kb == 0, w, tb + 13);
          SCLK(22 + kb);
          const uint32_t st = sb + c.s * ST_BYTES, db = dlo(st + ST_B, 4608), rt = sb + SM_RT + kb * 128 + t * 8;
          uint32_t a[4][4];
#pragma unroll
          for (int kk = 0; kk < 4; kk++) {
            uint32_t r[4];
            ldsm4(r, st + (aoff ^ (kk << 5)));
            const uint2 sc = lds64(rt + kk * 32);
            a[kk][0] = hmul2(__byte_perm(r[0], r[2], 0x5410), sc.x); a[kk][2] = hmul2(__byte_perm(r[0], r[2], 0x7632), sc.y);
            a[kk][1] = hmul2(__byte_perm(r[1], r[3], 0x5410), sc.x); a[kk][3] = hmul2(__byte_perm(r[1], r[3], 0x7632), sc.y);
          }
          if (!odd && kb + w == 0) bar_sync(6, 256);
          wgmma_fence();
#pragma unroll
          for (int i = 0; i < 8; i++) {
            const int kk = i & 3, hf = i >> 2;
            wgmma_rs_n144(acc + hf * 72, a[kk], dsc<128, 0>(db, kk * 9216 + hf * 2304), 1);
            if (i == 0) { wgmma_commit(); wgmma_wait<1>(); if (kb) release(prev); }
            if (i == 3) wgmma_commit();
          }
          wgmma_commit();
          prev = c.s; c.next();
        };
#pragma unroll 1
        for (int kb = 0; kb < 32; kb += 2) {
          if (!(kb & 7)) mbar_wait_c(bars + B_RT + kb, L);
          stage(kb, false);
          stage(kb + 1, true);
        }
        mbar_wait_c(bars + B_CV + w * 8, L);
        const float gk = 0.5f / GA;
        const float c1 = __uint_as_float(lds32(sb + SM_OFF + 4));
        const float gb0 = -gk * (c1 + __uint_as_float(lds32(sb + SM_CV + w * 256 + (16 * q + g) * 4))), gb1 = -gk * (c1 + __uint_as_float(lds32(sb + SM_CV + w * 256 + (16 * q + g + 8) * 4)));
        if (w == 1) { mbar_wait_c(bars + B_FULL + c.s * 8, c.ph); release(c.s); c.next(); }
        mbar_wait_c(bars + B_FULL + c.s * 8, c.ph);
        const uint32_t zs = sb + c.s * ST_BYTES + ST_B + (tid & 127) * 16;
        uint4 zl, zh;
#pragma unroll
        for (int u = 0; u < 18; u++) {
          if (u == 0) wgmma_wait<1>();
          if (u == 9) {
            wgmma_wait<0>();
            release(prev);
            if (L == 0) signal(EV_PT);
            TRC(tr, w, tb + 14);
            SCLK(54);
          }
          if (!(u & 1)) { zl = lds128(zs + u * 2048); zh = lds128(zs + u * 2048 + 2048); }
          const uint4 z = (u & 1) ? make_uint4(zl.z, zh.z, zl.w, zh.w) : make_uint4(zl.x, zh.x, zl.y, zh.y);
          hA[u][0] = hmul2(z.x, pack2(fmaf(acc[8 * u], gk, gb0), fmaf(acc[8 * u + 1], gk, gb0)));
          hA[u][1] = hmul2(z.y, pack2(fmaf(acc[8 * u + 2], gk, gb1), fmaf(acc[8 * u + 3], gk, gb1)));
          hA[u][2] = hmul2(z.z, pack2(fmaf(acc[8 * u + 4], gk, gb0), fmaf(acc[8 * u + 5], gk, gb0)));
          hA[u][3] = hmul2(z.w, pack2(fmaf(acc[8 * u + 6], gk, gb1), fmaf(acc[8 * u + 7], gk, gb1)));
        }
        __syncwarp();
        release(c.s);
        c.next();
        if (w == 0) { mbar_wait_c(bars + B_FULL + c.s * 8, c.ph); release(c.s); c.next(); }
        TRC(tr, w, tb + 15);
      }
      {
        CLK_INIT;
        if (w == 1) bar_arrive(6, 256);
        uint4 v[4];
#pragma unroll
        for (int u = 0; u < 4; u++) v[u] = make_uint4(0u, 0u, 0u, 0u);
        uint32_t rl = sb + SM_STG + w * 8192 + q * 2048 + (lane >> 3) * 128 + (((lane & 7) ^ (lane >> 3)) << 4);
        uint8_t* rd = Q.out + (128 * rb + 32 * q + 2 * (lane >> 3) + w) * (DM * 2) + j * 128 + (lane & 7) * 16;
        asm volatile("" : "+r"(rl), "+l"(rd));
        auto send = [&](int u0, int u1) {
#pragma unroll
          for (int u = u0; u < u1; u++)
            asm volatile("red.relaxed.gpu.global.add.noftz.v4.bf16x2 [%0], {%1,%2,%3,%4};" ::"l"(rd + u * (8 * DM * 2)), "r"(v[u].x), "r"(v[u].y), "r"(v[u].z), "r"(v[u].w) : "memory");
        };
#pragma unroll 1
        for (int p = 0; p < 9; p++) {
          float acc[32];
          CLK(0);
          mbar_wait_c(bars + B_FULL + c.s * 8, c.ph);
          const uint32_t db = dlo(sb + c.s * ST_BYTES + ST_B, 0);
          CLK(1);
          bar_sync(6 + w, 256);
          CLK(2);
          wgmma_fence();
#pragma unroll
          for (int kk = 0; kk < 18; kk++) {
            wgmma_rs_n64(acc, hA[kk], dsc<1024, 1>(db, kk * 2048), kk != 0);
            if (kk == PPK && (w == 0 || p < 8)) bar_arrive(7 - w, 256);
          }
          wgmma_commit();
          CLK(3);
          if (p > 0) { send(NOW, 4); rd += p + j == 9 ? -1024 : 128; }
          CLK(5);
          wgmma_wait<0>();
          CLK(4);
          if (L == 0 || p < 5) release(c.s);
          c.next();
          TRC(tr && p == 8, w, tb + 16);
#pragma unroll
          for (int u = 0; u < 4; u++)
            stsm4(sb + SM_STG + (aoff ^ (u << 5)), pack2(acc[8 * u], acc[8 * u + 1]), pack2(acc[8 * u + 2], acc[8 * u + 3]), pack2(acc[8 * u + 4], acc[8 * u + 5]), pack2(acc[8 * u + 6], acc[8 * u + 7]));
          __syncwarp();
#pragma unroll
          for (int u = 0; u < 4; u++) v[u] = lds128(rl + u * 512 ^ (u & 1) << 6);
          send(0, NOW);
        }
        send(NOW, 4);
        TRC(tr, w, tb + 17);
        if (L == 0) signal(EV_PT);
        CLK_OUT;
        TRC(tr, w, tb + 18);
      }
    }
    if ((tid & 127) == 0) Q.flags[(rb * 2 + w) * 32 + FR_EP + j] = epoch + 1;
    if (tid == 0) Q.flags[FJ + j * 32 + FJ_EP + rb] = epoch + 1;
  }
}

typedef CUresult (*EncodeFn)(CUtensorMap*, CUtensorMapDataType, cuuint32_t, void*, const cuuint64_t*, const cuuint64_t*, const cuuint32_t*,
                             const cuuint32_t*, CUtensorMapInterleave, CUtensorMapSwizzle, CUtensorMapL2promotion, CUtensorMapFloatOOBfill);

static void make_map(EncodeFn fn, CUtensorMap* m, const void* ptr, int rank, uint64_t d0, uint64_t d1, uint64_t d2, uint64_t s1, uint64_t s2,
                     uint32_t b0, uint32_t b1, uint32_t b2, CUtensorMapSwizzle swz) {
  cuuint64_t dims[3] = {d0, d1, d2}, strides[2] = {s1, s2};
  cuuint32_t box[3] = {b0, b1, b2}, es[3] = {1, 1, 1};
  fn(m, CU_TENSOR_MAP_DATA_TYPE_BFLOAT16, rank, const_cast<void*>(ptr), dims, strides, box, es, CU_TENSOR_MAP_INTERLEAVE_NONE, swz,
     CU_TENSOR_MAP_L2_PROMOTION_L2_128B, CU_TENSOR_MAP_FLOAT_OOB_FILL_NONE);
}

}

extern "C" void kernel_launch(void* const* d_in, const int* in_sizes, int n_in, void* d_out, int out_size) {
  using namespace mk;
  (void)in_sizes; (void)n_in; (void)out_size;
  static EncodeFn fn = nullptr;
  static Scratch* sc = nullptr;
  if (!fn) {
    cudaDriverEntryPointQueryResult qr;
    cudaGetDriverEntryPoint("cuTensorMapEncodeTiled", (void**)&fn, cudaEnableDefault, &qr);
    cudaGetSymbolAddress((void**)&sc, g_scratch);
    cudaFuncSetAttribute(mega_kernel, cudaFuncAttributeMaxDynamicSharedMemorySize, SM_TOTAL);
  }
  Params p;
  Ptrs a;
  a.x = (const uint8_t*)d_in[0];
  a.wqkv = (const __nv_bfloat16*)d_in[1];
  a.wo = (const __nv_bfloat16*)d_in[2];
  a.w_in = (const __nv_bfloat16*)d_in[4];
  a.w_sp = (const __nv_bfloat16*)d_in[5];
  a.b_sp = (const __nv_bfloat16*)d_in[6];
  a.out = (uint8_t*)d_out;
  a.zero = 0;
  a.WQ = sc->WQ; a.flags = sc->flags; a.CSP = sc->CSP; a.XST = sc->XST; a.HALO = sc->HALO; a.ST1 = sc->ST1; a.ZST = sc->ZST; a.RT = sc->RT; a.Z = sc->Z; a.WO = sc->WO;
  make_map(fn, &p.wsp, a.w_sp, 3, 2048, 1024, 2, 8192, 4096, 64, 64, 2, CU_TENSOR_MAP_SWIZZLE_128B);
  for (int i = 0; i < 2; i++) {
    make_map(fn, &p.act[i], i ? a.out : a.x, 3, DM, 1024, 2, 2304, 1152, 64, 64, 1, CU_TENSOR_MAP_SWIZZLE_128B);
    make_map(fn, &p.row[i], i ? a.out : a.x, 3, 192, 6, 1024, 384, 2304, 192, 3, 8, CU_TENSOR_MAP_SWIZZLE_NONE);
    make_map(fn, &p.res[i], i ? a.out : a.x, 3, DM, 1024, 2, 2304, 1152, 72, 32, 2, CU_TENSOR_MAP_SWIZZLE_NONE);
  }
  for (int i = 0; i < 2; i++) make_map(fn, &p.winb[i], a.w_in + 32 * i, 3, 64, 576, 72 - i, 9216, 128, 64, 16, 3, CU_TENSOR_MAP_SWIZZLE_128B);
  make_map(fn, &p.wins, a.w_in, 3, 64, 576, 72, 9216, 128, 64, 48, 1, CU_TENSOR_MAP_SWIZZLE_128B);
  make_map(fn, &p.wout, d_in[7], 2, 576, 2304, 1, 1152, 0, 64, 144, 1, CU_TENSOR_MAP_SWIZZLE_128B);
  mega_kernel<<<NGRID, 384, SM_TOTAL, cudaStreamPerThread>>>(a, p);
}
```

```cpp
#include <cuda_runtime.h>
#include <cuda.h>
#include <cuda_bf16.h>
#include <stdint.h>

#define MK_TRACE 0
#define MK_DBG 0
#define P5TRACE 0
#define LAG1 1
#define C0S 32.f
#define OFM 0x10u
#define NC2 2
#define NC1 8
#define PDEL 8
#define LD1 4
#define LD2 2
#define ZD1 8
#define ZD2 20
#define WPF 1
#define YPACE 2
#define SPL 3
#define XP0 10
#define EFM 0x23333022
#define EF(i) ((((EFM >> (4 * (i))) & 3) == 3) || (((EFM >> (4 * (i))) >> L) & 1))
#define AEP 2
#define PZI 4
#define KS 1
#define RFI 3
#define XK1 1
#define XK2 2
#define SDEL 10
#define FD3 14
#define FD4 0
#define FD5 0
#define PHM 15
#define NOW 2
#define WTI 12
#define APACE 7
#define HO3 41
#define HO4 41
#define PPK 17

namespace mk {

constexpr int SEQ = 2048, DM = 576, FH = 2304;
constexpr int NCTA = 128;
constexpr int NGRID = 132;
constexpr uint32_t ZB = 36864;
constexpr uint32_t WQ_SL = 72 * 3456;
constexpr uint32_t WO_SL = 72 * 1152;
constexpr float LN_EPS = 1e-5f;
constexpr float GA = 0.3292034911525734f, GB = 2.423681954311584f;

constexpr uint32_t ST_BYTES = 53248, ST_B = 16384, NST = 4;
constexpr uint32_t SM_STG = NST * ST_BYTES;
constexpr uint32_t SM_BAR = SM_STG + 2 * 9216, B_OFF = 896;
constexpr uint32_t SM_OFF = SM_BAR + B_OFF;
constexpr uint32_t SM_TOTAL = SM_BAR + 1024;
constexpr uint32_t SM_RT = SM_STG + 9216, SM_CV = SM_STG + 17408, SM_WT = SM_STG;
constexpr uint32_t SM_WOI = 44032, SM_CSQ = 49280, SM_XST = 50176;
enum { EV_PT = 0, EV_O = 1, EV_X1 = 2, EV_ZN = 3, EV_Z1 = 4, EV_XS = 5, EV_N = 6 };
constexpr uint32_t B_FULL = 0, B_FULLA = 32, B_RES = 96, B_WT = 112, B_GATE3 = 128, B_Z1 = 136, B_ZOK = 144, B_CV = 152, B_XRW = 168, B_F3 = 184, B_WF = 232, B_OF = 240,
                   B_RT = 320, B_AF3 = 352, B_RB = 544,
                   B_AD = 576, B_S5 = 608, B_AV = 616, B_CSQ = 760,
                   B_LAG = 768, B_X3 = 776, B_ZS = 784, B_EVT = 800,
                   B_IMG = 912, B_WOI = 920, B_E3 = 928, B_XD = 976,
                   B_EMPTY = 992;
constexpr uint32_t SM_B3 = 9 * 16384, SM_ZP3 = SM_STG + 8192;

enum { FR_X2 = 0, FR_O = 1, FR_XR = 5, FR_OL = 7, FR_PZ = 9, FR_EP = 16, FJ = 32 * 32, FJ_WQ = 0, FJ_WO = 1, FJ_ZN = 3, FJ_P4 = 5, FJ_EP = 16, F_N = FJ + 8 * 32 };

struct Scratch {
  alignas(1024) uint32_t flags[F_N];
  alignas(1024) float CSP[2 * NCTA * 216];
  alignas(1024) uint2 RT[SEQ];
  alignas(1024) uint4 XST[2 * SEQ];
  alignas(1024) uint4 ST1[SEQ * 4];
  alignas(1024) uint4 ZST[SEQ * 4];
  alignas(1024) uint4 HALO[32 * 8 * 6 * 32];
  alignas(1024) uint8_t WO[8 * WO_SL];
  alignas(1024) uint8_t WQ[8 * WQ_SL];
  alignas(1024) uint8_t Z[576 * ZB];
};
__device__ Scratch g_scratch;

struct Ptrs {
  const __nv_bfloat16* wqkv;
  uint8_t* WQ;
  uint32_t* flags;
  float* CSP;
  const uint8_t* x;
  uint32_t zero;
  uint4 *XST, *HALO, *ST1, *ZST;
  uint2* RT;
  uint8_t *Z, *WO, *out;
  const __nv_bfloat16 *wo, *w_in, *w_sp, *b_sp;
};
struct Params {
  CUtensorMap wsp, winb[2], wins, wout;
  CUtensorMap act[2];
  CUtensorMap res[2];
  CUtensorMap row[2];
};

__device__ __forceinline__ uint32_t smem_u32(const void* p) { return (uint32_t)__cvta_generic_to_shared(p); }
__device__ __forceinline__ void mbar_init(uint32_t bar, uint32_t cnt) { asm volatile("mbarrier.init.shared::cta.b64 [%0], %1;" ::"r"(bar), "r"(cnt)); }
__device__ __forceinline__ void mbar_arrive(uint32_t bar) { asm volatile("mbarrier.arrive.shared::cta.b64 _, [%0];" ::"r"(bar) : "memory"); }
__device__ __forceinline__ void mbar_wait(uint32_t bar, uint32_t parity) {
  asm volatile(
      "{\n.reg .pred p;\n.reg .u32 c;\nmov.u32 c, 0;\nLAB_WAIT:\n"
      "mbarrier.try_wait.parity.shared::cta.b64 p, [%0], %1;\n@p bra LAB_DONE;\n"
      "add.u32 c, c, 1;\nsetp.lt.u32 p, c, 0x100000;\n@p bra LAB_WAIT;\ntrap;\nLAB_DONE:\n}" ::"r"(bar), "r"(parity)
      : "memory");
}
__device__ __forceinline__ void mbar_wait_c(uint32_t bar, uint32_t parity) {
  asm volatile("{\n.reg .pred p;\nLAB_WAIT:\nmbarrier.try_wait.parity.shared::cta.b64 p, [%0], %1;\n@!p bra LAB_WAIT;\n}" ::"r"(bar), "r"(parity) : "memory");
}
__device__ __forceinline__ void flag_wait(const uint32_t* f, uint32_t target) {
  asm volatile(
      "{\n.reg .pred p;\n.reg .u32 c, v;\nmov.u32 c, 0;\nLAB_WAIT:\n"
      "ld.relaxed.gpu.global.u32 v, [%0];\nsub.u32 v, v, %1;\nsetp.ge.s32 p, v, 0;\n@p bra LAB_DONE;\n"
      "add.u32 c, c, 1;\nsetp.lt.u32 p, c, 0x400000;\n@p bra LAB_WAIT;\ntrap;\nLAB_DONE:\nfence.acquire.gpu;\n}" ::"l"(f), "r"(target)
      : "memory");
}
__device__ __forceinline__ void fence_gpu() { asm volatile("fence.acq_rel.gpu;" ::: "memory"); }
__device__ __forceinline__ void fence_async_g() { asm volatile("fence.proxy.async.global;" ::: "memory"); }
__device__ __forceinline__ void fence_async_s() { asm volatile("fence.proxy.async.shared::cta;" ::: "memory"); }
__device__ __forceinline__ uint32_t elect_one() {
  uint32_t p; asm volatile("{\n.reg .pred P;\nelect.sync _|P, 0xffffffff;\nselp.u32 %0, 1, 0, P;\n}" : "=r"(p)); return p;
}
__device__ __forceinline__ void expect_tx_p(uint32_t el, uint32_t bar, uint32_t bytes) {
  asm volatile("{\n.reg .pred P;\nsetp.ne.u32 P, %2, 0;\n@P mbarrier.arrive.expect_tx.shared::cta.b64 _, [%0], %1;\n}" ::"r"(bar), "r"(bytes), "r"(el) : "memory");
}
__device__ __forceinline__ void bulk_load_p(uint32_t el, uint32_t dst, const void* src, uint32_t bytes, uint32_t bar) {
  asm volatile("{\n.reg .pred P;\nsetp.ne.u32 P, %4, 0;\n@P cp.async.bulk.shared::cluster.global.mbarrier::complete_tx::bytes [%0], [%1], %2, [%3];\n}" ::"r"(dst), "l"(src), "r"(bytes), "r"(bar), "r"(el) : "memory");
}
__device__ __forceinline__ uint64_t policy_evict_first() { uint64_t p; asm("createpolicy.fractional.L2::evict_first.b64 %0, 1.0;" : "=l"(p)); return p; }
__device__ __forceinline__ void bulk_load_h(uint32_t el, uint32_t dst, const void* src, uint32_t bytes, uint32_t bar, bool ef, uint64_t pol) {
  if (ef) {
    asm volatile("{\n.reg .pred P;\nsetp.ne.u32 P, %4, 0;\n@P cp.async.bulk.shared::cluster.global.mbarrier::complete_tx::bytes.L2::cache_hint [%0], [%1], %2, [%3], %5;\n}" ::"r"(dst), "l"(src), "r"(bytes), "r"(bar), "r"(el), "l"(pol) : "memory");
  } else {
    asm volatile("{\n.reg .pred P;\nsetp.ne.u32 P, %4, 0;\n@P cp.async.bulk.shared::cluster.global.mbarrier::complete_tx::bytes [%0], [%1], %2, [%3];\n}" ::"r"(dst), "l"(src), "r"(bytes), "r"(bar), "r"(el) : "memory");
  }
}
__device__ __forceinline__ void bulk_mc_h(uint32_t el, uint32_t dst, const void* src, uint32_t bytes, uint32_t bar, bool ef, uint64_t pol) {
  if (ef) {
    asm volatile("{\n.reg .pred P;\nsetp.ne.u32 P, %4, 0;\n@P cp.async.bulk.shared::cluster.global.mbarrier::complete_tx::bytes.multicast::cluster.L2::cache_hint [%0], [%1], %2, [%3], %5, %6;\n}" ::"r"(dst), "l"(src), "r"(bytes), "r"(bar), "r"(el), "h"((uint16_t)3), "l"(pol) : "memory");
  } else {
    asm volatile("{\n.reg .pred P;\nsetp.ne.u32 P, %4, 0;\n@P cp.async.bulk.shared::cluster.global.mbarrier::complete_tx::bytes.multicast::cluster [%0], [%1], %2, [%3], %5;\n}" ::"r"(dst), "l"(src), "r"(bytes), "r"(bar), "r"(el), "h"((uint16_t)3) : "memory");
  }
}
__device__ __forceinline__ void tma3d_h(uint32_t el, uint32_t dst, const CUtensorMap* m, int c0, int c1, int c2, uint32_t bar, bool ef, uint64_t pol) {
  if (ef) {
    asm volatile("{\n.reg .pred P;\nsetp.ne.u32 P, %6, 0;\n@P cp.async.bulk.tensor.3d.shared::cluster.global.mbarrier::complete_tx::bytes.L2::cache_hint [%0], [%1, {%3, %4, %5}], [%2], %7;\n}" ::"r"(dst), "l"(m), "r"(bar), "r"(c0), "r"(c1), "r"(c2), "r"(el), "l"(pol) : "memory");
  } else {
    asm volatile("{\n.reg .pred P;\nsetp.ne.u32 P, %6, 0;\n@P cp.async.bulk.tensor.3d.shared::cluster.global.mbarrier::complete_tx::bytes [%0], [%1, {%3, %4, %5}], [%2];\n}" ::"r"(dst), "l"(m), "r"(bar), "r"(c0), "r"(c1), "r"(c2), "r"(el) : "memory");
  }
}
__device__ __forceinline__ void tma2d_mc_h(uint32_t el, uint32_t dst, const CUtensorMap* m, int c0, int c1, uint32_t bar, bool ef, uint64_t pol) {
  if (ef) {
    asm volatile("{\n.reg .pred P;\nsetp.ne.u32 P, %5, 0;\n@P cp.async.bulk.tensor.2d.shared::cluster.global.mbarrier::complete_tx::bytes.multicast::cluster.L2::cache_hint [%0], [%1, {%3, %4}], [%2], %6, %7;\n}" ::"r"(dst), "l"(m), "r"(bar), "r"(c0), "r"(c1), "r"(el), "h"((uint16_t)3), "l"(pol) : "memory");
  } else {
    asm volatile("{\n.reg .pred P;\nsetp.ne.u32 P, %5, 0;\n@P cp.async.bulk.tensor.2d.shared::cluster.global.mbarrier::complete_tx::bytes.multicast::cluster [%0], [%1, {%3, %4}], [%2], %6;\n}" ::"r"(dst), "l"(m), "r"(bar), "r"(c0), "r"(c1), "r"(el), "h"((uint16_t)3) : "memory");
  }
}
__device__ __forceinline__ void tma3d_mc_h(uint32_t el, uint32_t dst, const CUtensorMap* m, int c0, int c1, int c2, uint32_t bar, bool ef, uint64_t pol) {
  if (ef) {
    asm volatile("{\n.reg .pred P;\nsetp.ne.u32 P, %6, 0;\n@P cp.async.bulk.tensor.3d.shared::cluster.global.mbarrier::complete_tx::bytes.multicast::cluster.L2::cache_hint [%0], [%1, {%3, %4, %5}], [%2], %7, %8;\n}" ::"r"(dst), "l"(m), "r"(bar), "r"(c0), "r"(c1), "r"(c2), "r"(el), "h"((uint16_t)3), "l"(pol) : "memory");
  } else {
    asm volatile("{\n.reg .pred P;\nsetp.ne.u32 P, %6, 0;\n@P cp.async.bulk.tensor.3d.shared::cluster.global.mbarrier::complete_tx::bytes.multicast::cluster [%0], [%1, {%3, %4, %5}], [%2], %7;\n}" ::"r"(dst), "l"(m), "r"(bar), "r"(c0), "r"(c1), "r"(c2), "r"(el), "h"((uint16_t)3) : "memory");
  }
}
__device__ __forceinline__ void mbar_arrive_cluster(uint32_t addr) { asm volatile("mbarrier.arrive.shared::cluster.b64 _, [%0];" ::"r"(addr) : "memory"); }
__device__ __forceinline__ uint32_t mapa(uint32_t addr, uint32_t rank) { uint32_t r; asm("mapa.shared::cluster.u32 %0, %1, %2;" : "=r"(r) : "r"(addr), "r"(rank)); return r; }
__device__ __forceinline__ void bulk_store_p(uint32_t el, void* dst, uint32_t src, uint32_t bytes) {
  asm volatile("{\n.reg .pred P;\nsetp.ne.u32 P, %3, 0;\n@P cp.async.bulk.global.shared::cta.bulk_group [%0], [%1], %2;\n}" ::"l"(dst), "r"(src), "r"(bytes), "r"(el) : "memory");
}
__device__ __forceinline__ void flag_release_p(uint32_t el, uint32_t* f) {
  asm volatile("{\n.reg .pred P;\nsetp.ne.u32 P, %1, 0;\nfence.proxy.async;\n@P red.relaxed.gpu.global.add.u32 [%0], 1;\n}" ::"l"(f), "r"(el) : "memory");
}
__device__ __forceinline__ void flag_add_p(uint32_t el, uint32_t* f) {
  asm volatile("{\n.reg .pred P;\nsetp.ne.u32 P, %1, 0;\n@P red.relaxed.gpu.global.add.u32 [%0], 1;\n}" ::"l"(f), "r"(el) : "memory");
}
__device__ __forceinline__ void prefetch_l2(const void* src, uint32_t bytes) { asm volatile("cp.async.bulk.prefetch.L2.global [%0], %1;" ::"l"(src), "r"(bytes) : "memory"); }
__device__ __forceinline__ void prefetch_map(const CUtensorMap* m) { asm volatile("prefetch.tensormap [%0];" ::"l"(m) : "memory"); }
__device__ __forceinline__ void wgmma_fence() { asm volatile("wgmma.fence.sync.aligned;" ::: "memory"); }
__device__ __forceinline__ void wgmma_commit() { asm volatile("wgmma.commit_group.sync.aligned;" ::: "memory"); }
template <int N> __device__ __forceinline__ void wgmma_wait() { asm volatile("wgmma.wait_group.sync.aligned %0;" ::"n"(N) : "memory"); }
__device__ __forceinline__ uint32_t dlo(uint32_t addr, uint32_t lbo) { return ((addr & 0x3FFFF) >> 4) + ((lbo >> 4) << 16); }
template <uint32_t SBO, uint32_t SWZ> __device__ __forceinline__ uint64_t dsc(uint32_t lo, uint32_t off) {
  uint64_t d; asm("mov.b64 %0, {%1, %2};" : "=l"(d) : "r"(lo + (off >> 4)), "n"((SBO >> 4) | (SWZ << 30))); return d;
}
template <int R> __device__ __forceinline__ void reg_alloc() { asm volatile("setmaxnreg.inc.sync.aligned.u32 %0;" ::"n"(R)); }
template <int R> __device__ __forceinline__ void reg_dealloc() { asm volatile("setmaxnreg.dec.sync.aligned.u32 %0;" ::"n"(R)); }
__device__ __forceinline__ void bar_sync(int id, int n) { asm volatile("bar.sync %0, %1;" ::"r"(id), "r"(n) : "memory"); }
__device__ __forceinline__ void bar_arrive(int id, int n) { asm volatile("bar.arrive %0, %1;" ::"r"(id), "r"(n) : "memory"); }
__device__ __forceinline__ void ldsm4(uint32_t* r, uint32_t addr) {
  asm volatile("ldmatrix.sync.aligned.m8n8.x4.shared.b16 {%0,%1,%2,%3}, [%4];" : "=r"(r[0]), "=r"(r[1]), "=r"(r[2]), "=r"(r[3]) : "r"(addr) : "memory");
}
__device__ __forceinline__ uint32_t movm(uint32_t a) { uint32_t d; asm volatile("movmatrix.sync.aligned.m8n8.trans.b16 %0, %1;" : "=r"(d) : "r"(a)); return d; }
__device__ __forceinline__ void mma16(float* c, uint32_t a0, uint32_t a1, uint32_t a2, uint32_t a3, uint32_t b0, uint32_t b1) {
  asm volatile("mma.sync.aligned.m16n8k16.row.col.f32.bf16.bf16.f32 {%0,%1,%2,%3}, {%4,%5,%6,%7}, {%8,%9}, {%0,%1,%2,%3};"
               : "+f"(c[0]), "+f"(c[1]), "+f"(c[2]), "+f"(c[3]) : "r"(a0), "r"(a1), "r"(a2), "r"(a3), "r"(b0), "r"(b1));
}
__device__ __forceinline__ void mma8(float* c, uint32_t a0, uint32_t a1, uint32_t b0) {
  asm volatile("mma.sync.aligned.m16n8k8.row.col.f32.bf16.bf16.f32 {%0,%1,%2,%3}, {%4,%5}, {%6}, {%0,%1,%2,%3};"
               : "+f"(c[0]), "+f"(c[1]), "+f"(c[2]), "+f"(c[3]) : "r"(a0), "r"(a1), "r"(b0));
}
__device__ __forceinline__ uint32_t pack2(float lo, float hi) { uint32_t r; asm("cvt.rn.bf16x2.f32 %0, %1, %2;" : "=r"(r) : "f"(hi), "f"(lo)); return r; }
__device__ __forceinline__ float blo(uint32_t v) { return __uint_as_float(v << 16); }
__device__ __forceinline__ float bhi(uint32_t v) { return __uint_as_float(v & 0xffff0000u); }
__device__ __forceinline__ float tanh_fast(float x) { float y; asm("tanh.approx.f32 %0, %1;" : "=f"(y) : "f"(x)); return y; }
__device__ __forceinline__ float rcp_fast(float x) { float y; asm("rcp.approx.ftz.f32 %0, %1;" : "=f"(y) : "f"(x)); return y; }
__device__ __forceinline__ float rsq_fast(float x) { float y; asm("rsqrt.approx.ftz.f32 %0, %1;" : "=f"(y) : "f"(x)); return y; }
__device__ __forceinline__ float ex2(float x) { float y; asm("ex2.approx.ftz.f32 %0, %1;" : "=f"(y) : "f"(x)); return y; }
__device__ __forceinline__ float qsum(float v) { v += __shfl_xor_sync(~0u, v, 1); v += __shfl_xor_sync(~0u, v, 2); return v; }
__device__ __forceinline__ float qmax(float v) { v = fmaxf(v, __shfl_xor_sync(~0u, v, 1)); v = fmaxf(v, __shfl_xor_sync(~0u, v, 2)); return v; }
__device__ __forceinline__ void stg32(void* p, uint32_t v) { asm volatile("st.global.u32 [%0], %1;" ::"l"(p), "r"(v) : "memory"); }
__device__ __forceinline__ void stg128(void* p, uint32_t a, uint32_t b, uint32_t c, uint32_t d) { asm volatile("st.global.v4.u32 [%0], {%1,%2,%3,%4};" ::"l"(p), "r"(a), "r"(b), "r"(c), "r"(d) : "memory"); }
__device__ __forceinline__ uint32_t ldcg32(const void* p) { uint32_t v; asm volatile("ld.global.L1::no_allocate.u32 %0, [%1];" : "=r"(v) : "l"(p) : "memory"); return v; }
__device__ __forceinline__ void stg128_if(bool c, void* p, uint32_t a, uint32_t b, uint32_t cc, uint32_t d) {
  asm volatile("{\n.reg .pred P;\nsetp.ne.u32 P, %5, 0;\n@P st.global.v4.u32 [%0], {%1,%2,%3,%4};\n}" ::"l"(p), "r"(a), "r"(b), "r"(cc), "r"(d), "r"((uint32_t)c) : "memory");
}
__device__ __forceinline__ uint2 lds64(uint32_t a) { uint2 v; asm volatile("ld.shared.v2.u32 {%0,%1}, [%2];" : "=r"(v.x), "=r"(v.y) : "r"(a) : "memory"); return v; }
__device__ __forceinline__ uint4 ldcg128(const void* p) { uint4 v; asm volatile("ld.global.cg.v4.u32 {%0,%1,%2,%3}, [%4];" : "=r"(v.x), "=r"(v.y), "=r"(v.z), "=r"(v.w) : "l"(p) : "memory"); return v; }
__device__ __forceinline__ uint32_t ldnc16(const void* p) { uint16_t v; asm volatile("ld.global.nc.u16 %0, [%1];" : "=h"(v) : "l"(p)); return v; }
__device__ __forceinline__ uint4 ldnc128(const void* p) { uint4 v; asm volatile("ld.global.nc.v4.u32 {%0,%1,%2,%3}, [%4];" : "=r"(v.x), "=r"(v.y), "=r"(v.z), "=r"(v.w) : "l"(p)); return v; }
__device__ __forceinline__ void cp_async16(uint32_t dst, const void* src) { asm volatile("cp.async.cg.shared.global [%0], [%1], 16;" ::"r"(dst), "l"(src) : "memory"); }
__device__ __forceinline__ uint32_t hsub2(uint32_t a, uint32_t b) { uint32_t d; asm("sub.rn.bf16x2 %0, %1, %2;" : "=r"(d) : "r"(a), "r"(b)); return d; }
__device__ __forceinline__ void stg32_if(bool c, void* p, uint32_t v) {
  asm volatile("{\n.reg .pred P;\nsetp.ne.u32 P, %2, 0;\n@P st.global.u32 [%0], %1;\n}" ::"l"(p), "r"(v), "r"((uint32_t)c) : "memory");
}
__device__ __forceinline__ float wsum(float v) { for (int o = 16; o; o >>= 1) v += __shfl_xor_sync(~0u, v, o); return v; }
__device__ __forceinline__ uint32_t hmul2(uint32_t a, uint32_t b) { uint32_t d; asm("mul.rn.bf16x2 %0, %1, %2;" : "=r"(d) : "r"(a), "r"(b)); return d; }
__device__ __forceinline__ void sts32(uint32_t a, uint32_t v) { asm volatile("st.shared.u32 [%0], %1;" ::"r"(a), "r"(v) : "memory"); }
__device__ __forceinline__ uint32_t lds32(uint32_t a) { uint32_t v; asm volatile("ld.shared.u32 %0, [%1];" : "=r"(v) : "r"(a) : "memory"); return v; }
__device__ __forceinline__ void sts128(uint32_t a, uint32_t x, uint32_t y, uint32_t z, uint32_t w) { asm volatile("st.shared.v4.u32 [%0], {%1,%2,%3,%4};" ::"r"(a), "r"(x), "r"(y), "r"(z), "r"(w) : "memory"); }
__device__ __forceinline__ uint4 lds128(uint32_t a) { uint4 v; asm volatile("ld.shared.v4.u32 {%0,%1,%2,%3}, [%4];" : "=r"(v.x), "=r"(v.y), "=r"(v.z), "=r"(v.w) : "r"(a) : "memory"); return v; }
__device__ __forceinline__ void ll_st64(uint2* p, uint32_t v, uint32_t tag) {
  asm volatile("{\n.reg .b64 r;\nmov.b64 r, {%1,%2};\nst.relaxed.gpu.global.b64 [%0], r;\n}" ::"l"(p), "r"(v), "r"(tag) : "memory");
}
__device__ __forceinline__ uint2 ll_ld64(const uint2* p) {
  uint2 v; asm volatile("{\n.reg .b64 r;\nld.relaxed.gpu.global.b64 r, [%2];\nmov.b64 {%0,%1}, r;\n}" : "=r"(v.x), "=r"(v.y) : "l"(p) : "memory"); return v;
}
__device__ __forceinline__ void ll_st128(uint4* p, float a, float b, uint32_t tag, float c = 0.f) {
  asm volatile("{\n.reg .b128 r;\n.reg .b64 lo, hi;\nmov.b64 lo, {%1,%2};\nmov.b64 hi, {%3,%4};\nmov.b128 r, {lo, hi};\nst.relaxed.gpu.global.b128 [%0], r;\n}" ::"l"(p), "r"(__float_as_uint(a)), "r"(__float_as_uint(b)), "r"(tag), "r"(__float_as_uint(c)) : "memory");
}
__device__ __forceinline__ uint4 ll_ld128g(const void* p) {
  uint4 v; asm volatile("{\n.reg .b128 r;\n.reg .b64 lo, hi;\nld.relaxed.gpu.b128 r, [%4];\nmov.b128 {lo, hi}, r;\nmov.b64 {%0,%1}, lo;\nmov.b64 {%2,%3}, hi;\n}" : "=r"(v.x), "=r"(v.y), "=r"(v.z), "=r"(v.w) : "l"(p) : "memory"); return v;
}
__device__ __forceinline__ uint4 ll_ld128(const uint4* p) {
  uint4 v; asm volatile("{\n.reg .b128 r;\n.reg .b64 lo, hi;\nld.relaxed.gpu.global.b128 r, [%4];\nmov.b128 {lo, hi}, r;\nmov.b64 {%0,%1}, lo;\nmov.b64 {%2,%3}, hi;\n}" : "=r"(v.x), "=r"(v.y), "=r"(v.z), "=r"(v.w) : "l"(p) : "memory"); return v;
}
__device__ __forceinline__ void publish_p(uint32_t el, uint32_t* f) {
  asm volatile("{\n.reg .pred P;\nsetp.ne.u32 P, %1, 0;\n@P cp.async.bulk.commit_group;\n@P cp.async.bulk.wait_group 0;\n@P red.release.gpu.global.add.u32 [%0], 1;\n}" ::"l"(f), "r"(el) : "memory");
}
__device__ __forceinline__ void stsm4(uint32_t addr, uint32_t a, uint32_t b, uint32_t c, uint32_t d) {
  asm volatile("stmatrix.sync.aligned.m8n8.x4.shared.b16 [%0], {%1,%2,%3,%4};" ::"r"(addr), "r"(a), "r"(b), "r"(c), "r"(d) : "memory");
}
__device__ __forceinline__ void sts64(uint32_t a, uint32_t x, uint32_t y) { asm volatile("st.shared.v2.u32 [%0], {%1,%2};" ::"r"(a), "r"(x), "r"(y) : "memory"); }
__device__ __forceinline__ void ll_st128_if(bool on, uint4* p, float a, float b, uint32_t tag) {
  asm volatile("{\n.reg .pred P;\n.reg .b128 r;\n.reg .b64 lo, hi;\nsetp.ne.u32 P, %4, 0;\nmov.b64 lo, {%1,%2};\nmov.b64 hi, {%3,%3};\nmov.b128 r, {lo, hi};\n@P st.relaxed.gpu.global.b128 [%0], r;\n}" ::"l"(p), "r"(__float_as_uint(a)), "r"(__float_as_uint(b)), "r"(tag), "r"((uint32_t)on) : "memory");
}
__device__ __forceinline__ uint4 ldnc128_if(bool c, const void* p) {
  uint4 v = make_uint4(0u, 0u, 0u, 0u);
  asm volatile("{\n.reg .pred P;\nsetp.ne.u32 P, %5, 0;\n@P ld.global.nc.v4.u32 {%0,%1,%2,%3}, [%4];\n}" : "+r"(v.x), "+r"(v.y), "+r"(v.z), "+r"(v.w) : "l"(p), "r"((uint32_t)c));
  return v;
}
__device__ __forceinline__ uint32_t hfma2(uint32_t a, uint32_t b, uint32_t c) { uint32_t d; asm("fma.rn.bf16x2 %0, %1, %2, %3;" : "=r"(d) : "r"(a), "r"(b), "r"(c)); return d; }
__device__ __forceinline__ float2 lds64f(uint32_t a) { float2 v; asm volatile("ld.shared.v2.f32 {%0,%1}, [%2];" : "=f"(v.x), "=f"(v.y) : "r"(a) : "memory"); return v; }
#define TRC(cond, role, idx) do {} while (0)
#define TRV(role, idx, v) do {} while (0)
#define TRVI(c, role, idx, v) do {} while (0)

#define ACLK_INIT do {} while (0)
#define ACLK(i) do {} while (0)
#define ACLK_OUT do {} while (0)
#define QCLK(i) do {} while (0)
#define PH 1
#define RCLK(i) do {} while (0)
#define RCLK_INIT do {} while (0)
#define RCLK_OUT do {} while (0)
#define SCLK(i) do {} while (0)
#define SCLK2(i) do {} while (0)
#define SCLK3(i) do {} while (0)
#define PL 1
#define PCLK(i) do {} while (0)
#define PQ 1
#define CLK_INIT do {} while (0)
#define CLK(i) do {} while (0)
#define CLK_OUT do {} while (0)

__device__ __forceinline__ void wgmma_ss_n216(float* d, uint64_t da, uint64_t db, int scaleD) {
  asm volatile("{\n.reg .pred p;\nsetp.ne.b32 p, %110, 0;\nwgmma.mma_async.sync.aligned.m64n216k16.f32.bf16.bf16 "
    "{%0,%1,%2,%3,%4,%5,%6,%7,%8,%9,%10,%11,%12,%13,%14,%15,%16,%17,%18,%19,%20,%21,%22,%23,%24,%25,%26,%27,%28,%29,%30,%31,%32,%33,%34,%35,%36,%37,%38,%39,%40,%41,%42,%43,%44,%45,%46,%47,%48,%49,%50,%51,%52,%53,%54,%55,%56,%57,%58,%59,%60,%61,%62,%63,%64,%65,%66,%67,%68,%69,%70,%71,%72,%73,%74,%75,%76,%77,%78,%79,%80,%81,%82,%83,%84,%85,%86,%87,%88,%89,%90,%91,%92,%93,%94,%95,%96,%97,%98,%99,%100,%101,%102,%103,%104,%105,%106,%107}, "
    "%108, %109, p, 1, 1, 0, 1;\n}\n"
    : "+f"(d[0]), "+f"(d[1]), "+f"(d[2]), "+f"(d[3]), "+f"(d[4]), "+f"(d[5]), "+f"(d[6]), "+f"(d[7]), "+f"(d[8]), "+f"(d[9]), "+f"(d[10]), "+f"(d[11]), "+f"(d[12]), "+f"(d[13]), "+f"(d[14]), "+f"(d[15]), "+f"(d[16]), "+f"(d[17]), "+f"(d[18]), "+f"(d[19]), "+f"(d[20]), "+f"(d[21]), "+f"(d[22]), "+f"(d[23]), "+f"(d[24]), "+f"(d[25]), "+f"(d[26]), "+f"(d[27]), "+f"(d[28]), "+f"(d[29]), "+f"(d[30]), "+f"(d[31]), "+f"(d[32]), "+f"(d[33]), "+f"(d[34]), "+f"(d[35]), "+f"(d[36]), "+f"(d[37]), "+f"(d[38]), "+f"(d[39]), "+f"(d[40]), "+f"(d[41]), "+f"(d[42]), "+f"(d[43]), "+f"(d[44]), "+f"(d[45]), "+f"(d[46]), "+f"(d[47]), "+f"(d[48]), "+f"(d[49]), "+f"(d[50]), "+f"(d[51]), "+f"(d[52]), "+f"(d[53]), "+f"(d[54]), "+f"(d[55]), "+f"(d[56]), "+f"(d[57]), "+f"(d[58]), "+f"(d[59]), "+f"(d[60]), "+f"(d[61]), "+f"(d[62]), "+f"(d[63]), "+f"(d[64]), "+f"(d[65]), "+f"(d[66]), "+f"(d[67]), "+f"(d[68]), "+f"(d[69]), "+f"(d[70]), "+f"(d[71]), "+f"(d[72]), "+f"(d[73]), "+f"(d[74]), "+f"(d[75]), "+f"(d[76]), "+f"(d[77]), "+f"(d[78]), "+f"(d[79]), "+f"(d[80]), "+f"(d[81]), "+f"(d[82]), "+f"(d[83]), "+f"(d[84]), "+f"(d[85]), "+f"(d[86]), "+f"(d[87]), "+f"(d[88]), "+f"(d[89]), "+f"(d[90]), "+f"(d[91]), "+f"(d[92]), "+f"(d[93]), "+f"(d[94]), "+f"(d[95]), "+f"(d[96]), "+f"(d[97]), "+f"(d[98]), "+f"(d[99]), "+f"(d[100]), "+f"(d[101]), "+f"(d[102]), "+f"(d[103]), "+f"(d[104]), "+f"(d[105]), "+f"(d[106]), "+f"(d[107])
    : "l"(da), "l"(db), "r"(scaleD));
}
__device__ __forceinline__ void wgmma_ss_n72(float* d, uint64_t da, uint64_t db, int scaleD) {
  asm volatile("{\n.reg .pred p;\nsetp.ne.b32 p, %38, 0;\nwgmma.mma_async.sync.aligned.m64n72k16.f32.bf16.bf16 "
    "{%0,%1,%2,%3,%4,%5,%6,%7,%8,%9,%10,%11,%12,%13,%14,%15,%16,%17,%18,%19,%20,%21,%22,%23,%24,%25,%26,%27,%28,%29,%30,%31,%32,%33,%34,%35}, "
    "%36, %37, p, 1, 1, 0, 1;\n}\n"
    : "+f"(d[0]), "+f"(d[1]), "+f"(d[2]), "+f"(d[3]), "+f"(d[4]), "+f"(d[5]), "+f"(d[6]), "+f"(d[7]), "+f"(d[8]), "+f"(d[9]), "+f"(d[10]), "+f"(d[11]), "+f"(d[12]), "+f"(d[13]), "+f"(d[14]), "+f"(d[15]), "+f"(d[16]), "+f"(d[17]), "+f"(d[18]), "+f"(d[19]), "+f"(d[20]), "+f"(d[21]), "+f"(d[22]), "+f"(d[23]), "+f"(d[24]), "+f"(d[25]), "+f"(d[26]), "+f"(d[27]), "+f"(d[28]), "+f"(d[29]), "+f"(d[30]), "+f"(d[31]), "+f"(d[32]), "+f"(d[33]), "+f"(d[34]), "+f"(d[35])
    : "l"(da), "l"(db), "r"(scaleD));
}
__device__ __forceinline__ void wgmma_ss_n128(float* d, uint64_t da, uint64_t db, int scaleD) {
  asm volatile("{\n.reg .pred p;\nsetp.ne.b32 p, %66, 0;\nwgmma.mma_async.sync.aligned.m64n128k16.f32.bf16.bf16 "
    "{%0,%1,%2,%3,%4,%5,%6,%7,%8,%9,%10,%11,%12,%13,%14,%15,%16,%17,%18,%19,%20,%21,%22,%23,%24,%25,%26,%27,%28,%29,%30,%31,%32,%33,%34,%35,%36,%37,%38,%39,%40,%41,%42,%43,%44,%45,%46,%47,%48,%49,%50,%51,%52,%53,%54,%55,%56,%57,%58,%59,%60,%61,%62,%63}, "
    "%64, %65, p, 1, 1, 0, 1;\n}\n"
    : "+f"(d[0]), "+f"(d[1]), "+f"(d[2]), "+f"(d[3]), "+f"(d[4]), "+f"(d[5]), "+f"(d[6]), "+f"(d[7]), "+f"(d[8]), "+f"(d[9]), "+f"(d[10]), "+f"(d[11]), "+f"(d[12]), "+f"(d[13]), "+f"(d[14]), "+f"(d[15]), "+f"(d[16]), "+f"(d[17]), "+f"(d[18]), "+f"(d[19]), "+f"(d[20]), "+f"(d[21]), "+f"(d[22]), "+f"(d[23]), "+f"(d[24]), "+f"(d[25]), "+f"(d[26]), "+f"(d[27]), "+f"(d[28]), "+f"(d[29]), "+f"(d[30]), "+f"(d[31]), "+f"(d[32]), "+f"(d[33]), "+f"(d[34]), "+f"(d[35]), "+f"(d[36]), "+f"(d[37]), "+f"(d[38]), "+f"(d[39]), "+f"(d[40]), "+f"(d[41]), "+f"(d[42]), "+f"(d[43]), "+f"(d[44]), "+f"(d[45]), "+f"(d[46]), "+f"(d[47]), "+f"(d[48]), "+f"(d[49]), "+f"(d[50]), "+f"(d[51]), "+f"(d[52]), "+f"(d[53]), "+f"(d[54]), "+f"(d[55]), "+f"(d[56]), "+f"(d[57]), "+f"(d[58]), "+f"(d[59]), "+f"(d[60]), "+f"(d[61]), "+f"(d[62]), "+f"(d[63])
    : "l"(da), "l"(db), "r"(scaleD));
}
__device__ __forceinline__ void wgmma_ss_n160(float* d, uint64_t da, uint64_t db, int scaleD) {
  asm volatile("{\n.reg .pred p;\nsetp.ne.b32 p, %82, 0;\nwgmma.mma_async.sync.aligned.m64n160k16.f32.bf16.bf16 "
    "{%0,%1,%2,%3,%4,%5,%6,%7,%8,%9,%10,%11,%12,%13,%14,%15,%16,%17,%18,%19,%20,%21,%22,%23,%24,%25,%26,%27,%28,%29,%30,%31,%32,%33,%34,%35,%36,%37,%38,%39,%40,%41,%42,%43,%44,%45,%46,%47,%48,%49,%50,%51,%52,%53,%54,%55,%56,%57,%58,%59,%60,%61,%62,%63,%64,%65,%66,%67,%68,%69,%70,%71,%72,%73,%74,%75,%76,%77,%78,%79}, "
    "%80, %81, p, 1, 1, 0, 1;\n}\n"
    : "+f"(d[0]), "+f"(d[1]), "+f"(d[2]), "+f"(d[3]), "+f"(d[4]), "+f"(d[5]), "+f"(d[6]), "+f"(d[7]), "+f"(d[8]), "+f"(d[9]), "+f"(d[10]), "+f"(d[11]), "+f"(d[12]), "+f"(d[13]), "+f"(d[14]), "+f"(d[15]), "+f"(d[16]), "+f"(d[17]), "+f"(d[18]), "+f"(d[19]), "+f"(d[20]), "+f"(d[21]), "+f"(d[22]), "+f"(d[23]), "+f"(d[24]), "+f"(d[25]), "+f"(d[26]), "+f"(d[27]), "+f"(d[28]), "+f"(d[29]), "+f"(d[30]), "+f"(d[31]), "+f"(d[32]), "+f"(d[33]), "+f"(d[34]), "+f"(d[35]), "+f"(d[36]), "+f"(d[37]), "+f"(d[38]), "+f"(d[39]), "+f"(d[40]), "+f"(d[41]), "+f"(d[42]), "+f"(d[43]), "+f"(d[44]), "+f"(d[45]), "+f"(d[46]), "+f"(d[47]), "+f"(d[48]), "+f"(d[49]), "+f"(d[50]), "+f"(d[51]), "+f"(d[52]), "+f"(d[53]), "+f"(d[54]), "+f"(d[55]), "+f"(d[56]), "+f"(d[57]), "+f"(d[58]), "+f"(d[59]), "+f"(d[60]), "+f"(d[61]), "+f"(d[62]), "+f"(d[63]), "+f"(d[64]), "+f"(d[65]), "+f"(d[66]), "+f"(d[67]), "+f"(d[68]), "+f"(d[69]), "+f"(d[70]), "+f"(d[71]), "+f"(d[72]), "+f"(d[73]), "+f"(d[74]), "+f"(d[75]), "+f"(d[76]), "+f"(d[77]), "+f"(d[78]), "+f"(d[79])
    : "l"(da), "l"(db), "r"(scaleD));
}
__device__ __forceinline__ void wgmma_rs_n144(float* d, const uint32_t* a, uint64_t db, int scaleD) {
  asm volatile("{\n.reg .pred p;\nsetp.ne.b32 p, %77, 0;\nwgmma.mma_async.sync.aligned.m64n144k16.f32.bf16.bf16 "
    "{%0,%1,%2,%3,%4,%5,%6,%7,%8,%9,%10,%11,%12,%13,%14,%15,%16,%17,%18,%19,%20,%21,%22,%23,%24,%25,%26,%27,%28,%29,%30,%31,%32,%33,%34,%35,%36,%37,%38,%39,%40,%41,%42,%43,%44,%45,%46,%47,%48,%49,%50,%51,%52,%53,%54,%55,%56,%57,%58,%59,%60,%61,%62,%63,%64,%65,%66,%67,%68,%69,%70,%71}, "
    "{%72,%73,%74,%75}, %76, p, 1, 1, 1;\n}\n"
    : "+f"(d[0]), "+f"(d[1]), "+f"(d[2]), "+f"(d[3]), "+f"(d[4]), "+f"(d[5]), "+f"(d[6]), "+f"(d[7]), "+f"(d[8]), "+f"(d[9]), "+f"(d[10]), "+f"(d[11]), "+f"(d[12]), "+f"(d[13]), "+f"(d[14]), "+f"(d[15]), "+f"(d[16]), "+f"(d[17]), "+f"(d[18]), "+f"(d[19]), "+f"(d[20]), "+f"(d[21]), "+f"(d[22]), "+f"(d[23]), "+f"(d[24]), "+f"(d[25]), "+f"(d[26]), "+f"(d[27]), "+f"(d[28]), "+f"(d[29]), "+f"(d[30]), "+f"(d[31]), "+f"(d[32]), "+f"(d[33]), "+f"(d[34]), "+f"(d[35]), "+f"(d[36]), "+f"(d[37]), "+f"(d[38]), "+f"(d[39]), "+f"(d[40]), "+f"(d[41]), "+f"(d[42]), "+f"(d[43]), "+f"(d[44]), "+f"(d[45]), "+f"(d[46]), "+f"(d[47]), "+f"(d[48]), "+f"(d[49]), "+f"(d[50]), "+f"(d[51]), "+f"(d[52]), "+f"(d[53]), "+f"(d[54]), "+f"(d[55]), "+f"(d[56]), "+f"(d[57]), "+f"(d[58]), "+f"(d[59]), "+f"(d[60]), "+f"(d[61]), "+f"(d[62]), "+f"(d[63]), "+f"(d[64]), "+f"(d[65]), "+f"(d[66]), "+f"(d[67]), "+f"(d[68]), "+f"(d[69]), "+f"(d[70]), "+f"(d[71])
    : "r"(a[0]), "r"(a[1]), "r"(a[2]), "r"(a[3]), "l"(db), "r"(scaleD));
}
__device__ __forceinline__ void wgmma_rs_n64(float* d, const uint32_t* a, uint64_t db, int scaleD) {
  asm volatile("{\n.reg .pred p;\nsetp.ne.b32 p, %37, 0;\nwgmma.mma_async.sync.aligned.m64n64k16.f32.bf16.bf16 "
    "{%0,%1,%2,%3,%4,%5,%6,%7,%8,%9,%10,%11,%12,%13,%14,%15,%16,%17,%18,%19,%20,%21,%22,%23,%24,%25,%26,%27,%28,%29,%30,%31}, "
    "{%32,%33,%34,%35}, %36, p, 1, 1, 1;\n}\n"
    : "+f"(d[0]), "+f"(d[1]), "+f"(d[2]), "+f"(d[3]), "+f"(d[4]), "+f"(d[5]), "+f"(d[6]), "+f"(d[7]), "+f"(d[8]), "+f"(d[9]), "+f"(d[10]), "+f"(d[11]), "+f"(d[12]), "+f"(d[13]), "+f"(d[14]), "+f"(d[15]), "+f"(d[16]), "+f"(d[17]), "+f"(d[18]), "+f"(d[19]), "+f"(d[20]), "+f"(d[21]), "+f"(d[22]), "+f"(d[23]), "+f"(d[24]), "+f"(d[25]), "+f"(d[26]), "+f"(d[27]), "+f"(d[28]), "+f"(d[29]), "+f"(d[30]), "+f"(d[31])
    : "r"(a[0]), "r"(a[1]), "r"(a[2]), "r"(a[3]), "l"(db), "r"(scaleD));
}

template <int V> struct Int { static constexpr int value = V; };
struct Cur {
  uint32_t s, ph;
  __device__ __forceinline__ void next() { if (++s == NST) { s = 0; ph ^= 1; } }
};

__device__ __forceinline__ uint32_t o_place(uint32_t w, uint32_t e) { return (((w ? 0xd5310u : 0xa8d57u) >> (4 * e)) & 15) * 8192 + 90112; }
#define z1_block(rb, w, j) (Q.Z + ((rb) * 16 + (w) * 8 + (j)) * ZB)
#define xn_block(hw) (Q.Z + (512 + (hw) * 2) * ZB)
#define z2_block(kb, j) (Q.Z + (256 + (kb) * 8 + (j)) * ZB)
template <int N> __device__ __forceinline__ void pause(uint32_t zero) {
  if (N <= 0) return;
  uint32_t z = clock() + threadIdx.x;
  do {
#pragma unroll (N > 8 ? 1 : 8)
    for (int i = 0; i < N; i++) asm volatile("shfl.sync.bfly.b32 %0, %0, 1, 0x1f, 0xffffffff;" : "+r"(z)::"memory");
  } while (__any_sync(~0u, z & zero));
}

__global__ void __cluster_dims__(2, 1, 1) __launch_bounds__(384, 1) mega_kernel(const Ptrs Q, const __grid_constant__ Params P) {
  extern __shared__ __align__(1024) uint8_t smem_raw[];
  const uint32_t sb = smem_u32(smem_raw);
  const uint32_t bars = sb + SM_BAR;
  const int tid = threadIdx.x;
  int lane = tid & 31;
  const int wid = __shfl_sync(~0u, tid >> 5, 0);
  const int cl = blockIdx.x >> 1;
  const int bid = (cl < 4 ? cl * 8 + 32 : cl - 4 + (max(cl - 29, 0) * 37 >> 8)) * 2 + (blockIdx.x & 1);
  const int rb = bid & 15, j = bid >> 4;
  uint4 wv[5];
  {
    const int n8 = min(tid >> 3, 26), part = n8 / 9;
    const uint8_t* src = (const uint8_t*)Q.wqkv + (8 * rb + (tid & 7)) * (3 * DM * 2) + (part * (DM - 72) + 72 * j + 8 * n8) * 2;
#pragma unroll
    for (int u = 0; u < 5; u++) wv[u] = ldnc128_if(tid < 216 && cl < 64 && (u < 4 || rb < 8), src + u * (128 * 3 * DM * 2));
  }
  if (cl >= 64) return;
  if (wid >= 7 && lane == 0) {
    if (wid < 10) {
#pragma unroll
      for (uint32_t b = 0; b < B_AD / 3; b += 8) mbar_init(bars + (wid - 7) * (B_AD / 3) + b, 1);
    } else if (wid == 10) {
#pragma unroll
      for (uint32_t b = B_AD; b < B_EVT; b += 8) mbar_init(bars + b, b < B_LAG ? 2 : 4);
    } else {
#pragma unroll
      for (uint32_t b = B_EVT; b < 1024; b += 8) if (b < B_OFF || b >= B_IMG) mbar_init(bars + b, b < B_IMG ? 4 : b < B_EMPTY ? 8 : 16);
    }
    asm volatile("fence.mbarrier_init.release.cluster;" ::: "memory");
  }
  __syncthreads();

  if (wid >= 8) {
    reg_dealloc<56>();
    const uint32_t el = elect_one();
    const uint64_t pol = policy_evict_first();
    uint32_t* const fj = Q.flags + FJ + j * 32;
    if (wid == 8) {
      if (el) { prefetch_map(&P.wsp); prefetch_map(&P.winb[j & 1]); prefetch_map(&P.wins); prefetch_map(&P.wout); prefetch_map(&P.act[1]); prefetch_map(&P.res[0]); prefetch_map(&P.res[1]); prefetch_map(&P.row[1]); }
      const uint32_t epoch = ldcg32(fj + FJ_EP + rb);
      Cur c{0, 1};
      const uint32_t rk = bid & 1;
      uint32_t st, full;
      auto slot = [&](uint32_t bytes) {
        st = sb + c.s * ST_BYTES; full = bars + B_FULL + c.s * 8;
        mbar_wait(full, c.ph);
        expect_tx_p(el, full, bytes);
        mbar_wait(full - B_FULL + B_EMPTY, c.ph);
      };
#pragma unroll 1
      for (int L = 0; L < 2; L++) {
#pragma unroll 1
        for (int i = 0; i < 9; i++) {
          if (L == 0 && i == 0) {
            flag_wait(fj + FJ_WQ, (epoch + 1) * 16);
            fence_async_g();
            TRC(el, 2, 45);
          }
          slot(27648);
          bulk_mc_h(el, st + ST_B + rk * 13824, Q.WQ + j * WQ_SL + i * 27648 + rk * 13824, 13824, full, EF(0), pol);
          c.next();
        }
        if (L == 0) {
          flag_wait(fj + FJ_WO, (epoch + 1) * 16);
          fence_async_g();
          TRC(el, 2, 46);
        }
#pragma unroll 1
        while (c.s) {
          mbar_wait(bars + B_EMPTY + c.s * 8, c.ph);
          if (el) { mbar_arrive(bars + B_FULL + c.s * 8); asm volatile("mbarrier.arrive.shared::cta.b64 _, [%0], 16;" ::"r"(bars + B_EMPTY + c.s * 8) : "memory"); }
          c.next();
        }
        expect_tx_p(el, bars + B_WF, WO_SL);
        mbar_wait(bars + B_EMPTY, c.ph);
        mbar_wait(bars + B_EMPTY + 8, c.ph);
        bulk_mc_h(el, sb + rk * (WO_SL / 2), Q.WO + j * WO_SL + rk * (WO_SL / 2), WO_SL / 2, bars + B_WF, EF(1), pol);
#pragma unroll 1
        for (int r = 0; r < 10; r++) {
          const bool big = r >= 2 && r < 8;
          const int a0 = (r < 5 ? 36 : 0) + ((9 * j) >> 1) + (big ? 2 - 2 * (j & 1) : 3 * (j & 1) + rk), ks = big ? 32 : 48;
          int k = big ? (r < 5 ? r - 2 : r - 5) * 192 + rk * 16 : (r & 1) * 288;
          const CUtensorMap* m = big ? &P.winb[j & 1] : &P.wins;
          const uint32_t dst = sb + SM_B3 + rk * 6144;
#pragma unroll
          for (int p = 0; p < 6; p++, k += ks) {
            if (!(p & 3) && r == 0) mbar_wait(bars + B_XD + p * 2, L);
            if (p) mbar_wait_c(bars + B_E3 + p * 8, ~r & 1); else mbar_wait(bars + B_E3, ~r & 1);
            expect_tx_p(el, bars + B_F3 + p * 8, 12288);
            tma3d_mc_h(el, dst + p * 12288, m, 0, k, a0, bars + B_F3 + p * 8, EF(2), pol);
          }
        }
        TRC(el, 2, L * 16 + 6);
        mbar_wait(bars + B_ZOK, L);
        fence_async_g();
        TRC(el, 2, L * 16 + 7);
        const uint8_t* src = z2_block(0, j) + rk * 18432;
#pragma unroll 1
        for (int r = 0; r < 8; r++) {
          const int k = (r & 3) * 512 + ((r >> 2) ^ 1) * 64;
#pragma unroll
          for (int p = 0; p < 4; p++, src += 8 * ZB) {
            if ((p == 1 || p == 2) && r == 0) mbar_wait(bars + B_E3 - 8 + p * 24, 1);
            mbar_wait_c(bars + B_AD + p * 8, ~r & 1);
            if (p) mbar_wait_c(bars + B_EMPTY + p * 8, c.ph); else mbar_wait(bars + B_EMPTY, c.ph);
            expect_tx_p(el, bars + B_FULL + p * 8, ST_BYTES);
            bulk_mc_h(el, sb + p * ST_BYTES + ST_B + rk * 18432, src, 18432, bars + B_FULL + p * 8, EF(4), pol);
            tma3d_h(el, sb + p * ST_BYTES, &P.wsp, k + p * 128, rb * 64, 0, bars + B_FULL + p * 8, EF(3), pol);
          }
          c.ph ^= 1;
        }
        mbar_wait(bars + B_Z1, L);
        fence_async_g();
#pragma unroll 1
        for (int i = 0; i < 11; i++) {
          const int cb = i - 2 + j;
          if (i < 4) mbar_wait(bars + B_AD + c.s * 8, 1);
          slot(ZB);
          if (i < 2) bulk_load_h(el, st + ST_B, z1_block(rb, i, j), ZB, full, true, pol);
          else tma2d_mc_h(el, st + ST_B + rk * 18432, &P.wout, (cb >= 9 ? cb - 9 : cb) * 64, 288 * j + rk * 144, full, EF(5), pol);
          c.next();
        }
      }
    } else if (wid < 11) {
      uint32_t id = bid * 2 + wid - 9;
#define AGENT_IDS asm volatile("" : "+r"(lane), "+r"(id)); const uint32_t w = id & 1, hw = id & 31, rb = hw >> 1, j = id >> 5, ev = bars + B_EVT + w * EV_N * 8; \
      uint32_t* const fr = Q.flags + hw * 32; uint32_t* const fj = Q.flags + FJ + j * 32; (void)fr; (void)fj; (void)ev; (void)rb
      uint32_t t8 = 0;
      Cur c{0, 1};
#pragma unroll 1
      for (int L = 0; L < 2; L++) {
        if (L) {
          AGENT_IDS;
          const uint32_t full = bars + B_FULLA + w * 32 + c.s * 8, dst = sb + c.s * ST_BYTES + w * 8192;
          expect_tx_p(el, full, 8192);
          mbar_wait_c(ev + EV_PT * 8, 1);
          TRC(el, 3, w * 32 + 16);
          flag_release_p(el, fr + FR_X2);
          TRC(el, 3, w * 32 + 17);
          mbar_wait_c(bars + B_EMPTY + c.s * 8, c.ph);
          flag_wait(fr + FR_X2, t8);
          fence_async_g();
          tma3d_h(el, dst, &P.act[1], 0, rb * 64, w, full, false, pol);
          c.next();
          TRC(el, 3, w * 32 + 18);
        }
#pragma unroll 1
        for (int i = L; i < 9; i++) {
          AGENT_IDS;
          const uint32_t full = bars + B_FULLA + w * 32 + c.s * 8, dst = sb + c.s * ST_BYTES + w * 8192;
          if (L == 0 && i == AEP) t8 = (ldcg32(fr + FR_EP + j) + 1) * 8;
          mbar_wait_c(bars + B_EMPTY + c.s * 8, c.ph);
          expect_tx_p(el, full, 8192);
          tma3d_h(el, dst, &P.act[L], i * 64, rb * 64, w, full, false, pol);
          c.next();
          if (i == PZI || i == PZI + 1) {
            uint8_t* d = (i == PZI ? xn_block(hw) : z1_block(rb, 0, 0) + w * 4608) + j * 9216 + lane * 16;
#pragma unroll 1
            for (int u = i == PZI ? 0 : 3; u < 6; u++, d += 1536) { stg128(d, ~0u, ~0u, ~0u, ~0u); stg128(d + 512, ~0u, ~0u, ~0u, ~0u); stg128(d + 1024, ~0u, ~0u, ~0u, ~0u); }
          }
          if (i == PZI) { stg128(Q.ST1 + (hw * 8 + j) * 32 + lane, ~0u, ~0u, ~0u, ~0u); stg128(Q.ZST + (hw * 8 + j) * 32 + lane, ~0u, ~0u, ~0u, ~0u); }
          if (i == RFI) {
            expect_tx_p(el, bars + B_WT + w * 8, 9216);
            tma3d_h(el, sb + SM_STG + w * 9216, &P.row[L], 0, 3 * w, rb * 64 + 8 * j, bars + B_WT + w * 8, false, pol);
          }
          if (i == 4 && L > w) {
            expect_tx_p(el, bars + B_XRW + 8, 864);
            bulk_load_p(el, sb + 3 * ST_BYTES + SM_CSQ, Q.CSP + (NCTA + (id >> 1)) * 216, 864, bars + B_XRW + 8);
          }
        }
        if (c.s) { c.s = 0; c.ph ^= 1; }
        {
          AGENT_IDS;
          const uint32_t tag = (t8 >> 2) - 1 + L;
          uint4* const xs = Q.XST + hw * 128;
          const uint32_t tab = sb + L * (3 * ST_BYTES) + SM_XST + w * 768 + lane * 8;
          TRC(el, 3, w * 32 + L * 16 + 13);
#pragma unroll 1
          for (int it = 0; it < (1 << 22); it++) {
            const uint4 a = ll_ld128(xs + 2 * lane), b = ll_ld128(xs + 64 + 2 * lane), h = ll_ld128(xs - (rb ? 192 : 0) + 2 * (lane | 24));
            if (__all_sync(~0u, a.z == tag && b.z == tag && h.z == tag)) { sts64(tab, h.x, h.y); sts64(tab + 256, a.x, a.y); sts64(tab + 512, b.x, b.y); break; }
          }
          __syncwarp();
          if (el) mbar_arrive(bars + B_CSQ);
          TRC(el, 3, w * 32 + L * 16 + 14);
          uint32_t* f = Q.flags + rb * 64 + FR_PZ + L;
          flag_release_p(el, f);
          expect_tx_p(el, bars + B_RES + w * 8, 9216);
          tma3d_h(el, sb + SM_STG + w * 9216, &P.res[L], j * 72, (hw ^ 1) * 32, 0, bars + B_RES + w * 8, !L, pol);
          pause<FD3>(Q.zero);
          flag_wait(f, t8 * 2);
          fence_async_g();
          TRC(el, 3, w * 32 + L * 16 + 15);
        }
        {
          AGENT_IDS;
          uint32_t* f = Q.flags + rb * 64 + FR_O + L;
#pragma unroll 1
          for (int e = 0; e < 5; e++) {
            const uint32_t nb = e ? 16384 : 8192, full = bars + B_OF + w * 40 + e * 8, dst = sb + o_place(w, e);
            const uint8_t* src = z1_block(rb, w, 0) + (e ? e * 16384 - 8192 : 0);
            expect_tx_p(el, full, nb);
            if (e == 0) {
              mbar_wait_c(ev + EV_O * 8, L);
              TRC(el, 3, w * 32 + L * 16 + 3);
              if (!w) flag_add_p(el, f);
              flag_wait(f + w * (FR_OL - FR_O), t8);
              if (w) fence_async_g();
            }
            if (w && (e == 0 || e == 3)) mbar_wait_c(bars + (e ? B_X3 : B_OF + YPACE * 8), L);
            bulk_load_h(el, dst, src, nb, full, EF(6), pol);
            TRC(el && e == 0, 3, w * 32 + L * 16 + 5);
          }
        }
        {
          AGENT_IDS;
          const uint8_t* src = xn_block(hw);
          uint32_t full = bars + B_AF3 + w * 96, dst = sb + w * 6144;
          if (L) flag_wait(fj + FJ_P4, t8 * 4);
          mbar_wait_c(bars + B_XD + 8, L);
          mbar_wait_c(ev + EV_X1 * 8, L);
          TRC(el, 3, w * 32 + L * 16 + 6);
          pause<SDEL>(Q.zero);
#pragma unroll 1
          for (int k = 0; k < 12; k++, src += 6144, dst += 12288, full += 8) {
            expect_tx_p(el, full, 6144);
            if (k >= APACE) mbar_wait_c(full - APACE * 8, L);
            bulk_load_h(el, dst, src, 6144, full, EF(7), pol);
            TRC(el && k == 0, 3, w * 32 + L * 16 + 8);
          }
        }
        if (wid == 10) {
          AGENT_IDS;
          mbar_wait_c(ev - (EV_N - EV_ZN) * 8, L);
          mbar_wait_c(ev + EV_ZN * 8, L);
          asm volatile("fence.release.gpu;" ::: "memory");
          flag_add_p(el, fj + FJ_ZN + L);
          flag_add_p(el, fr - 32 + FR_XR + L);
          pause<FD4>(Q.zero);
          flag_wait(fj + FJ_ZN + L, t8 * 2);
          flag_wait(fr - 32 + FR_XR + L, t8);
          if (el) mbar_arrive(bars + B_ZOK);
        } else if (WPF) {
          AGENT_IDS;
          mbar_wait_c(ev + EV_ZN * 8, L);
          if (el) asm volatile("cp.async.bulk.prefetch.tensor.3d.L2.global [%0, {%1, %2, %3}];" ::"l"(&P.wsp), "r"(j * 128 + 64), "r"(rb * 64), "r"(0) : "memory");

        }
        float cv;
        {
        AGENT_IDS;
        cv = (lane & 3) ? 0.f : -blo(ldnc16(Q.b_sp + 128 * rb + 16 * j + 2 * (lane >> 2) + w));
        const uint32_t ro = (w * 64 + 8 * j + (lane >> 2)) * 128, x0 = ((lane & 3) * 2) ^ (lane >> 2);
#pragma unroll 1
        for (int i = 0; i < 32; i++) {
          const bool tail = (i >> 1) == 12;
          const int kb = tail ? i + 6 : i < 24 ? i : i - 2;
          if (!(i & 7)) mbar_wait_c(bars + B_RT + i, L);
          if (i == 24) mbar_wait_c(bars + B_WT + w * 8, 1);
          if (!tail) mbar_wait(bars + B_FULL + c.s * 8, c.ph ^ 1);
          uint4 x[2];
#pragma unroll
          for (int e = 0; e < 2; e++) x[e] = lds128(!tail ? sb + c.s * ST_BYTES + ro + ((x0 ^ e) << 4) : sb + SM_WT + w * 3200 + (lane >> 2) * 400 + (i - 24) * 256 + (lane & 3) * 32 + e * 16);
          if (!tail) {
            __syncwarp();
            if (el) mbar_arrive(bars + B_AD + c.s * 8);
            c.next();
          }
#pragma unroll
          for (int e = 0; e < 2; e++) {
            const uint4 a = x[e], m = lds128(sb + SM_RT + 4096 + kb * 128 + (lane & 3) * 32 + e * 16);
            cv = fmaf(blo(a.x), blo(m.x), fmaf(bhi(a.x), bhi(m.x), fmaf(blo(a.y), blo(m.y), fmaf(bhi(a.y), bhi(m.y), cv))));
            cv = fmaf(blo(a.z), blo(m.z), fmaf(bhi(a.z), bhi(m.z), fmaf(blo(a.w), blo(m.w), fmaf(bhi(a.w), bhi(m.w), cv))));
          }
          if (i == WTI) {
            uint32_t id2 = id;
            asm volatile("" : "+r"(id2));
            expect_tx_p(el, bars + B_WT + w * 8, 3072);
#pragma unroll 1
            for (int r = 0; r < 8; r++)
              bulk_load_p(el, sb + SM_WT + w * 3200 + r * 400, (const uint8_t*)Q.w_sp + (64 * (id2 & 30) + 16 * (id2 >> 5) + 2 * r + w) * (SEQ * 2) + 28 * 128, 384, bars + B_WT + w * 8);
          }
        }
        }
        AGENT_IDS;
        TRC(el, 3, w * 32 + L * 16 + 11);
        asm volatile("" : "+r"(t8));
        const uint32_t tag = (t8 >> 2) - 1 + L;
        cv = qsum(cv);
        uint2* const cs = (uint2*)(Q.XST + hw * 128 + 1);
        if ((lane & 3) == 0) ll_st64(cs + 32 * j + (lane >> 2) * 4, __float_as_uint(cv), tag);
        pause<FD5>(Q.zero);
#pragma unroll 1
        for (int it = 0; it < (1 << 22); it++) {
          const uint2 a = ll_ld64(cs + 4 * lane), b = ll_ld64(cs + 128 + 4 * lane);
          if (__all_sync(~0u, a.y == tag && b.y == tag)) { sts32(sb + SM_CV + w * 256 + lane * 4, a.x); sts32(sb + SM_CV + w * 256 + 128 + lane * 4, b.x); break; }
        }
        __syncwarp();
        if (el) mbar_arrive(bars + B_CV + w * 8);
        TRC(el, 3, w * 32 + L * 16 + 12);
#pragma unroll 1
        for (int kb = 30; kb < 32; kb++) {
          mbar_wait_c(bars + B_FULL + c.s * 8, c.ph ^ 1);
          if (el) mbar_arrive(bars + B_AD + c.s * 8);
          c.next();
        }
        c.ph ^= ((c.s + 11) >> 2) & 1; c.s = (c.s + 11) & 3;
        if (L == 0) {
          mbar_wait_c(ev + EV_PT * 8, 0);
          flag_add_p(el, fj + FJ_P4);
        }
      }
    } else {
      const uint32_t epoch = ldcg32(fj + FJ_EP + rb);
      mbar_wait(bars + B_IMG, 0);
      TRC(el, 2, 41);
      flag_release_p(el, fj + FJ_WQ);
      TRC(el, 2, 42);
#pragma unroll 1
      for (int L = 0; L < 2; L++) {
        float* const csf = Q.CSP + (NCTA + bid) * 216;
        if (L == 0) {
          flag_wait(fj + FJ_WQ, (epoch + 1) * 16);
          fence_async_g();
          expect_tx_p(el, bars + B_XRW, 13824);
          bulk_load_p(el, sb + ST_BYTES + SM_WOI, Q.CSP + j * 16 * 216, 6912, bars + B_XRW);
          bulk_load_p(el, sb + 2 * ST_BYTES + SM_WOI, Q.CSP + (j * 16 + 8) * 216, 6912, bars + B_XRW);
          mbar_wait(bars + B_XRW, 0);
#pragma unroll 1
          for (int f = lane; f < 54; f += 32) {
            float s[4] = {0.f, 0.f, 0.f, 0.f};
#pragma unroll 2
            for (int r = 0; r < 16; r++) {
              const uint4 v = lds128(sb + ST_BYTES + SM_WOI + (r >> 3) * ST_BYTES + (r & 7) * 864 + f * 16);
              s[0] += __uint_as_float(v.x); s[1] += __uint_as_float(v.y); s[2] += __uint_as_float(v.z); s[3] += __uint_as_float(v.w);
            }
            sts128(sb + SM_CSQ + f * 16, __float_as_uint(s[0]), __float_as_uint(s[1]), __float_as_uint(s[2]), __float_as_uint(s[3]));
            stg128(csf + f * 4, __float_as_uint(s[0]), __float_as_uint(s[1]), __float_as_uint(s[2]), __float_as_uint(s[3]));
          }
          __syncwarp();
          if (el) mbar_arrive(bars + B_XRW + 8);
          TRC(el, 2, 43);
          mbar_wait(bars + B_WOI, 0);
          bulk_store_p(el, Q.WO + j * WO_SL + rb * (41 * 128), sb + SM_WOI, (rb < 15 ? 41 : 33) * 128);
          publish_p(el, fj + FJ_WO);
          TRC(el, 2, 44);
          if (el) prefetch_l2((const uint8_t*)Q.w_in + bid * 41472, 41472);
          float o0 = 0.f, o1 = 0.f;
#pragma unroll 1
          for (int u = 0; u < 2; u++) {
            const uint8_t* src = (u ? (const uint8_t*)Q.w_sp + 500 * (SEQ * 2) + 2048 : (const uint8_t*)Q.w_in + 100 * (2 * FH * 2) + FH * 2) + lane * 16;
            const uint4 a = ldnc128(src), b = ldnc128(src + 300 * (2 * FH * 2) + 2048);
            const uint32_t x[8] = {a.x, a.y, a.z, a.w, b.x, b.y, b.z, b.w};
            float sq = 0.f;
#pragma unroll
            for (int e = 0; e < 8; e++) sq = fmaf(blo(x[e]), blo(x[e]), fmaf(bhi(x[e]), bhi(x[e]), sq));
            o0 = o1;
            asm("sqrt.approx.f32 %0, %1;" : "=f"(o1) : "f"(wsum(sq) * (u ? C0S * C0S * SEQ / 512.f : 2.f * GA * GA * DM / 512.f)));
          }
          const uint32_t off = (__float_as_uint(o0) & 0x7f800000u) >> 16 | 0x8000u | OFM;
          const uint32_t c0 = min(max(__float_as_uint(o1) & 0x7f800000u, 0x04000000u), 0x7e000000u) | 0x00400000u;
          if (el) sts128(sb + SM_OFF, off * 0x10001u, c0, __float_as_uint(GB), ((c0 >> 16) - 0x200u) * 0x10001u);
        }
        mbar_wait(bars + B_EVT + EV_O * 8, L);
        mbar_wait(bars + B_EVT + (EV_N + EV_O) * 8, L);
        flag_release_p(el, Q.flags + rb * 64 + FR_OL + L);
#pragma unroll 1
        for (int w = 0; w < 2; w++) {
          mbar_wait(bars + B_EVT + (w * EV_N + EV_XS) * 8, L);
          if (!w) mbar_wait(bars + B_AF3 + 96 + XP0 * 8, L);
          if (el) asm volatile("cp.async.bulk.tensor.3d.global.shared::cta.tile.bulk_group [%0, {%2, %3, %4}], [%1];\ncp.async.bulk.commit_group;\ncp.async.bulk.wait_group.read 0;" ::"l"(&P.res[1]), "r"(sb + SM_STG + 9216), "r"(j * 72), "r"(rb * 64 + (w ^ 1) * 32), "r"(0) : "memory");
          __syncwarp();
          if (lane < 2 && !w) mbar_arrive(bars + B_S5);
        }
        sts64(sb + SM_CV + 512 + lane * 8, 0x3f803f80u, 0x3f803f80u);
        fence_async_s();
        __syncwarp();
        if (el) { asm volatile("cp.async.bulk.wait_group 0;" ::: "memory"); mbar_arrive(bars + B_GATE3); }
        const uint32_t tag = epoch * 2 + L + 1;
        asm volatile("" : "+r"(lane));
#pragma unroll 1
        for (int b = 0; b < 8; b++) {
          if (!(b & 3)) {
            const int mb = b >> 2;
            mbar_wait(bars + B_ZS + mb * 8, L);
            pause<ZD1>(Q.zero);
            TRC(el && !mb, 2, L * 16 + 8);
            uint4 v;
#pragma unroll 1
            for (int it = 0; it < (1 << 22); it++) {
              v = ll_ld128(Q.ZST + ((rb * 2 + mb) * 8 + (lane >> 2)) * 32 + 4 * j + (lane & 3));
              if (__all_sync(~0u, max(max(v.x, v.y), max(v.z, v.w)) != ~0u)) break;
            }
            const bool o = lane & 16;
            float ss = __uint_as_float(o ? v.y : v.x) + __shfl_xor_sync(~0u, __uint_as_float(o ? v.x : v.y), 16), sq = __uint_as_float(o ? v.w : v.z) + __shfl_xor_sync(~0u, __uint_as_float(o ? v.z : v.w), 16);
            ss += __shfl_xor_sync(~0u, ss, 4); sq += __shfl_xor_sync(~0u, sq, 4); ss += __shfl_xor_sync(~0u, ss, 8); sq += __shfl_xor_sync(~0u, sq, 8);
            const float mean = ss * (1.f / FH), rs = blo(pack2(rsq_fast(fmaxf(fmaf(sq, 1.f / FH, -mean * mean), 0.f) + 4.f * GA * GA * LN_EPS), 0.f));
            if (!(lane & 12)) ll_st64(Q.RT + (mb * 16 + rb) * 64 + 8 * j + 2 * (lane & 3) + (lane >> 4), pack2(rs, rs * (mean - blo(lds32(sb + SM_OFF)))), tag);
            TRC(el && !mb, 2, L * 16 + 10);
            pause<ZD2>(Q.zero);
          }
          uint4 v[4];
#pragma unroll 1
          for (int it = 0; it < (1 << 22); it++) {
            bool ok = true;
#pragma unroll
            for (int u = 0; u < 4; u++) { v[u] = ll_ld128((const uint4*)Q.RT + b * 128 + u * 32 + lane); ok = ok && v[u].y == tag && v[u].w == tag; }
            if (__all_sync(~0u, ok)) break;
          }
#pragma unroll
          for (int u = 0; u < 4; u++) {
            const uint32_t rt = sb + SM_RT + b * 512 + u * 128, ro = (lane >> 3) * 32 + (lane & 3) * 8 + ((lane >> 2) & 1) * 2;
            sts32(rt + 4096 + lane * 4, __byte_perm(v[u].x, v[u].z, 0x7632));
            asm volatile("st.shared.u16 [%0], %1;\nst.shared.u16 [%0 + 4], %2;" ::"r"(rt + ro), "h"((uint16_t)v[u].x), "h"((uint16_t)v[u].z) : "memory");
          }
          __syncwarp();
          if (el && (b & 1)) mbar_arrive(bars + B_RT + (b - 1) * 4);
          TRC(el && b < 2, 2, L * 16 + 11 + b);
        }
        TRC(el, 2, L * 16 + 9);
        mbar_wait(bars + B_EVT + EV_Z1 * 8, L);
        mbar_wait(bars + B_EVT + (EV_N + EV_Z1) * 8, L);
        fence_gpu();
        if (el) mbar_arrive(bars + B_Z1);
      }
    }
  } else {
    int w = wid >> 2, q = wid & 3, rb = bid & 15, j = bid >> 4;
    int g = lane >> 2, t = lane & 3;
#define PHASE asm volatile("" : "+r"(w), "+r"(q), "+r"(rb), "+r"(j))
#define stg (sb + SM_STG + w * 9216)
    const bool tr = (tid & 127) == 0;
    (void)tr;
    Cur c{0, 0};
    const uint32_t ebar = mapa(bars + B_EMPTY, (bid & 1) ^ (lane & 1));
    auto release = [&](uint32_t s) { if (lane < 2) mbar_arrive_cluster(ebar + s * 8); };
    uint32_t ia = 0;
    auto wait_ab = [&]() { mbar_wait_c(bars + B_FULL + c.s * 8, c.ph); mbar_wait_c(bars + B_FULLA + w * 32 + c.s * 8, (ia >> c.s) & 1); ia ^= 1u << c.s; };
    uint32_t lagph = 0;
    auto yield = [&](int left, int lag) { if (w == 1 && left == lag) mbar_wait_c(bars + B_LAG, lagph); };
    auto yield_done = [&]() { if (w == 0 && lane == 0) mbar_arrive(bars + B_LAG); };
    uint32_t rp = 0;
    auto check = [&](auto n, uint32_t dst, const uint8_t* src) {
      const uint32_t a = dst + lane * 32 + (lane >> 2) * 4;
#pragma unroll 1
      for (int it = 0; it < (1 << 16); it++) {
        uint32_t x = lds32(a);
#pragma unroll
        for (int e = 1; e < n.value; e++) x = max(x, lds32(a + e * 1024));
        if (!__any_sync(~0u, x == ~0u)) break;
        fence_async_s();
        __syncwarp();
        const uint32_t el = elect_one();
        expect_tx_p(el, bars + B_RB + q * 8, n.value * 1024);
        bulk_load_p(el, dst, src, n.value * 1024, bars + B_RB + q * 8);
        mbar_wait_c(bars + B_RB + q * 8, rp & 1);
        rp++;
      }
    };
    auto signal = [&](int e) { __syncwarp(); if (lane == 0) mbar_arrive(bars + B_EVT + w * EV_N * 8 + e * 8); };
    TRC(tr, w, 0);

    {
      uint8_t* dst = Q.WQ + j * WQ_SL + rb * 3456 + tid * 16;
#pragma unroll
      for (int u = 0; u < 5; u++) {
        stg128_if((u < 4 || rb < 8) && tid < 216, dst + u * (16 * 3456), wv[u].x, wv[u].y, wv[u].z, wv[u].w);
        if (u == 0) TRC(tr, w, 60);
      }
      if (Q.zero == 0) {
        float s[8];
#pragma unroll
        for (int u = 0; u < 5; u++) {
          const uint32_t x[4] = {wv[u].x, wv[u].y, wv[u].z, wv[u].w};
#pragma unroll
          for (int e = 0; e < 4; e++) { s[2 * e] = u ? s[2 * e] + blo(x[e]) : blo(x[e]); s[2 * e + 1] = u ? s[2 * e + 1] + bhi(x[e]) : bhi(x[e]); }
        }
#pragma unroll
        for (int m = 4; m; m >>= 1) {
#pragma unroll
          for (int e = 0; e < m; e++) s[e] = ((tid & m) ? s[e + m] : s[e]) + __shfl_xor_sync(~0u, (tid & m) ? s[e] : s[e + m], m);
        }
        stg32_if(tid < 216, Q.CSP + bid * 216 + tid, __float_as_uint(s[0]));
      }
      __syncwarp();
      if (lane == 0) mbar_arrive(bars + B_IMG);
    }
    reg_alloc<224>();
    auto fetch_wo = [&]() {
#pragma unroll 1
      for (int u = tid; u < 328; u += 256) {
        const int m = min(41 * rb + (u >> 3), 647), k8 = m / 9;
        cp_async16(sb + SM_WOI + u * 16, (const uint8_t*)Q.wo + (8 * k8 + (u & 7)) * (DM * 2) + (72 * j + 8 * (m - k8 * 9)) * 2);
      }
    };
    const uint32_t epoch = ldcg32(Q.flags + (rb * 2 + w) * 32 + FR_EP + j);
    TRC(tr, w, 1);

#pragma unroll 1
    for (int L = 0; L < 2; L++) {
      const int tb = 2 + L * 24;
      asm volatile("" : "+r"(lane), "+r"(g), "+r"(t));
      if (PHM & 1) PHASE;
      (void)tb;
      const uint32_t tag = epoch * 2 + L + 1;
      {
        uint32_t Pk[27][2];
        float rk[2][2], sc[2][2];
        const bool up0 = 2 * t > g, up1 = 2 * t + 1 > g;
        constexpr int HA_[6] = {0, 2, 4, 7, 12, 15}, HC_[6] = {6, 9, 10, 11, 14, 17};
        const bool remote = q == 0 && rb > 0;
        uint4* hp = Q.HALO + ((((rb - (q == 0)) * 2 + w) * 8 + j) * 6) * 32 + lane;
        const uint32_t att = 2 * ST_BYTES + w * 8192 + lane * 16;
        const uint8_t* hs = remote ? (const uint8_t*)hp : smem_raw + att + (q == 3 ? ST_BYTES : q == 2 ? 3072 : 0);
        uint8_t* od = z1_block(rb, (q >> 1) ^ 1, 0) + (9 * j) * 1024 + (4 * (q & 1) + w) * 128 + lane * 4;
        ACLK_INIT;
        {
          float acc[108];
#pragma unroll
          for (int i = 0; i < 108; i++) acc[i] = 0.f;
          float sx[2] = {0.f, 0.f}, sq[2] = {0.f, 0.f};
          uint32_t prev = 0;
#pragma unroll 1
          for (int kb = 0; kb < 7; kb++) {
            wait_ab();
            TRC(tr && kb == 0, w, tb + 0);
            PCLK(kb * 4);
            const uint32_t st = sb + c.s * ST_BYTES, da = dlo(st + w * 8192, 16), db = dlo(st + ST_B, 3456);
            wgmma_fence();
#pragma unroll
            for (int kk = 0; kk < 4; kk++) {
              wgmma_ss_n216(acc, dsc<1024, 1>(da, kk * 32), dsc<128, 0>(db, kk * 6912), 1);
              if (kk == 0) { wgmma_commit(); wgmma_wait<1>(); if (kb > 0) release(prev); }
              if (kk == 3) wgmma_commit();
              if (kk == XK1) {
            if (kb >= KS && kb < KS + 3) {
              mbar_wait_c(bars + B_WT + w * 8, 0);
#pragma unroll
              for (int u = 0; u < 3; u++) {
                const uint2 x = lds64(stg + (2 * q + (lane >> 4)) * 1152 + (lane & 15) * 8 + (kb - KS) * 384 + u * 128);
                sx[0] += blo(x.x) + bhi(x.x); sx[1] += blo(x.y) + bhi(x.y);
                sq[0] = fmaf(blo(x.x), blo(x.x), fmaf(bhi(x.x), bhi(x.x), sq[0])); sq[1] = fmaf(blo(x.y), blo(x.y), fmaf(bhi(x.y), bhi(x.y), sq[1]));
              }
            }
            if (kb == KS + 3) {
              const bool o = lane & 1;
              float v = (o ? sq[0] + sq[1] : sx[0] + sx[1]) + __shfl_xor_sync(~0u, o ? sx[0] + sx[1] : sq[0] + sq[1], 1);
              v += __shfl_xor_sync(~0u, v, 2); v += __shfl_xor_sync(~0u, v, 4); v += __shfl_xor_sync(~0u, v, 8);
              const float m = v * (-1.f / DM), r = rsq_fast(fmaxf(fmaf(__shfl_xor_sync(~0u, v, 1), 1.f / DM, -m * m), 0.f) + LN_EPS);
              ll_st128_if(!(lane & 15), Q.XST + (rb * 2 + w) * 128 + 16 * j + 4 * q + (lane >> 3), m, r, tag);
            }
              }
              if (kk == XK2 && L == 0) {
            if (kb == 0) fetch_wo();
            if (kb == 3) {
              asm volatile("cp.async.wait_all;" ::: "memory");
              fence_async_s();
              __syncwarp();
              if (lane == 0) mbar_arrive(bars + B_WOI);
            }
              }
            }
            prev = c.s; c.next();
          }
          const uint32_t ls = sb + L * (3 * ST_BYTES), cs = ls + SM_CSQ + t * 8;
          float2 cv[27];
          mbar_wait_c(bars + B_XRW + 8, L);
#pragma unroll
          for (int kb = 7; kb < 9; kb++) {
            wait_ab();
            yield(9 - kb, LAG1);
            PCLK(kb * 4);
            const uint32_t st = sb + c.s * ST_BYTES, da = dlo(st + w * 8192, 16), db = dlo(st + ST_B, 3456);
            wgmma_fence();
#pragma unroll
            for (int kk = 0; kk < 4; kk++) {
              wgmma_ss_n216(acc, dsc<1024, 1>(da, kk * 32), dsc<128, 0>(db, kk * 6912), 1);
              if (kk == 0) { wgmma_commit(); wgmma_wait<1>(); release(prev); }
              if (kb == 7 && kk < 3) {
#pragma unroll
                for (int G = 9 * kk; G < 9 * kk + 9; G++) cv[G] = lds64f(cs + G * 32);
                wgmma_fence();
              }
            }
            wgmma_commit();
            prev = c.s; c.next();
          }
          yield_done();
          mbar_wait_c(bars + B_CSQ, L);
          const uint32_t xs = ls + SM_XST + w * 768 + 256 + q * 128;
          const float2 n0 = lds64f(xs + g * 8), n1 = lds64f(xs + g * 8 + 64);
          const float m0 = n0.x, m1 = n1.x;
#pragma unroll
          for (int u = 0; u < 4; u++) {
            rk[u >> 1][u & 1] = __uint_as_float(lds32(xs + t * 16 + ((u & 1 ? up1 : up0) ? -64 : 0) + (u & 1) * 8 + (u >> 1) * 64 + 4));
            sc[u >> 1][u & 1] = rk[u >> 1][u & 1] * ((u >> 1 ? n1.y : n0.y) * (0.23570226039551584f * 1.4426950408889634f));
          }
          PCLK(36);
          wgmma_wait<0>();
          PCLK(37);
          release(prev);
          lagph ^= 1;
          TRC(tr, w, tb + 1);
          ACLK(0);
#pragma unroll
          for (int G = 9; G < 27; G++) Pk[G][1] = pack2(fmaf(m1, cv[G].x, acc[4 * G + 2]), fmaf(m1, cv[G].y, acc[4 * G + 3]));
          if (q < 3) {
#pragma unroll
            for (int i = 0; i < 6; i++) sts128(sb + att + (q >> 1) * ST_BYTES + (q & 1) * 3072 + i * 512, Pk[9 + HA_[i]][1], Pk[10 + HA_[i]][1], tag, Pk[9 + HC_[i]][1]);
          } else if (rb < 15) {
#pragma unroll
            for (int i = 0; i < 6; i++) ll_st128(hp + i * 32, __uint_as_float(Pk[9 + HA_[i]][1]), __uint_as_float(Pk[10 + HA_[i]][1]), tag, __uint_as_float(Pk[9 + HC_[i]][1]));
          }
#pragma unroll
          for (int G = 0; G < 27; G++) {
            Pk[G][0] = pack2(fmaf(m0, cv[G].x, acc[4 * G]), fmaf(m0, cv[G].y, acc[4 * G + 1]));
            if (G < 9) Pk[G][1] = pack2(fmaf(m1, cv[G].x, acc[4 * G + 2]), fmaf(m1, cv[G].y, acc[4 * G + 3]));
          }
        }
        ACLK(1);
        constexpr int GA_[4] = {0, 2, 4, 7}, GB_[4] = {1, 3, 5, 8}, GC_[4] = {2, 4, 6, 6};
        float S1[4][4], S2[4][4];
        uint32_t qa[4][2], qc[4][2];
#pragma unroll
        for (int h = 0; h < 4; h++) {
#pragma unroll
          for (int r = 0; r < 2; r++) {
            qa[h][r] = (h == 0 || h == 3 || t >= h) ? Pk[GA_[h]][r] : 0u;
            qc[h][r] = (h == 3 ? t == 3 : t <= h) ? Pk[GC_[h]][r] : 0u;
          }
#pragma unroll
          for (int i = 0; i < 4; i++) S1[h][i] = S2[h][i] = 0.f;
          mma16(S1[h], qa[h][0], qa[h][1], Pk[GB_[h]][0], Pk[GB_[h]][1], Pk[9 + GA_[h]][0], Pk[9 + GB_[h]][0]);
          mma16(S2[h], qa[h][0], qa[h][1], Pk[GB_[h]][0], Pk[GB_[h]][1], Pk[9 + GA_[h]][1], Pk[9 + GB_[h]][1]);
        }
#pragma unroll
        for (int h = 0; h < 4; h++) {
          mma8(S1[h], qc[h][0], qc[h][1], Pk[9 + GC_[h]][0]);
          mma8(S2[h], qc[h][0], qc[h][1], Pk[9 + GC_[h]][1]);
        }
        uint32_t V1[9], V2[9];
#pragma unroll
        for (int i = 0; i < 9; i++) { V1[i] = movm(Pk[18 + i][0]); V2[i] = movm(Pk[18 + i][1]); }
        uint4 hv[6];
#pragma unroll
        for (int i = 0; i < 6; i++) hv[i] = ll_ld128g(hs + i * 512);
        const uint32_t mup = (up0 ? 0xffffu : 0u) | (up1 ? 0xffff0000u : 0u);
        auto finish = [&](const float (&x0)[4], const float (&x1)[4], const uint32_t (&Vb)[9], uint32_t ma, int hi) {
          uint32_t p[4], n[4];
          float rs[4];
#pragma unroll
          for (int h = 0; h < 4; h++) {
            const float m = qmax(fmaxf(x0[h], x1[h])), e0 = ex2(x0[h] - m), e1 = ex2(x1[h] - m);
            n[h] = pack2(e0, e1);
            p[h] = pack2(e0 * rk[hi][0], e1 * rk[hi][1]);
          }
#pragma unroll
          for (int h = 0; h < 4; h += 2) {
            float D[4] = {0.f, 0.f, 0.f, 0.f};
            mma8(D, n[h], n[h + 1], 0x3f803f80u);
            rs[h] = rcp_fast(D[0]); rs[h + 1] = rcp_fast(D[2]);
          }
#pragma unroll
          for (int i = 0; i < 9; i++) {
            const int h = i < 4 ? 0 : i == 4 ? 1 : 2;
            const bool nx = (i == 2 || i == 4 || i == 6) ? 2 * t >= i : i == 3 || i > 6;
            float O[4] = {0.f, 0.f, 0.f, 0.f};
            mma16(O, p[h] & ma, p[h + 1] & ma, p[h] & ~ma, p[h + 1] & ~ma, V1[i], Vb[i]);
            const float r = nx ? rs[h + 1] : rs[h];
            stg32(od + i * 1024 + hi * 256, pack2((nx ? O[2] : O[0]) * r, (nx ? O[3] : O[1]) * r));
          }
        };
        {
          float x0[4], x1[4];
#pragma unroll
          for (int h = 0; h < 4; h++) { x0[h] = (up0 ? S1[h][2] : S2[h][2]) * sc[1][0]; x1[h] = (up1 ? S1[h][3] : S2[h][3]) * sc[1][1]; }
          finish(x0, x1, V2, mup, 1);
        }
        ACLK(2);
        bar_sync(1 + w, 128);
#pragma unroll 1
        for (int it = 0; it < (1 << 20); it++) {
          if (remote) {
            bool ok = true;
#pragma unroll
            for (int i = 0; i < 6; i++) ok = ok && hv[i].z == tag;
            if (__all_sync(~0u, ok)) break;
          }
#pragma unroll
          for (int i = 0; i < 6; i++) hv[i] = ll_ld128g(hs + i * 512);
          if (!remote) break;
        }
        uint32_t H[18];
#pragma unroll
        for (int i = 0; i < 6; i++) { H[HA_[i]] = hv[i].x; H[HA_[i] + 1] = hv[i].y; H[HC_[i]] = hv[i].w; }
        float S0[4][4];
#pragma unroll
        for (int h = 0; h < 4; h++) {
#pragma unroll
          for (int i = 0; i < 4; i++) S0[h][i] = 0.f;
          mma16(S0[h], qa[h][0], qa[h][1], Pk[GB_[h]][0], Pk[GB_[h]][1], H[GA_[h]], H[GB_[h]]);
        }
#pragma unroll
        for (int h = 0; h < 4; h++) mma8(S0[h], qc[h][0], qc[h][1], H[GC_[h]]);
        uint32_t V0[9];
#pragma unroll
        for (int i = 0; i < 9; i++) V0[i] = movm(H[9 + i]);
        ACLK(3);
        {
          const bool nohalo = (rb | q) == 0;
          const float b0 = up0 && nohalo ? -INFINITY : 0.f, b1 = up1 && nohalo ? -INFINITY : 0.f;
          float x0[4], x1[4];
#pragma unroll
          for (int h = 0; h < 4; h++) { x0[h] = fmaf(up0 ? S0[h][0] : S1[h][0], sc[0][0], b0); x1[h] = fmaf(up1 ? S0[h][1] : S1[h][1], sc[0][1], b1); }
          finish(x0, x1, V0, ~mup, 0);
        }
        ACLK(4);
        __syncwarp();
        if (lane == 0) mbar_arrive(bars + B_EVT + (EV_N * (q < 2) + EV_O) * 8);
        ACLK_OUT;
        TRC(tr, w, tb + 2);
      }
      if (c.s) { c.s = 0; c.ph ^= 1; }
      if (PHM & 2) PHASE;
      {
        float acc[36];
        const int hw = rb * 2 + w;
        const uint32_t xt = stg + (8 * q + g) * 144 + t * 4;
        uint32_t xm = sb + SM_STG + 9216 + (8 * q + (lane & 7)) * 144 + (lane & 8) * 576 + (lane & 16);
        uint8_t* xn = xn_block(hw) + j * 9216 + q * 256 + lane * 4;
        uint32_t* sp = (uint32_t*)(Q.ST1 + (hw * 8 + j) * 32 + 8 * q) + lane;
        const uint4* sg = Q.ST1 + (hw * 8 + t) * 32 + 8 * q + g;
        asm volatile("" : "+r"(xm), "+l"(xn), "+l"(sp), "+l"(sg));
        mbar_wait_c(bars + B_RES + w * 8, L);
        TRC(tr, w, tb + 21);
#pragma unroll
        for (int i = 0; i < 18; i++) { const uint32_t x = lds32(xt + (i >> 1) * 16 + (i & 1) * 4608); acc[2 * i] = blo(x); acc[2 * i + 1] = bhi(x); asm volatile("" : "+f"(acc[2 * i]), "+f"(acc[2 * i + 1])); }
        mbar_wait_c(bars + B_WF, L);
        const uint32_t db = dlo(sb, 1152), of = bars + (w ? B_OF + 40 : B_AV + 96);
        uint32_t da[5];
#pragma unroll
        for (int e = 0; e < 5; e++) da[e] = __shfl_sync(~0u, dlo(sb + o_place(w, e), 1024), 0);
        if (w) {
#pragma unroll 1
          for (int kb = q ^ 2; kb < 9; kb += 4) {
            const uint32_t e = (kb + 1) >> 1;
            mbar_wait_c(bars + B_OF + e * 8, L);
            check(Int<8>{}, sb + o_place(0, e) + (kb && !(kb & 1)) * 8192, z1_block(rb, 0, 0) + kb * 8192);
            if (lane <= !kb) mbar_arrive(bars + B_AV + (12 + e) * 8);
          }
          bar_sync(7, 256);
        }
        mbar_wait_c(of, L & w);
        TRC(tr, w, tb + 3);
        wgmma_fence();
#pragma unroll
        for (int kk = 0; kk < 4; kk++) wgmma_ss_n72(acc, dsc<128, 0>(da[0], kk * 2048), dsc<128, 0>(db, kk * 2304), 1);
        wgmma_commit();
#pragma unroll 1
        for (int h = 0; h < 2; h++) {
#pragma unroll
          for (int u = 0; u < 4; u++) {
            if (!(u & 1)) { mbar_wait_c(of + 8 + h * 16 + u * 4, 1 + 2 * h + (u >> 1) < SPL ? L & w : L); wgmma_fence(); }
            if (u == 3 && h && !w) bar_arrive(7, 256);
#pragma unroll
            for (int kk = 0; kk < 4; kk++) wgmma_ss_n72(acc, dsc<128, 0>(da[1 + (u >> 1)], (u & 1) * 8192 + kk * 2048), dsc<128, 0>(db + h * 2304, (1 + u) * 9216 + kk * 2304), 1);
            if (u != 2) wgmma_commit();
            if (u == 0) { wgmma_wait<1>(); if (lane + w == 0 && h) mbar_arrive(bars + B_X3); }
          }
          da[1] = da[3]; da[2] = da[4];
        }
        RCLK_INIT;
        wgmma_wait<0>();
        RCLK(0);
        if (lane < 2) mbar_arrive_cluster(ebar + B_XD - B_EMPTY + w * 8);
        TRC(tr && P5TRACE != 5, w, tb + 4);
        {
          float s0 = 0.f, s1 = 0.f, q0 = 0.f, q1 = 0.f;
#pragma unroll
          for (int i = 0; i < 36; i++) {
            if (i & 2) { s1 += acc[i]; q1 = fmaf(acc[i], acc[i], q1); } else { s0 += acc[i]; q0 = fmaf(acc[i], acc[i], q0); }
          }
          const bool o1 = t & 1, o2 = t & 2;
          const float ss = (o1 ? s1 : s0) + __shfl_xor_sync(~0u, o1 ? s0 : s1, 1), sq = (o1 ? q1 : q0) + __shfl_xor_sync(~0u, o1 ? q0 : q1, 1);
          const float v = (o2 ? sq : ss) + __shfl_xor_sync(~0u, o2 ? ss : sq, 2);
          asm volatile("st.relaxed.gpu.global.u32 [%0], %1;" ::"l"(sp), "r"(__float_as_uint(v)) : "memory");
        }
        RCLK(1);
        RCLK(2);
        pause<PDEL>(Q.zero);
        uint4 pa, pb;
        auto there = [&](const uint4& a, const uint4& b) { return __all_sync(~0u, max(max(max(a.x, a.y), max(a.z, a.w)), max(max(b.x, b.y), max(b.z, b.w))) != ~0u); };
#pragma unroll 1
        for (int it = 0; it < (1 << 20); it++) {
          pa = ll_ld128(sg); pb = ll_ld128(sg + 128);
          if (there(pa, pb)) break;
        }
        RCLK(3);
        float mean0 = qsum(__uint_as_float(pa.x) + __uint_as_float(pb.x)) * (-1.f / DM), mean1 = qsum(__uint_as_float(pa.y) + __uint_as_float(pb.y)) * (-1.f / DM);
        const float rs0 = GA * rsq_fast(fmaxf(fmaf(qsum(__uint_as_float(pa.z) + __uint_as_float(pb.z)), 1.f / DM, -mean0 * mean0), 0.f) + LN_EPS);
        const float rs1 = GA * rsq_fast(fmaxf(fmaf(qsum(__uint_as_float(pa.w) + __uint_as_float(pb.w)), 1.f / DM, -mean1 * mean1), 0.f) + LN_EPS);
        mean0 *= rs0; mean1 *= rs1;
#pragma unroll
        for (int i = 0; i < 18; i++) {
          const float a = (i & 1) ? rs1 : rs0, b = (i & 1) ? mean1 : mean0;
          stg32(xn + (i >> 1) * 1024 + (i & 1) * 128, pack2(fmaf(acc[2 * i], a, b), fmaf(acc[2 * i + 1], a, b)));
        }
        signal(EV_X1);
        RCLK(4);
        if (w) {
#pragma unroll 1
          for (int u = q; u < 24; u += 4) {
            const uint32_t mb = u < 2 * SPL ? u >= SPL : u & 1, k = u < 2 * SPL ? u - mb * SPL : u >> 1;
            mbar_wait_c(bars + B_AF3 + mb * 96 + k * 8, L);
            SCLK3(u);
            check(Int<6>{}, sb + k * 12288 + mb * 6144, xn_block(rb * 2 + mb) + k * 6144);
            SCLK3(24 + u);
            if (lane <= (u < 2 * SPL)) mbar_arrive(bars + B_AV + (u < SPL ? 12 + k : k) * 8);
          }
          TRVI(lane == 0 && P5TRACE != 5, 5, 56 + L * 4 + q, rp);
          mbar_wait_c(bars + B_S5, L);
        }
#pragma unroll
        for (int u = 0; u < 4; u++)
          stsm4(xm + u * 32, pack2(acc[8 * u], acc[8 * u + 1]), pack2(acc[8 * u + 2], acc[8 * u + 3]), pack2(acc[8 * u + 4], acc[8 * u + 5]), pack2(acc[8 * u + 6], acc[8 * u + 7]));
        asm volatile("stmatrix.sync.aligned.m8n8.x2.shared.b16 [%0], {%1,%2};" ::"r"(xm + 128), "r"(pack2(acc[32], acc[33])), "r"(pack2(acc[34], acc[35])) : "memory");
        fence_async_s();
        signal(EV_XS);
        RCLK(5);
        TRC(tr, w, tb + 5);
        RCLK(6);
        RCLK_OUT;
      }
      if (PHM & 4) PHASE;
      {
      float acc[160];
#pragma unroll
      for (int i = 0; i < 160; i++) acc[i] = 0.f;
      float s[2] = {0.f, 0.f}, qq[2] = {0.f, 0.f}, zo = 0.f;
      const uint32_t zp = sb + SM_ZP3 + (tid & 127) * 4;
      auto zstat = [&](int mb, bool on) {
        const bool o1 = t & 1, o2 = t & 2;
        const float ss = ((o1 ? s[1] : s[0]) + __shfl_xor_sync(~0u, o1 ? s[0] : s[1], 1)) * 0x1p60f, sq = (o1 ? qq[1] : qq[0]) + __shfl_xor_sync(~0u, o1 ? qq[0] : qq[1], 1);
        const uint32_t v = __float_as_uint((o2 ? sq : ss) + zo + __shfl_xor_sync(~0u, o2 ? ss : sq, 2));
        asm volatile("{\n.reg .pred p, q, r;\nsetp.eq.u32 p, %4, 1;\nsetp.eq.u32 q, %4, 2;\nsetp.eq.and.u32 r, %5, 0, q;\n@p st.shared.u32 [%0], %2;\n@p bar.arrive 13, 256;\n"
                     "@q st.relaxed.gpu.global.u32 [%1], %2;\n@r mbarrier.arrive.shared::cta.b64 _, [%3];\n}" ::"r"(zp + mb * 512), "l"((uint32_t*)(Q.ZST + ((rb * 2 + mb) * 8 + j) * 32) + (tid & 127)),
                     "r"(v), "r"(bars + B_ZS + mb * 8), "r"(on ? 1 + w : 0), "r"(lane) : "memory");
        s[0] = s[1] = qq[0] = qq[1] = 0.f;
      };
      const uint32_t ebar3 = ebar + (B_E3 - B_EMPTY);
#pragma unroll 1
      for (int half = 0; half < 2; half++) {
        const bool big = half != w;
        auto rel3 = [&](int p) { if (lane < 2) mbar_arrive_cluster(ebar3 + p * 8); };
        auto pass = [&](auto nk) {
          constexpr int NK = nk.value;
          uint32_t d0 = dlo(sb, 1024), ph = half & ~w, af = bars + B_AV;
          const uint32_t db = dlo(sb + SM_B3, NK == 3 ? 6144 : 2048);
          const bool lead = NK == 3 && !half;
          if (lead) {
#pragma unroll
            for (int u = 0; u < 2 * SPL; u++) {
              const int mb = u / SPL, p = u % SPL;
              if (!mb) mbar_wait_c(bars + B_F3 + p * 8, 0);
              mbar_wait_c(af + (mb ? p : 12 + p) * 8, mb || p > 4 ? L : 1);
              TRC(tr && u == 0, w, tb + 6);
              SCLK2(u);
              if (p == 0) SCLK(mb * 4);
              wgmma_fence();
#pragma unroll
              for (int kk = 0; kk < 3; kk++) {
                wgmma_ss_n128(acc + mb * 80, dsc<128, 0>(d0, p * 12288 + kk * 2048 + mb * 6144), dsc<1024, 1>(db, p * 12288 + kk * 2048), p + kk > 0);
                if (kk == 0 && u > SPL) { wgmma_commit(); wgmma_wait<1>(); rel3(p - 1); }
              }
              wgmma_commit();
            }
          }
#pragma unroll 1
          for (int it = 0; it < 6 / NK; it++) {
#pragma unroll
            for (int p = 0; p < 6; p++) {
              if (p < SPL && lead && it == 0) continue;
              if (NK == 3) mbar_wait_c(af + p * 8, L);
              if (p == 0 && it == 0) bar_sync(6 + w, 256);
              mbar_wait_c(bars + B_F3 + p * 8, ph);
              TRC(tr && p == 0 && it == 0, w, tb + 6 + half * 4);
              if (lead) SCLK2(12 + it * 6 + p);
              if (NK == 2 ? !(p & 1) : p % 3 == 0) SCLK(half * 11 + (NK == 2 ? it * 3 + p / 2 : it * 2 + p / 3));
              wgmma_fence();
#pragma unroll
              for (int u = 0; u < 2 * NK; u++) {
                const int kk = u >> 1, mb = u & 1, e = p * NK + kk;
                const uint64_t da = dsc<128, 0>(d0, (e / 3) * 12288 + (e % 3) * 2048 + mb * 6144);
                if (NK == 3) wgmma_ss_n128(acc + mb * 80, da, dsc<1024, 1>(db, p * 12288 + kk * 2048), e > 0 || it > 0);
                else wgmma_ss_n160(acc + mb * 80, da, dsc<1024, 1>(db, p * 12288 + kk * 6144), e > 0 || it > 0);
                if (u == 0) { wgmma_commit(); wgmma_wait<1>(); if (p > 0 || it > 0) rel3((p + 5) % 6); }
                if (p * 8 + u == (NK == 2 ? HO3 : HO4) && it == 6 / NK - 1) bar_arrive(7 - w, 256);
              }
              wgmma_commit();
            }
            d0 += NK * 1536; af += 48;
            ph ^= 1;
          }
        };
        const int go = (j & 1) ? (big ? 0 : 20) : (big ? 16 : 0);
        const float* gbp = (const float*)(smem_raw + SM_OFF + 8);
        asm volatile("" : "+l"(gbp));
        uint8_t* zd = half ? z1_block(rb, 0, j) + go * 1024 + (q & 1) * 2048 + 1024 + (q >> 1) * 512 + lane * 16 : z2_block(rb, j) + q * 9216 + go * 128 + ((g & 3) * 2 + (g >> 2)) * 16 + t * 4;
        asm volatile("" : "+l"(zd));
        if (big) pass(Int<2>{}); else pass(Int<3>{});
        if (w) { bar_sync(13, 256); zo = __uint_as_float(lds32(zp + half * 512)); }
        if (half) zstat(1, true);
        const uint32_t off2 = lds32(sb + SM_OFF);
        wgmma_wait<0>();
        SCLK(half * 11 + 9);
        rel3(5);
        TRC(tr, w, tb + 7 + half * 4);
        auto gelu = [&](auto z2) {
          constexpr int NC = z2.value ? NC2 : NC1;
          float gate[NC], gb = GB, gn = GB;
          uint32_t qa[2][3] = {{0, 0, 0}, {0, 0, 0}};
#pragma unroll
          for (int e = 0; e < NC; e++) gate[e] = GB;
#pragma unroll
          for (int G = 0; G < 20; G++) {
            if (G == 16 && !big) break;
            if (G % (z2.value ? LD2 : LD1) == 0) { gb = gn; if (G < 20 - (z2.value ? LD2 : LD1)) asm volatile("ld.f32 %0, [%1];" : "=f"(gn) : "l"(gbp) : "memory"); }
#pragma unroll
            for (int r = 0; r < 2; r++) {
              float z[2];
              float& gt = gate[(G * 2 + r) % NC];
#pragma unroll
              for (int e = 0; e < 2; e++) {
                const float v = acc[4 * G + 2 * r + e];
                z[e] = fmaf(v, tanh_fast(v * fmaf(v, v, gt)), v);
                if (z2.value) { s[r] = fmaf(z[e], 0x1p-60f, s[r]); qq[r] = fmaf(z[e], z[e], qq[r]); }
              }
              const uint32_t pk = pack2(z[0], z[1]);
              if (z2.value) {
                stg32(zd + G * 128 + r * 4608, hsub2(pk, off2));
                gt = fmaf(qq[r], s[r], gb);
              } else {
                gt = fmaf(__uint_as_float(pk), 0x1p-60f, gb);
                if ((G & 3) == 3) stg128(zd + (G >> 2) * 4096 + r * (8 * ZB), qa[r][0], qa[r][1], qa[r][2], pk);
                else qa[r][G & 3] = pk;
              }
            }
          }
        };
#pragma unroll 1
        for (int mb = 0;; mb++) {
          if (half) gelu(Int<0>{}); else gelu(Int<1>{});
          if (mb) break;
          zstat(0, !half);
#pragma unroll
          for (int i = 0; i < 80; i++) acc[i] = acc[80 + i];
          zd += half ? -1024 : (int)(128 * ZB);
        }
        mbar_wait_c(bars + B_GATE3, L);
        signal(half ? EV_Z1 : EV_ZN);
        SCLK(half * 11 + 10);
        TRC(tr, w, tb + 8 + half * 4);
      }
      }
      if (PHM & 8) PHASE;
      const uint32_t aoff = (w * 64 + q * 16 + (lane & 15)) * 128 + (((lane >> 4) ^ (lane & 7)) << 4);
      uint32_t hA[18][4];
      {
        float acc[144];
        {
          const uint32_t c16 = lds32(sb + SM_OFF + 12), a[4] = {c16, c16, c16, c16};
          wgmma_fence();
          wgmma_rs_n144(acc, a, dsc<0, 0>(dlo(sb + SM_CV + 512, 0), 0), 0);
          wgmma_rs_n144(acc + 72, a, dsc<0, 0>(dlo(sb + SM_CV + 512, 0), 128), 0);
          wgmma_commit();
        }
        uint32_t prev = 0;
        auto stage = [&](int kb, bool odd) {
          mbar_wait_c(bars + B_FULL + c.s * 8, c.ph);
          TRC(tr && kb == 0, w, tb + 13);
          SCLK(22 + kb);
          const uint32_t st = sb + c.s * ST_BYTES, db = dlo(st + ST_B, 4608), rt = sb + SM_RT + kb * 128 + t * 8;
          uint32_t a[4][4];
#pragma unroll
          for (int kk = 0; kk < 4; kk++) {
            uint32_t r[4];
            ldsm4(r, st + (aoff ^ (kk << 5)));
            const uint2 sc = lds64(rt + kk * 32);
            a[kk][0] = hmul2(__byte_perm(r[0], r[2], 0x5410), sc.x); a[kk][2] = hmul2(__byte_perm(r[0], r[2], 0x7632), sc.y);
            a[kk][1] = hmul2(__byte_perm(r[1], r[3], 0x5410), sc.x); a[kk][3] = hmul2(__byte_perm(r[1], r[3], 0x7632), sc.y);
          }
          if (!odd && kb + w == 0) bar_sync(6, 256);
          wgmma_fence();
#pragma unroll
          for (int i = 0; i < 8; i++) {
            const int kk = i & 3, hf = i >> 2;
            wgmma_rs_n144(acc + hf * 72, a[kk], dsc<128, 0>(db, kk * 9216 + hf * 2304), 1);
            if (i == 0) { wgmma_commit(); wgmma_wait<1>(); if (kb) release(prev); }
            if (i == 3) wgmma_commit();
          }
          wgmma_commit();
          prev = c.s; c.next();
        };
#pragma unroll 1
        for (int kb = 0; kb < 32; kb += 2) {
          if (!(kb & 7)) mbar_wait_c(bars + B_RT + kb, L);
          stage(kb, false);
          stage(kb + 1, true);
        }
        mbar_wait_c(bars + B_CV + w * 8, L);
        const float gk = 0.5f / GA;
        const float c1 = __uint_as_float(lds32(sb + SM_OFF + 4));
        const float gb0 = -gk * (c1 + __uint_as_float(lds32(sb + SM_CV + w * 256 + (16 * q + g) * 4))), gb1 = -gk * (c1 + __uint_as_float(lds32(sb + SM_CV + w * 256 + (16 * q + g + 8) * 4)));
        if (w == 1) { mbar_wait_c(bars + B_FULL + c.s * 8, c.ph); release(c.s); c.next(); }
        mbar_wait_c(bars + B_FULL + c.s * 8, c.ph);
        const uint32_t zs = sb + c.s * ST_BYTES + ST_B + (tid & 127) * 16;
        uint4 zl, zh;
#pragma unroll
        for (int u = 0; u < 18; u++) {
          if (u == 0) wgmma_wait<1>();
          if (u == 9) {
            wgmma_wait<0>();
            release(prev);
            if (L == 0) signal(EV_PT);
            TRC(tr, w, tb + 14);
            SCLK(54);
          }
          if (!(u & 1)) { zl = lds128(zs + u * 2048); zh = lds128(zs + u * 2048 + 2048); }
          const uint4 z = (u & 1) ? make_uint4(zl.z, zh.z, zl.w, zh.w) : make_uint4(zl.x, zh.x, zl.y, zh.y);
          hA[u][0] = hmul2(z.x, pack2(fmaf(acc[8 * u], gk, gb0), fmaf(acc[8 * u + 1], gk, gb0)));
          hA[u][1] = hmul2(z.y, pack2(fmaf(acc[8 * u + 2], gk, gb1), fmaf(acc[8 * u + 3], gk, gb1)));
          hA[u][2] = hmul2(z.z, pack2(fmaf(acc[8 * u + 4], gk, gb0), fmaf(acc[8 * u + 5], gk, gb0)));
          hA[u][3] = hmul2(z.w, pack2(fmaf(acc[8 * u + 6], gk, gb1), fmaf(acc[8 * u + 7], gk, gb1)));
        }
        __syncwarp();
        release(c.s);
        c.next();
        if (w == 0) { mbar_wait_c(bars + B_FULL + c.s * 8, c.ph); release(c.s); c.next(); }
        TRC(tr, w, tb + 15);
      }
      {
        CLK_INIT;
        if (w == 1) bar_arrive(6, 256);
        uint4 v[4];
#pragma unroll
        for (int u = 0; u < 4; u++) v[u] = make_uint4(0u, 0u, 0u, 0u);
        uint32_t rl = sb + SM_STG + w * 8192 + q * 2048 + (lane >> 3) * 128 + (((lane & 7) ^ (lane >> 3)) << 4);
        uint8_t* rd = Q.out + (128 * rb + 32 * q + 2 * (lane >> 3) + w) * (DM * 2) + j * 128 + (lane & 7) * 16;
        asm volatile("" : "+r"(rl), "+l"(rd));
        auto send = [&](int u0, int u1) {
#pragma unroll
          for (int u = u0; u < u1; u++)
            asm volatile("red.relaxed.gpu.global.add.noftz.v4.bf16x2 [%0], {%1,%2,%3,%4};" ::"l"(rd + u * (8 * DM * 2)), "r"(v[u].x), "r"(v[u].y), "r"(v[u].z), "r"(v[u].w) : "memory");
        };
#pragma unroll 1
        for (int p = 0; p < 9; p++) {
          float acc[32];
          CLK(0);
          mbar_wait_c(bars + B_FULL + c.s * 8, c.ph);
          const uint32_t db = dlo(sb + c.s * ST_BYTES + ST_B, 0);
          CLK(1);
          bar_sync(6 + w, 256);
          CLK(2);
          wgmma_fence();
#pragma unroll
          for (int kk = 0; kk < 18; kk++) {
            wgmma_rs_n64(acc, hA[kk], dsc<1024, 1>(db, kk * 2048), kk != 0);
            if (kk == PPK && (w == 0 || p < 8)) bar_arrive(7 - w, 256);
          }
          wgmma_commit();
          CLK(3);
          if (p > 0) { send(NOW, 4); rd += p + j == 9 ? -1024 : 128; }
          CLK(5);
          wgmma_wait<0>();
          CLK(4);
          if (L == 0 || p < 5) release(c.s);
          c.next();
          TRC(tr && p == 8, w, tb + 16);
#pragma unroll
          for (int u = 0; u < 4; u++)
            stsm4(sb + SM_STG + (aoff ^ (u << 5)), pack2(acc[8 * u], acc[8 * u + 1]), pack2(acc[8 * u + 2], acc[8 * u + 3]), pack2(acc[8 * u + 4], acc[8 * u + 5]), pack2(acc[8 * u + 6], acc[8 * u + 7]));
          __syncwarp();
#pragma unroll
          for (int u = 0; u < 4; u++) v[u] = lds128(rl + u * 512 ^ (u & 1) << 6);
          send(0, NOW);
        }
        send(NOW, 4);
        TRC(tr, w, tb + 17);
        if (L == 0) signal(EV_PT);
        CLK_OUT;
        TRC(tr, w, tb + 18);
      }
    }
    if ((tid & 127) == 0) Q.flags[(rb * 2 + w) * 32 + FR_EP + j] = epoch + 1;
    if (tid == 0) Q.flags[FJ + j * 32 + FJ_EP + rb] = epoch + 1;
  }
}

typedef CUresult (*EncodeFn)(CUtensorMap*, CUtensorMapDataType, cuuint32_t, void*, const cuuint64_t*, const cuuint64_t*, const cuuint32_t*,
                             const cuuint32_t*, CUtensorMapInterleave, CUtensorMapSwizzle, CUtensorMapL2promotion, CUtensorMapFloatOOBfill);

static void make_map(EncodeFn fn, CUtensorMap* m, const void* ptr, int rank, uint64_t d0, uint64_t d1, uint64_t d2, uint64_t s1, uint64_t s2,
                     uint32_t b0, uint32_t b1, uint32_t b2, CUtensorMapSwizzle swz) {
  cuuint64_t dims[3] = {d0, d1, d2}, strides[2] = {s1, s2};
  cuuint32_t box[3] = {b0, b1, b2}, es[3] = {1, 1, 1};
  fn(m, CU_TENSOR_MAP_DATA_TYPE_BFLOAT16, rank, const_cast<void*>(ptr), dims, strides, box, es, CU_TENSOR_MAP_INTERLEAVE_NONE, swz,
     CU_TENSOR_MAP_L2_PROMOTION_L2_128B, CU_TENSOR_MAP_FLOAT_OOB_FILL_NONE);
}

}

extern "C" void kernel_launch(void* const* d_in, const int* in_sizes, int n_in, void* d_out, int out_size) {
  using namespace mk;
  (void)in_sizes; (void)n_in; (void)out_size;
  static EncodeFn fn = nullptr;
  static Scratch* sc = nullptr;
  if (!fn) {
    cudaDriverEntryPointQueryResult qr;
    cudaGetDriverEntryPoint("cuTensorMapEncodeTiled", (void**)&fn, cudaEnableDefault, &qr);
    cudaGetSymbolAddress((void**)&sc, g_scratch);
    cudaFuncSetAttribute(mega_kernel, cudaFuncAttributeMaxDynamicSharedMemorySize, SM_TOTAL);
  }
  Params p;
  Ptrs a;
  a.x = (const uint8_t*)d_in[0];
  a.wqkv = (const __nv_bfloat16*)d_in[1];
  a.wo = (const __nv_bfloat16*)d_in[2];
  a.w_in = (const __nv_bfloat16*)d_in[4];
  a.w_sp = (const __nv_bfloat16*)d_in[5];
  a.b_sp = (const __nv_bfloat16*)d_in[6];
  a.out = (uint8_t*)d_out;
  a.zero = 0;
  a.WQ = sc->WQ; a.flags = sc->flags; a.CSP = sc->CSP; a.XST = sc->XST; a.HALO = sc->HALO; a.ST1 = sc->ST1; a.ZST = sc->ZST; a.RT = sc->RT; a.Z = sc->Z; a.WO = sc->WO;
  make_map(fn, &p.wsp, a.w_sp, 3, 2048, 1024, 2, 8192, 4096, 64, 64, 2, CU_TENSOR_MAP_SWIZZLE_128B);
  for (int i = 0; i < 2; i++) {
    make_map(fn, &p.act[i], i ? a.out : a.x, 3, DM, 1024, 2, 2304, 1152, 64, 64, 1, CU_TENSOR_MAP_SWIZZLE_128B);
    make_map(fn, &p.row[i], i ? a.out : a.x, 3, 192, 6, 1024, 384, 2304, 192, 3, 8, CU_TENSOR_MAP_SWIZZLE_NONE);
    make_map(fn, &p.res[i], i ? a.out : a.x, 3, DM, 1024, 2, 2304, 1152, 72, 32, 2, CU_TENSOR_MAP_SWIZZLE_NONE);
  }
  for (int i = 0; i < 2; i++) make_map(fn, &p.winb[i], a.w_in + 32 * i, 3, 64, 576, 72 - i, 9216, 128, 64, 16, 3, CU_TENSOR_MAP_SWIZZLE_128B);
  make_map(fn, &p.wins, a.w_in, 3, 64, 576, 72, 9216, 128, 64, 48, 1, CU_TENSOR_MAP_SWIZZLE_128B);
  make_map(fn, &p.wout, d_in[7], 2, 576, 2304, 1, 1152, 0, 64, 144, 1, CU_TENSOR_MAP_SWIZZLE_128B);
  mega_kernel<<<NGRID, 384, SM_TOTAL, cudaStreamPerThread>>>(a, p);
}
```

```cpp
#include <cuda_runtime.h>
#include <cuda.h>
#include <cuda_bf16.h>
#include <stdint.h>

#define MK_TRACE 0
#define MK_DBG 0
#define P5TRACE 0

#define LAG1 1
#define C0S 32.f
#define OFM 0x10u
#define NC2 2
#define NC1 8
#define LD1 4
#define LD2 2
#define PDEL 8
#define SDEL 10
#define ZD1 8
#define ZD2 20
#define FD3 14
#define YPACE 2
#define SPL 3
#define XP0 10
#define APACE 7
#define AEP 2
#define PZI 4
#define RFI 3
#define KS 1
#define XK1 1
#define XK2 2
#define HO3 41
#define HO4 41
#define PPK 17
#define NOW 2
#define WTI 12
#define EFM 0x23333022
#define EF(i) ((((EFM >> (4 * (i))) & 3) == 3) || (((EFM >> (4 * (i))) >> L) & 1))

namespace mk {

constexpr int SEQ = 2048, DM = 576, FH = 2304;
constexpr int NCTA = 128;
constexpr int NGRID = 132;
constexpr uint32_t ZB = 36864;
constexpr uint32_t WQ_SL = 72 * 3456;
constexpr uint32_t WO_SL = 72 * 1152;
constexpr float LN_EPS = 1e-5f;
constexpr float GA = 0.3292034911525734f, GB = 2.423681954311584f;

constexpr uint32_t ST_BYTES = 53248, ST_B = 16384, NST = 4;
constexpr uint32_t SM_STG = NST * ST_BYTES;
constexpr uint32_t SM_BAR = SM_STG + 2 * 9216, B_OFF = 896;
constexpr uint32_t SM_OFF = SM_BAR + B_OFF;
constexpr uint32_t SM_TOTAL = SM_BAR + 1024;
constexpr uint32_t SM_RT = SM_STG + 9216, SM_CV = SM_STG + 17408, SM_WT = SM_STG;
constexpr uint32_t SM_WOI = 44032, SM_CSQ = 49280, SM_XST = 50176;
enum { EV_PT = 0, EV_O = 1, EV_X1 = 2, EV_ZN = 3, EV_Z1 = 4, EV_XS = 5, EV_N = 6 };
constexpr uint32_t B_FULL = 0, B_FULLA = 32, B_RES = 96, B_WT = 112, B_GATE3 = 128, B_Z1 = 136, B_ZOK = 144, B_CV = 152, B_XRW = 168, B_F3 = 184, B_WF = 232, B_OF = 240,
                   B_RT = 320, B_AF3 = 352, B_RB = 544,
                   B_AD = 576, B_S5 = 608, B_AV = 616, B_CSQ = 760,
                   B_LAG = 768, B_X3 = 776, B_ZS = 784, B_EVT = 800,
                   B_IMG = 912, B_WOI = 920, B_E3 = 928, B_XD = 976,
                   B_EMPTY = 992;
constexpr uint32_t SM_B3 = 9 * 16384, SM_ZP3 = SM_STG + 8192;

enum { FR_X2 = 0, FR_O = 1, FR_XR = 5, FR_OL = 7, FR_PZ = 9, FR_EP = 16, FJ = 32 * 32, FJ_WQ = 0, FJ_WO = 1, FJ_ZN = 3, FJ_P4 = 5, FJ_EP = 16, F_N = FJ + 8 * 32 };

struct Scratch {
  alignas(1024) uint32_t flags[F_N];
  alignas(1024) float CSP[2 * NCTA * 216];
  alignas(1024) uint2 RT[SEQ];
  alignas(1024) uint4 XST[2 * SEQ];
  alignas(1024) uint4 ST1[SEQ * 4];
  alignas(1024) uint4 ZST[SEQ * 4];
  alignas(1024) uint4 HALO[32 * 8 * 6 * 32];
  alignas(1024) uint8_t WO[8 * WO_SL];
  alignas(1024) uint8_t WQ[8 * WQ_SL];
  alignas(1024) uint8_t Z[576 * ZB];
};
__device__ Scratch g_scratch;

struct Ptrs {
  const __nv_bfloat16* wqkv;
  uint8_t* WQ;
  uint32_t* flags;
  float* CSP;
  const uint8_t* x;
  uint32_t zero;
  uint4 *XST, *HALO, *ST1, *ZST;
  uint2* RT;
  uint8_t *Z, *WO, *out;
  const __nv_bfloat16 *wo, *w_in, *w_sp, *b_sp;
};
struct Params {
  CUtensorMap wsp, winb[2], wins, wout;
  CUtensorMap act[2];
  CUtensorMap res[2];
  CUtensorMap row[2];
};

__device__ __forceinline__ uint32_t smem_u32(const void* p) { return (uint32_t)__cvta_generic_to_shared(p); }
__device__ __forceinline__ void mbar_init(uint32_t bar, uint32_t cnt) { asm volatile("mbarrier.init.shared::cta.b64 [%0], %1;" ::"r"(bar), "r"(cnt)); }
__device__ __forceinline__ void mbar_arrive(uint32_t bar) { asm volatile("mbarrier.arrive.shared::cta.b64 _, [%0];" ::"r"(bar) : "memory"); }
__device__ __forceinline__ void mbar_wait(uint32_t bar, uint32_t parity) {
  asm volatile(
      "{\n.reg .pred p;\n.reg .u32 c;\nmov.u32 c, 0;\nLAB_WAIT:\n"
      "mbarrier.try_wait.parity.shared::cta.b64 p, [%0], %1;\n@p bra LAB_DONE;\n"
      "add.u32 c, c, 1;\nsetp.lt.u32 p, c, 0x100000;\n@p bra LAB_WAIT;\ntrap;\nLAB_DONE:\n}" ::"r"(bar), "r"(parity)
      : "memory");
}
__device__ __forceinline__ void mbar_wait_c(uint32_t bar, uint32_t parity) {
  asm volatile("{\n.reg .pred p;\nLAB_WAIT:\nmbarrier.try_wait.parity.shared::cta.b64 p, [%0], %1;\n@!p bra LAB_WAIT;\n}" ::"r"(bar), "r"(parity) : "memory");
}
__device__ __forceinline__ void flag_wait(const uint32_t* f, uint32_t target) {
  asm volatile(
      "{\n.reg .pred p;\n.reg .u32 c, v;\nmov.u32 c, 0;\nLAB_WAIT:\n"
      "ld.relaxed.gpu.global.u32 v, [%0];\nsub.u32 v, v, %1;\nsetp.ge.s32 p, v, 0;\n@p bra LAB_DONE;\n"
      "add.u32 c, c, 1;\nsetp.lt.u32 p, c, 0x400000;\n@p bra LAB_WAIT;\ntrap;\nLAB_DONE:\nfence.acquire.gpu;\n}" ::"l"(f), "r"(target)
      : "memory");
}
__device__ __forceinline__ void fence_gpu() { asm volatile("fence.acq_rel.gpu;" ::: "memory"); }
__device__ __forceinline__ void fence_async_g() { asm volatile("fence.proxy.async.global;" ::: "memory"); }
__device__ __forceinline__ void fence_async_s() { asm volatile("fence.proxy.async.shared::cta;" ::: "memory"); }
__device__ __forceinline__ uint32_t elect_one() {
  uint32_t p; asm volatile("{\n.reg .pred P;\nelect.sync _|P, 0xffffffff;\nselp.u32 %0, 1, 0, P;\n}" : "=r"(p)); return p;
}
__device__ __forceinline__ void expect_tx_p(uint32_t el, uint32_t bar, uint32_t bytes) {
  asm volatile("{\n.reg .pred P;\nsetp.ne.u32 P, %2, 0;\n@P mbarrier.arrive.expect_tx.shared::cta.b64 _, [%0], %1;\n}" ::"r"(bar), "r"(bytes), "r"(el) : "memory");
}
__device__ __forceinline__ void bulk_load_p(uint32_t el, uint32_t dst, const void* src, uint32_t bytes, uint32_t bar) {
  asm volatile("{\n.reg .pred P;\nsetp.ne.u32 P, %4, 0;\n@P cp.async.bulk.shared::cluster.global.mbarrier::complete_tx::bytes [%0], [%1], %2, [%3];\n}" ::"r"(dst), "l"(src), "r"(bytes), "r"(bar), "r"(el) : "memory");
}
__device__ __forceinline__ uint64_t policy_evict_first() { uint64_t p; asm("createpolicy.fractional.L2::evict_first.b64 %0, 1.0;" : "=l"(p)); return p; }
__device__ __forceinline__ void bulk_load_h(uint32_t el, uint32_t dst, const void* src, uint32_t bytes, uint32_t bar, bool ef, uint64_t pol) {
  if (ef) {
    asm volatile("{\n.reg .pred P;\nsetp.ne.u32 P, %4, 0;\n@P cp.async.bulk.shared::cluster.global.mbarrier::complete_tx::bytes.L2::cache_hint [%0], [%1], %2, [%3], %5;\n}" ::"r"(dst), "l"(src), "r"(bytes), "r"(bar), "r"(el), "l"(pol) : "memory");
  } else {
    asm volatile("{\n.reg .pred P;\nsetp.ne.u32 P, %4, 0;\n@P cp.async.bulk.shared::cluster.global.mbarrier::complete_tx::bytes [%0], [%1], %2, [%3];\n}" ::"r"(dst), "l"(src), "r"(bytes), "r"(bar), "r"(el) : "memory");
  }
}
__device__ __forceinline__ void bulk_mc_h(uint32_t el, uint32_t dst, const void* src, uint32_t bytes, uint32_t bar, bool ef, uint64_t pol) {
  if (ef) {
    asm volatile("{\n.reg .pred P;\nsetp.ne.u32 P, %4, 0;\n@P cp.async.bulk.shared::cluster.global.mbarrier::complete_tx::bytes.multicast::cluster.L2::cache_hint [%0], [%1], %2, [%3], %5, %6;\n}" ::"r"(dst), "l"(src), "r"(bytes), "r"(bar), "r"(el), "h"((uint16_t)3), "l"(pol) : "memory");
  } else {
    asm volatile("{\n.reg .pred P;\nsetp.ne.u32 P, %4, 0;\n@P cp.async.bulk.shared::cluster.global.mbarrier::complete_tx::bytes.multicast::cluster [%0], [%1], %2, [%3], %5;\n}" ::"r"(dst), "l"(src), "r"(bytes), "r"(bar), "r"(el), "h"((uint16_t)3) : "memory");
  }
}
__device__ __forceinline__ void tma3d_h(uint32_t el, uint32_t dst, const CUtensorMap* m, int c0, int c1, int c2, uint32_t bar, bool ef, uint64_t pol) {
  if (ef) {
    asm volatile("{\n.reg .pred P;\nsetp.ne.u32 P, %6, 0;\n@P cp.async.bulk.tensor.3d.shared::cluster.global.mbarrier::complete_tx::bytes.L2::cache_hint [%0], [%1, {%3, %4, %5}], [%2], %7;\n}" ::"r"(dst), "l"(m), "r"(bar), "r"(c0), "r"(c1), "r"(c2), "r"(el), "l"(pol) : "memory");
  } else {
    asm volatile("{\n.reg .pred P;\nsetp.ne.u32 P, %6, 0;\n@P cp.async.bulk.tensor.3d.shared::cluster.global.mbarrier::complete_tx::bytes [%0], [%1, {%3, %4, %5}], [%2];\n}" ::"r"(dst), "l"(m), "r"(bar), "r"(c0), "r"(c1), "r"(c2), "r"(el) : "memory");
  }
}
__device__ __forceinline__ void tma2d_mc_h(uint32_t el, uint32_t dst, const CUtensorMap* m, int c0, int c1, uint32_t bar, bool ef, uint64_t pol) {
  if (ef) {
    asm volatile("{\n.reg .pred P;\nsetp.ne.u32 P, %5, 0;\n@P cp.async.bulk.tensor.2d.shared::cluster.global.mbarrier::complete_tx::bytes.multicast::cluster.L2::cache_hint [%0], [%1, {%3, %4}], [%2], %6, %7;\n}" ::"r"(dst), "l"(m), "r"(bar), "r"(c0), "r"(c1), "r"(el), "h"((uint16_t)3), "l"(pol) : "memory");
  } else {
    asm volatile("{\n.reg .pred P;\nsetp.ne.u32 P, %5, 0;\n@P cp.async.bulk.tensor.2d.shared::cluster.global.mbarrier::complete_tx::bytes.multicast::cluster [%0], [%1, {%3, %4}], [%2], %6;\n}" ::"r"(dst), "l"(m), "r"(bar), "r"(c0), "r"(c1), "r"(el), "h"((uint16_t)3) : "memory");
  }
}
__device__ __forceinline__ void tma3d_mc_h(uint32_t el, uint32_t dst, const CUtensorMap* m, int c0, int c1, int c2, uint32_t bar, bool ef, uint64_t pol) {
  if (ef) {
    asm volatile("{\n.reg .pred P;\nsetp.ne.u32 P, %6, 0;\n@P cp.async.bulk.tensor.3d.shared::cluster.global.mbarrier::complete_tx::bytes.multicast::cluster.L2::cache_hint [%0], [%1, {%3, %4, %5}], [%2], %7, %8;\n}" ::"r"(dst), "l"(m), "r"(bar), "r"(c0), "r"(c1), "r"(c2), "r"(el), "h"((uint16_t)3), "l"(pol) : "memory");
  } else {
    asm volatile("{\n.reg .pred P;\nsetp.ne.u32 P, %6, 0;\n@P cp.async.bulk.tensor.3d.shared::cluster.global.mbarrier::complete_tx::bytes.multicast::cluster [%0], [%1, {%3, %4, %5}], [%2], %7;\n}" ::"r"(dst), "l"(m), "r"(bar), "r"(c0), "r"(c1), "r"(c2), "r"(el), "h"((uint16_t)3) : "memory");
  }
}
__device__ __forceinline__ void mbar_arrive_cluster(uint32_t addr) { asm volatile("mbarrier.arrive.shared::cluster.b64 _, [%0];" ::"r"(addr) : "memory"); }
__device__ __forceinline__ uint32_t mapa(uint32_t addr, uint32_t rank) { uint32_t r; asm("mapa.shared::cluster.u32 %0, %1, %2;" : "=r"(r) : "r"(addr), "r"(rank)); return r; }
__device__ __forceinline__ void bulk_store_p(uint32_t el, void* dst, uint32_t src, uint32_t bytes) {
  asm volatile("{\n.reg .pred P;\nsetp.ne.u32 P, %3, 0;\n@P cp.async.bulk.global.shared::cta.bulk_group [%0], [%1], %2;\n}" ::"l"(dst), "r"(src), "r"(bytes), "r"(el) : "memory");
}
__device__ __forceinline__ void flag_release_p(uint32_t el, uint32_t* f) {
  asm volatile("{\n.reg .pred P;\nsetp.ne.u32 P, %1, 0;\nfence.proxy.async;\n@P red.relaxed.gpu.global.add.u32 [%0], 1;\n}" ::"l"(f), "r"(el) : "memory");
}
__device__ __forceinline__ void flag_add_p(uint32_t el, uint32_t* f) {
  asm volatile("{\n.reg .pred P;\nsetp.ne.u32 P, %1, 0;\n@P red.relaxed.gpu.global.add.u32 [%0], 1;\n}" ::"l"(f), "r"(el) : "memory");
}
__device__ __forceinline__ void prefetch_l2(const void* src, uint32_t bytes) { asm volatile("cp.async.bulk.prefetch.L2.global [%0], %1;" ::"l"(src), "r"(bytes) : "memory"); }
__device__ __forceinline__ void prefetch_map(const CUtensorMap* m) { asm volatile("prefetch.tensormap [%0];" ::"l"(m) : "memory"); }
__device__ __forceinline__ void wgmma_fence() { asm volatile("wgmma.fence.sync.aligned;" ::: "memory"); }
__device__ __forceinline__ void wgmma_commit() { asm volatile("wgmma.commit_group.sync.aligned;" ::: "memory"); }
template <int N> __device__ __forceinline__ void wgmma_wait() { asm volatile("wgmma.wait_group.sync.aligned %0;" ::"n"(N) : "memory"); }
__device__ __forceinline__ uint32_t dlo(uint32_t addr, uint32_t lbo) { return ((addr & 0x3FFFF) >> 4) + ((lbo >> 4) << 16); }
template <uint32_t SBO, uint32_t SWZ> __device__ __forceinline__ uint64_t dsc(uint32_t lo, uint32_t off) {
  uint64_t d; asm("mov.b64 %0, {%1, %2};" : "=l"(d) : "r"(lo + (off >> 4)), "n"((SBO >> 4) | (SWZ << 30))); return d;
}
template <int R> __device__ __forceinline__ void reg_alloc() { asm volatile("setmaxnreg.inc.sync.aligned.u32 %0;" ::"n"(R)); }
template <int R> __device__ __forceinline__ void reg_dealloc() { asm volatile("setmaxnreg.dec.sync.aligned.u32 %0;" ::"n"(R)); }
__device__ __forceinline__ void bar_sync(int id, int n) { asm volatile("bar.sync %0, %1;" ::"r"(id), "r"(n) : "memory"); }
__device__ __forceinline__ void bar_arrive(int id, int n) { asm volatile("bar.arrive %0, %1;" ::"r"(id), "r"(n) : "memory"); }
__device__ __forceinline__ void ldsm4(uint32_t* r, uint32_t addr) {
  asm volatile("ldmatrix.sync.aligned.m8n8.x4.shared.b16 {%0,%1,%2,%3}, [%4];" : "=r"(r[0]), "=r"(r[1]), "=r"(r[2]), "=r"(r[3]) : "r"(addr) : "memory");
}
__device__ __forceinline__ uint32_t movm(uint32_t a) { uint32_t d; asm volatile("movmatrix.sync.aligned.m8n8.trans.b16 %0, %1;" : "=r"(d) : "r"(a)); return d; }
__device__ __forceinline__ void mma16(float* c, uint32_t a0, uint32_t a1, uint32_t a2, uint32_t a3, uint32_t b0, uint32_t b1) {
  asm volatile("mma.sync.aligned.m16n8k16.row.col.f32.bf16.bf16.f32 {%0,%1,%2,%3}, {%4,%5,%6,%7}, {%8,%9}, {%0,%1,%2,%3};"
               : "+f"(c[0]), "+f"(c[1]), "+f"(c[2]), "+f"(c[3]) : "r"(a0), "r"(a1), "r"(a2), "r"(a3), "r"(b0), "r"(b1));
}
__device__ __forceinline__ void mma8(float* c, uint32_t a0, uint32_t a1, uint32_t b0) {
  asm volatile("mma.sync.aligned.m16n8k8.row.col.f32.bf16.bf16.f32 {%0,%1,%2,%3}, {%4,%5}, {%6}, {%0,%1,%2,%3};"
               : "+f"(c[0]), "+f"(c[1]), "+f"(c[2]), "+f"(c[3]) : "r"(a0), "r"(a1), "r"(b0));
}
__device__ __forceinline__ uint32_t pack2(float lo, float hi) { uint32_t r; asm("cvt.rn.bf16x2.f32 %0, %1, %2;" : "=r"(r) : "f"(hi), "f"(lo)); return r; }
__device__ __forceinline__ float blo(uint32_t v) { return __uint_as_float(v << 16); }
__device__ __forceinline__ float bhi(uint32_t v) { return __uint_as_float(v & 0xffff0000u); }
__device__ __forceinline__ float tanh_fast(float x) { float y; asm("tanh.approx.f32 %0, %1;" : "=f"(y) : "f"(x)); return y; }
__device__ __forceinline__ float rcp_fast(float x) { float y; asm("rcp.approx.ftz.f32 %0, %1;" : "=f"(y) : "f"(x)); return y; }
__device__ __forceinline__ float rsq_fast(float x) { float y; asm("rsqrt.approx.ftz.f32 %0, %1;" : "=f"(y) : "f"(x)); return y; }
__device__ __forceinline__ float ex2(float x) { float y; asm("ex2.approx.ftz.f32 %0, %1;" : "=f"(y) : "f"(x)); return y; }
__device__ __forceinline__ float qsum(float v) { v += __shfl_xor_sync(~0u, v, 1); v += __shfl_xor_sync(~0u, v, 2); return v; }
__device__ __forceinline__ float qmax(float v) { v = fmaxf(v, __shfl_xor_sync(~0u, v, 1)); v = fmaxf(v, __shfl_xor_sync(~0u, v, 2)); return v; }
__device__ __forceinline__ void stg32(void* p, uint32_t v) { asm volatile("st.global.u32 [%0], %1;" ::"l"(p), "r"(v) : "memory"); }
__device__ __forceinline__ void stg128(void* p, uint32_t a, uint32_t b, uint32_t c, uint32_t d) { asm volatile("st.global.v4.u32 [%0], {%1,%2,%3,%4};" ::"l"(p), "r"(a), "r"(b), "r"(c), "r"(d) : "memory"); }
__device__ __forceinline__ uint32_t ldcg32(const void* p) { uint32_t v; asm volatile("ld.global.L1::no_allocate.u32 %0, [%1];" : "=r"(v) : "l"(p) : "memory"); return v; }
__device__ __forceinline__ void stg128_if(bool c, void* p, uint32_t a, uint32_t b, uint32_t cc, uint32_t d) {
  asm volatile("{\n.reg .pred P;\nsetp.ne.u32 P, %5, 0;\n@P st.global.v4.u32 [%0], {%1,%2,%3,%4};\n}" ::"l"(p), "r"(a), "r"(b), "r"(cc), "r"(d), "r"((uint32_t)c) : "memory");
}
__device__ __forceinline__ uint2 lds64(uint32_t a) { uint2 v; asm volatile("ld.shared.v2.u32 {%0,%1}, [%2];" : "=r"(v.x), "=r"(v.y) : "r"(a) : "memory"); return v; }
__device__ __forceinline__ uint32_t ldnc16(const void* p) { uint16_t v; asm volatile("ld.global.nc.u16 %0, [%1];" : "=h"(v) : "l"(p)); return v; }
__device__ __forceinline__ uint4 ldnc128(const void* p) { uint4 v; asm volatile("ld.global.nc.v4.u32 {%0,%1,%2,%3}, [%4];" : "=r"(v.x), "=r"(v.y), "=r"(v.z), "=r"(v.w) : "l"(p)); return v; }
__device__ __forceinline__ void cp_async16(uint32_t dst, const void* src) { asm volatile("cp.async.cg.shared.global [%0], [%1], 16;" ::"r"(dst), "l"(src) : "memory"); }
__device__ __forceinline__ uint32_t hsub2(uint32_t a, uint32_t b) { uint32_t d; asm("sub.rn.bf16x2 %0, %1, %2;" : "=r"(d) : "r"(a), "r"(b)); return d; }
__device__ __forceinline__ void stg32_if(bool c, void* p, uint32_t v) {
  asm volatile("{\n.reg .pred P;\nsetp.ne.u32 P, %2, 0;\n@P st.global.u32 [%0], %1;\n}" ::"l"(p), "r"(v), "r"((uint32_t)c) : "memory");
}
__device__ __forceinline__ float wsum(float v) { for (int o = 16; o; o >>= 1) v += __shfl_xor_sync(~0u, v, o); return v; }
__device__ __forceinline__ uint32_t hmul2(uint32_t a, uint32_t b) { uint32_t d; asm("mul.rn.bf16x2 %0, %1, %2;" : "=r"(d) : "r"(a), "r"(b)); return d; }
__device__ __forceinline__ void sts32(uint32_t a, uint32_t v) { asm volatile("st.shared.u32 [%0], %1;" ::"r"(a), "r"(v) : "memory"); }
__device__ __forceinline__ uint32_t lds32(uint32_t a) { uint32_t v; asm volatile("ld.shared.u32 %0, [%1];" : "=r"(v) : "r"(a) : "memory"); return v; }
__device__ __forceinline__ void sts128(uint32_t a, uint32_t x, uint32_t y, uint32_t z, uint32_t w) { asm volatile("st.shared.v4.u32 [%0], {%1,%2,%3,%4};" ::"r"(a), "r"(x), "r"(y), "r"(z), "r"(w) : "memory"); }
__device__ __forceinline__ uint4 lds128(uint32_t a) { uint4 v; asm volatile("ld.shared.v4.u32 {%0,%1,%2,%3}, [%4];" : "=r"(v.x), "=r"(v.y), "=r"(v.z), "=r"(v.w) : "r"(a) : "memory"); return v; }
__device__ __forceinline__ void ll_st64(uint2* p, uint32_t v, uint32_t tag) {
  asm volatile("{\n.reg .b64 r;\nmov.b64 r, {%1,%2};\nst.relaxed.gpu.global.b64 [%0], r;\n}" ::"l"(p), "r"(v), "r"(tag) : "memory");
}
__device__ __forceinline__ uint2 ll_ld64(const uint2* p) {
  uint2 v; asm volatile("{\n.reg .b64 r;\nld.relaxed.gpu.global.b64 r, [%2];\nmov.b64 {%0,%1}, r;\n}" : "=r"(v.x), "=r"(v.y) : "l"(p) : "memory"); return v;
}
__device__ __forceinline__ void ll_st128(uint4* p, float a, float b, uint32_t tag, float c = 0.f) {
  asm volatile("{\n.reg .b128 r;\n.reg .b64 lo, hi;\nmov.b64 lo, {%1,%2};\nmov.b64 hi, {%3,%4};\nmov.b128 r, {lo, hi};\nst.relaxed.gpu.global.b128 [%0], r;\n}" ::"l"(p), "r"(__float_as_uint(a)), "r"(__float_as_uint(b)), "r"(tag), "r"(__float_as_uint(c)) : "memory");
}
__device__ __forceinline__ uint4 ll_ld128g(const void* p) {
  uint4 v; asm volatile("{\n.reg .b128 r;\n.reg .b64 lo, hi;\nld.relaxed.gpu.b128 r, [%4];\nmov.b128 {lo, hi}, r;\nmov.b64 {%0,%1}, lo;\nmov.b64 {%2,%3}, hi;\n}" : "=r"(v.x), "=r"(v.y), "=r"(v.z), "=r"(v.w) : "l"(p) : "memory"); return v;
}
__device__ __forceinline__ uint4 ll_ld128(const uint4* p) {
  uint4 v; asm volatile("{\n.reg .b128 r;\n.reg .b64 lo, hi;\nld.relaxed.gpu.global.b128 r, [%4];\nmov.b128 {lo, hi}, r;\nmov.b64 {%0,%1}, lo;\nmov.b64 {%2,%3}, hi;\n}" : "=r"(v.x), "=r"(v.y), "=r"(v.z), "=r"(v.w) : "l"(p) : "memory"); return v;
}
__device__ __forceinline__ void publish_p(uint32_t el, uint32_t* f) {
  asm volatile("{\n.reg .pred P;\nsetp.ne.u32 P, %1, 0;\n@P cp.async.bulk.commit_group;\n@P cp.async.bulk.wait_group 0;\n@P red.release.gpu.global.add.u32 [%0], 1;\n}" ::"l"(f), "r"(el) : "memory");
}
__device__ __forceinline__ void stsm4(uint32_t addr, uint32_t a, uint32_t b, uint32_t c, uint32_t d) {
  asm volatile("stmatrix.sync.aligned.m8n8.x4.shared.b16 [%0], {%1,%2,%3,%4};" ::"r"(addr), "r"(a), "r"(b), "r"(c), "r"(d) : "memory");
}
__device__ __forceinline__ void sts64(uint32_t a, uint32_t x, uint32_t y) { asm volatile("st.shared.v2.u32 [%0], {%1,%2};" ::"r"(a), "r"(x), "r"(y) : "memory"); }
__device__ __forceinline__ void ll_st128_if(bool on, uint4* p, float a, float b, uint32_t tag) {
  asm volatile("{\n.reg .pred P;\n.reg .b128 r;\n.reg .b64 lo, hi;\nsetp.ne.u32 P, %4, 0;\nmov.b64 lo, {%1,%2};\nmov.b64 hi, {%3,%3};\nmov.b128 r, {lo, hi};\n@P st.relaxed.gpu.global.b128 [%0], r;\n}" ::"l"(p), "r"(__float_as_uint(a)), "r"(__float_as_uint(b)), "r"(tag), "r"((uint32_t)on) : "memory");
}
__device__ __forceinline__ uint4 ldnc128_if(bool c, const void* p) {
  uint4 v = make_uint4(0u, 0u, 0u, 0u);
  asm volatile("{\n.reg .pred P;\nsetp.ne.u32 P, %5, 0;\n@P ld.global.nc.v4.u32 {%0,%1,%2,%3}, [%4];\n}" : "+r"(v.x), "+r"(v.y), "+r"(v.z), "+r"(v.w) : "l"(p), "r"((uint32_t)c));
  return v;
}
__device__ __forceinline__ float2 lds64f(uint32_t a) { float2 v; asm volatile("ld.shared.v2.f32 {%0,%1}, [%2];" : "=f"(v.x), "=f"(v.y) : "r"(a) : "memory"); return v; }
#define TRC(cond, role, idx) do {} while (0)
#define TRV(role, idx, v) do {} while (0)
#define TRVI(c, role, idx, v) do {} while (0)

#define ACLK_INIT do {} while (0)
#define ACLK(i) do {} while (0)
#define ACLK_OUT do {} while (0)
#define RCLK(i) do {} while (0)
#define RCLK_INIT do {} while (0)
#define RCLK_OUT do {} while (0)
#define SCLK(i) do {} while (0)
#define SCLK2(i) do {} while (0)
#define SCLK3(i) do {} while (0)
#define PL 1
#define PCLK(i) do {} while (0)
#define PQ 1
#define CLK_INIT do {} while (0)
#define CLK(i) do {} while (0)
#define CLK_OUT do {} while (0)

__device__ __forceinline__ void wgmma_ss_n216(float* d, uint64_t da, uint64_t db, int scaleD) {
  asm volatile("{\n.reg .pred p;\nsetp.ne.b32 p, %110, 0;\nwgmma.mma_async.sync.aligned.m64n216k16.f32.bf16.bf16 "
    "{%0,%1,%2,%3,%4,%5,%6,%7,%8,%9,%10,%11,%12,%13,%14,%15,%16,%17,%18,%19,%20,%21,%22,%23,%24,%25,%26,%27,%28,%29,%30,%31,%32,%33,%34,%35,%36,%37,%38,%39,%40,%41,%42,%43,%44,%45,%46,%47,%48,%49,%50,%51,%52,%53,%54,%55,%56,%57,%58,%59,%60,%61,%62,%63,%64,%65,%66,%67,%68,%69,%70,%71,%72,%73,%74,%75,%76,%77,%78,%79,%80,%81,%82,%83,%84,%85,%86,%87,%88,%89,%90,%91,%92,%93,%94,%95,%96,%97,%98,%99,%100,%101,%102,%103,%104,%105,%106,%107}, "
    "%108, %109, p, 1, 1, 0, 1;\n}\n"
    : "+f"(d[0]), "+f"(d[1]), "+f"(d[2]), "+f"(d[3]), "+f"(d[4]), "+f"(d[5]), "+f"(d[6]), "+f"(d[7]), "+f"(d[8]), "+f"(d[9]), "+f"(d[10]), "+f"(d[11]), "+f"(d[12]), "+f"(d[13]), "+f"(d[14]), "+f"(d[15]), "+f"(d[16]), "+f"(d[17]), "+f"(d[18]), "+f"(d[19]), "+f"(d[20]), "+f"(d[21]), "+f"(d[22]), "+f"(d[23]), "+f"(d[24]), "+f"(d[25]), "+f"(d[26]), "+f"(d[27]), "+f"(d[28]), "+f"(d[29]), "+f"(d[30]), "+f"(d[31]), "+f"(d[32]), "+f"(d[33]), "+f"(d[34]), "+f"(d[35]), "+f"(d[36]), "+f"(d[37]), "+f"(d[38]), "+f"(d[39]), "+f"(d[40]), "+f"(d[41]), "+f"(d[42]), "+f"(d[43]), "+f"(d[44]), "+f"(d[45]), "+f"(d[46]), "+f"(d[47]), "+f"(d[48]), "+f"(d[49]), "+f"(d[50]), "+f"(d[51]), "+f"(d[52]), "+f"(d[53]), "+f"(d[54]), "+f"(d[55]), "+f"(d[56]), "+f"(d[57]), "+f"(d[58]), "+f"(d[59]), "+f"(d[60]), "+f"(d[61]), "+f"(d[62]), "+f"(d[63]), "+f"(d[64]), "+f"(d[65]), "+f"(d[66]), "+f"(d[67]), "+f"(d[68]), "+f"(d[69]), "+f"(d[70]), "+f"(d[71]), "+f"(d[72]), "+f"(d[73]), "+f"(d[74]), "+f"(d[75]), "+f"(d[76]), "+f"(d[77]), "+f"(d[78]), "+f"(d[79]), "+f"(d[80]), "+f"(d[81]), "+f"(d[82]), "+f"(d[83]), "+f"(d[84]), "+f"(d[85]), "+f"(d[86]), "+f"(d[87]), "+f"(d[88]), "+f"(d[89]), "+f"(d[90]), "+f"(d[91]), "+f"(d[92]), "+f"(d[93]), "+f"(d[94]), "+f"(d[95]), "+f"(d[96]), "+f"(d[97]), "+f"(d[98]), "+f"(d[99]), "+f"(d[100]), "+f"(d[101]), "+f"(d[102]), "+f"(d[103]), "+f"(d[104]), "+f"(d[105]), "+f"(d[106]), "+f"(d[107])
    : "l"(da), "l"(db), "r"(scaleD));
}
__device__ __forceinline__ void wgmma_ss_n72(float* d, uint64_t da, uint64_t db, int scaleD) {
  asm volatile("{\n.reg .pred p;\nsetp.ne.b32 p, %38, 0;\nwgmma.mma_async.sync.aligned.m64n72k16.f32.bf16.bf16 "
    "{%0,%1,%2,%3,%4,%5,%6,%7,%8,%9,%10,%11,%12,%13,%14,%15,%16,%17,%18,%19,%20,%21,%22,%23,%24,%25,%26,%27,%28,%29,%30,%31,%32,%33,%34,%35}, "
    "%36, %37, p, 1, 1, 0, 1;\n}\n"
    : "+f"(d[0]), "+f"(d[1]), "+f"(d[2]), "+f"(d[3]), "+f"(d[4]), "+f"(d[5]), "+f"(d[6]), "+f"(d[7]), "+f"(d[8]), "+f"(d[9]), "+f"(d[10]), "+f"(d[11]), "+f"(d[12]), "+f"(d[13]), "+f"(d[14]), "+f"(d[15]), "+f"(d[16]), "+f"(d[17]), "+f"(d[18]), "+f"(d[19]), "+f"(d[20]), "+f"(d[21]), "+f"(d[22]), "+f"(d[23]), "+f"(d[24]), "+f"(d[25]), "+f"(d[26]), "+f"(d[27]), "+f"(d[28]), "+f"(d[29]), "+f"(d[30]), "+f"(d[31]), "+f"(d[32]), "+f"(d[33]), "+f"(d[34]), "+f"(d[35])
    : "l"(da), "l"(db), "r"(scaleD));
}
__device__ __forceinline__ void wgmma_ss_n128(float* d, uint64_t da, uint64_t db, int scaleD) {
  asm volatile("{\n.reg .pred p;\nsetp.ne.b32 p, %66, 0;\nwgmma.mma_async.sync.aligned.m64n128k16.f32.bf16.bf16 "
    "{%0,%1,%2,%3,%4,%5,%6,%7,%8,%9,%10,%11,%12,%13,%14,%15,%16,%17,%18,%19,%20,%21,%22,%23,%24,%25,%26,%27,%28,%29,%30,%31,%32,%33,%34,%35,%36,%37,%38,%39,%40,%41,%42,%43,%44,%45,%46,%47,%48,%49,%50,%51,%52,%53,%54,%55,%56,%57,%58,%59,%60,%61,%62,%63}, "
    "%64, %65, p, 1, 1, 0, 1;\n}\n"
    : "+f"(d[0]), "+f"(d[1]), "+f"(d[2]), "+f"(d[3]), "+f"(d[4]), "+f"(d[5]), "+f"(d[6]), "+f"(d[7]), "+f"(d[8]), "+f"(d[9]), "+f"(d[10]), "+f"(d[11]), "+f"(d[12]), "+f"(d[13]), "+f"(d[14]), "+f"(d[15]), "+f"(d[16]), "+f"(d[17]), "+f"(d[18]), "+f"(d[19]), "+f"(d[20]), "+f"(d[21]), "+f"(d[22]), "+f"(d[23]), "+f"(d[24]), "+f"(d[25]), "+f"(d[26]), "+f"(d[27]), "+f"(d[28]), "+f"(d[29]), "+f"(d[30]), "+f"(d[31]), "+f"(d[32]), "+f"(d[33]), "+f"(d[34]), "+f"(d[35]), "+f"(d[36]), "+f"(d[37]), "+f"(d[38]), "+f"(d[39]), "+f"(d[40]), "+f"(d[41]), "+f"(d[42]), "+f"(d[43]), "+f"(d[44]), "+f"(d[45]), "+f"(d[46]), "+f"(d[47]), "+f"(d[48]), "+f"(d[49]), "+f"(d[50]), "+f"(d[51]), "+f"(d[52]), "+f"(d[53]), "+f"(d[54]), "+f"(d[55]), "+f"(d[56]), "+f"(d[57]), "+f"(d[58]), "+f"(d[59]), "+f"(d[60]), "+f"(d[61]), "+f"(d[62]), "+f"(d[63])
    : "l"(da), "l"(db), "r"(scaleD));
}
__device__ __forceinline__ void wgmma_ss_n160(float* d, uint64_t da, uint64_t db, int scaleD) {
  asm volatile("{\n.reg .pred p;\nsetp.ne.b32 p, %82, 0;\nwgmma.mma_async.sync.aligned.m64n160k16.f32.bf16.bf16 "
    "{%0,%1,%2,%3,%4,%5,%6,%7,%8,%9,%10,%11,%12,%13,%14,%15,%16,%17,%18,%19,%20,%21,%22,%23,%24,%25,%26,%27,%28,%29,%30,%31,%32,%33,%34,%35,%36,%37,%38,%39,%40,%41,%42,%43,%44,%45,%46,%47,%48,%49,%50,%51,%52,%53,%54,%55,%56,%57,%58,%59,%60,%61,%62,%63,%64,%65,%66,%67,%68,%69,%70,%71,%72,%73,%74,%75,%76,%77,%78,%79}, "
    "%80, %81, p, 1, 1, 0, 1;\n}\n"
    : "+f"(d[0]), "+f"(d[1]), "+f"(d[2]), "+f"(d[3]), "+f"(d[4]), "+f"(d[5]), "+f"(d[6]), "+f"(d[7]), "+f"(d[8]), "+f"(d[9]), "+f"(d[10]), "+f"(d[11]), "+f"(d[12]), "+f"(d[13]), "+f"(d[14]), "+f"(d[15]), "+f"(d[16]), "+f"(d[17]), "+f"(d[18]), "+f"(d[19]), "+f"(d[20]), "+f"(d[21]), "+f"(d[22]), "+f"(d[23]), "+f"(d[24]), "+f"(d[25]), "+f"(d[26]), "+f"(d[27]), "+f"(d[28]), "+f"(d[29]), "+f"(d[30]), "+f"(d[31]), "+f"(d[32]), "+f"(d[33]), "+f"(d[34]), "+f"(d[35]), "+f"(d[36]), "+f"(d[37]), "+f"(d[38]), "+f"(d[39]), "+f"(d[40]), "+f"(d[41]), "+f"(d[42]), "+f"(d[43]), "+f"(d[44]), "+f"(d[45]), "+f"(d[46]), "+f"(d[47]), "+f"(d[48]), "+f"(d[49]), "+f"(d[50]), "+f"(d[51]), "+f"(d[52]), "+f"(d[53]), "+f"(d[54]), "+f"(d[55]), "+f"(d[56]), "+f"(d[57]), "+f"(d[58]), "+f"(d[59]), "+f"(d[60]), "+f"(d[61]), "+f"(d[62]), "+f"(d[63]), "+f"(d[64]), "+f"(d[65]), "+f"(d[66]), "+f"(d[67]), "+f"(d[68]), "+f"(d[69]), "+f"(d[70]), "+f"(d[71]), "+f"(d[72]), "+f"(d[73]), "+f"(d[74]), "+f"(d[75]), "+f"(d[76]), "+f"(d[77]), "+f"(d[78]), "+f"(d[79])
    : "l"(da), "l"(db), "r"(scaleD));
}
__device__ __forceinline__ void wgmma_rs_n144(float* d, const uint32_t* a, uint64_t db, int scaleD) {
  asm volatile("{\n.reg .pred p;\nsetp.ne.b32 p, %77, 0;\nwgmma.mma_async.sync.aligned.m64n144k16.f32.bf16.bf16 "
    "{%0,%1,%2,%3,%4,%5,%6,%7,%8,%9,%10,%11,%12,%13,%14,%15,%16,%17,%18,%19,%20,%21,%22,%23,%24,%25,%26,%27,%28,%29,%30,%31,%32,%33,%34,%35,%36,%37,%38,%39,%40,%41,%42,%43,%44,%45,%46,%47,%48,%49,%50,%51,%52,%53,%54,%55,%56,%57,%58,%59,%60,%61,%62,%63,%64,%65,%66,%67,%68,%69,%70,%71}, "
    "{%72,%73,%74,%75}, %76, p, 1, 1, 1;\n}\n"
    : "+f"(d[0]), "+f"(d[1]), "+f"(d[2]), "+f"(d[3]), "+f"(d[4]), "+f"(d[5]), "+f"(d[6]), "+f"(d[7]), "+f"(d[8]), "+f"(d[9]), "+f"(d[10]), "+f"(d[11]), "+f"(d[12]), "+f"(d[13]), "+f"(d[14]), "+f"(d[15]), "+f"(d[16]), "+f"(d[17]), "+f"(d[18]), "+f"(d[19]), "+f"(d[20]), "+f"(d[21]), "+f"(d[22]), "+f"(d[23]), "+f"(d[24]), "+f"(d[25]), "+f"(d[26]), "+f"(d[27]), "+f"(d[28]), "+f"(d[29]), "+f"(d[30]), "+f"(d[31]), "+f"(d[32]), "+f"(d[33]), "+f"(d[34]), "+f"(d[35]), "+f"(d[36]), "+f"(d[37]), "+f"(d[38]), "+f"(d[39]), "+f"(d[40]), "+f"(d[41]), "+f"(d[42]), "+f"(d[43]), "+f"(d[44]), "+f"(d[45]), "+f"(d[46]), "+f"(d[47]), "+f"(d[48]), "+f"(d[49]), "+f"(d[50]), "+f"(d[51]), "+f"(d[52]), "+f"(d[53]), "+f"(d[54]), "+f"(d[55]), "+f"(d[56]), "+f"(d[57]), "+f"(d[58]), "+f"(d[59]), "+f"(d[60]), "+f"(d[61]), "+f"(d[62]), "+f"(d[63]), "+f"(d[64]), "+f"(d[65]), "+f"(d[66]), "+f"(d[67]), "+f"(d[68]), "+f"(d[69]), "+f"(d[70]), "+f"(d[71])
    : "r"(a[0]), "r"(a[1]), "r"(a[2]), "r"(a[3]), "l"(db), "r"(scaleD));
}
__device__ __forceinline__ void wgmma_rs_n64(float* d, const uint32_t* a, uint64_t db, int scaleD) {
  asm volatile("{\n.reg .pred p;\nsetp.ne.b32 p, %37, 0;\nwgmma.mma_async.sync.aligned.m64n64k16.f32.bf16.bf16 "
    "{%0,%1,%2,%3,%4,%5,%6,%7,%8,%9,%10,%11,%12,%13,%14,%15,%16,%17,%18,%19,%20,%21,%22,%23,%24,%25,%26,%27,%28,%29,%30,%31}, "
    "{%32,%33,%34,%35}, %36, p, 1, 1, 1;\n}\n"
    : "+f"(d[0]), "+f"(d[1]), "+f"(d[2]), "+f"(d[3]), "+f"(d[4]), "+f"(d[5]), "+f"(d[6]), "+f"(d[7]), "+f"(d[8]), "+f"(d[9]), "+f"(d[10]), "+f"(d[11]), "+f"(d[12]), "+f"(d[13]), "+f"(d[14]), "+f"(d[15]), "+f"(d[16]), "+f"(d[17]), "+f"(d[18]), "+f"(d[19]), "+f"(d[20]), "+f"(d[21]), "+f"(d[22]), "+f"(d[23]), "+f"(d[24]), "+f"(d[25]), "+f"(d[26]), "+f"(d[27]), "+f"(d[28]), "+f"(d[29]), "+f"(d[30]), "+f"(d[31])
    : "r"(a[0]), "r"(a[1]), "r"(a[2]), "r"(a[3]), "l"(db), "r"(scaleD));
}

template <int V> struct Int { static constexpr int value = V; };
struct Cur {
  uint32_t s, ph;
  __device__ __forceinline__ void next() { if (++s == NST) { s = 0; ph ^= 1; } }
};

__device__ __forceinline__ uint32_t o_place(uint32_t w, uint32_t e) { return (((w ? 0xd5310u : 0xa8d57u) >> (4 * e)) & 15) * 8192 + 90112; }
#define z1_block(rb, w, j) (Q.Z + ((rb) * 16 + (w) * 8 + (j)) * ZB)
#define xn_block(hw) (Q.Z + (512 + (hw) * 2) * ZB)
#define z2_block(kb, j) (Q.Z + (256 + (kb) * 8 + (j)) * ZB)
template <int N> __device__ __forceinline__ void pause(uint32_t zero) {
  if (N <= 0) return;
  uint32_t z = clock() + threadIdx.x;
  do {
#pragma unroll (N > 8 ? 1 : 8)
    for (int i = 0; i < N; i++) asm volatile("shfl.sync.bfly.b32 %0, %0, 1, 0x1f, 0xffffffff;" : "+r"(z)::"memory");
  } while (__any_sync(~0u, z & zero));
}

__global__ void __cluster_dims__(2, 1, 1) __launch_bounds__(384, 1) mega_kernel(const Ptrs Q, const __grid_constant__ Params P) {
  extern __shared__ __align__(1024) uint8_t smem_raw[];
  const uint32_t sb = smem_u32(smem_raw);
  const uint32_t bars = sb + SM_BAR;
  const int tid = threadIdx.x;
  int lane = tid & 31;
  const int wid = __shfl_sync(~0u, tid >> 5, 0);
  const int cl = blockIdx.x >> 1;
  const int bid = (cl < 4 ? cl * 8 + 32 : cl - 4 + (max(cl - 29, 0) * 37 >> 8)) * 2 + (blockIdx.x & 1);
  const int rb = bid & 15, j = bid >> 4;
  uint4 wv[5];
  {
    const int n8 = min(tid >> 3, 26), part = n8 / 9;
    const uint8_t* src = (const uint8_t*)Q.wqkv + (8 * rb + (tid & 7)) * (3 * DM * 2) + (part * (DM - 72) + 72 * j + 8 * n8) * 2;
#pragma unroll
    for (int u = 0; u < 5; u++) wv[u] = ldnc128_if(tid < 216 && cl < 64 && (u < 4 || rb < 8), src + u * (128 * 3 * DM * 2));
  }
  if (cl >= 64) return;
  if (wid >= 7 && lane == 0) {
    if (wid < 10) {
#pragma unroll
      for (uint32_t b = 0; b < B_AD / 3; b += 8) mbar_init(bars + (wid - 7) * (B_AD / 3) + b, 1);
    } else if (wid == 10) {
#pragma unroll
      for (uint32_t b = B_AD; b < B_EVT; b += 8) mbar_init(bars + b, b < B_LAG ? 2 : 4);
    } else {
#pragma unroll
      for (uint32_t b = B_EVT; b < 1024; b += 8) if (b < B_OFF || b >= B_IMG) mbar_init(bars + b, b < B_IMG ? 4 : b < B_EMPTY ? 8 : 16);
    }
    asm volatile("fence.mbarrier_init.release.cluster;" ::: "memory");
  }
  __syncthreads();

  if (wid >= 8) {
    reg_dealloc<56>();
    const uint32_t el = elect_one();
    const uint64_t pol = policy_evict_first();
    uint32_t* const fj = Q.flags + FJ + j * 32;
    if (wid == 8) {
      if (el) { prefetch_map(&P.wsp); prefetch_map(&P.winb[j & 1]); prefetch_map(&P.wins); prefetch_map(&P.wout); prefetch_map(&P.act[1]); prefetch_map(&P.res[0]); prefetch_map(&P.res[1]); prefetch_map(&P.row[1]); }
      const uint32_t epoch = ldcg32(fj + FJ_EP + rb);
      Cur c{0, 1};
      const uint32_t rk = bid & 1;
      uint32_t st, full;
      auto slot = [&](uint32_t bytes) {
        st = sb + c.s * ST_BYTES; full = bars + B_FULL + c.s * 8;
        mbar_wait(full, c.ph);
        expect_tx_p(el, full, bytes);
        mbar_wait(full - B_FULL + B_EMPTY, c.ph);
      };
#pragma unroll 1
      for (int L = 0; L < 2; L++) {
#pragma unroll 1
        for (int i = 0; i < 9; i++) {
          if (L == 0 && i == 0) {
            flag_wait(fj + FJ_WQ, (epoch + 1) * 16);
            fence_async_g();
            TRC(el, 2, 45);
          }
          slot(27648);
          bulk_mc_h(el, st + ST_B + rk * 13824, Q.WQ + j * WQ_SL + i * 27648 + rk * 13824, 13824, full, EF(0), pol);
          c.next();
        }
        if (L == 0) {
          flag_wait(fj + FJ_WO, (epoch + 1) * 16);
          fence_async_g();
          TRC(el, 2, 46);
        }
#pragma unroll 1
        while (c.s) {
          mbar_wait(bars + B_EMPTY + c.s * 8, c.ph);
          if (el) { mbar_arrive(bars + B_FULL + c.s * 8); asm volatile("mbarrier.arrive.shared::cta.b64 _, [%0], 16;" ::"r"(bars + B_EMPTY + c.s * 8) : "memory"); }
          c.next();
        }
        expect_tx_p(el, bars + B_WF, WO_SL);
        mbar_wait(bars + B_EMPTY, c.ph);
        mbar_wait(bars + B_EMPTY + 8, c.ph);
        bulk_mc_h(el, sb + rk * (WO_SL / 2), Q.WO + j * WO_SL + rk * (WO_SL / 2), WO_SL / 2, bars + B_WF, EF(1), pol);
#pragma unroll 1
        for (int r = 0; r < 10; r++) {
          const bool big = r >= 2 && r < 8;
          const int a0 = (r < 5 ? 36 : 0) + ((9 * j) >> 1) + (big ? 2 - 2 * (j & 1) : 3 * (j & 1) + rk), ks = big ? 32 : 48;
          int k = big ? (r < 5 ? r - 2 : r - 5) * 192 + rk * 16 : (r & 1) * 288;
          const CUtensorMap* m = big ? &P.winb[j & 1] : &P.wins;
          const uint32_t dst = sb + SM_B3 + rk * 6144;
#pragma unroll
          for (int p = 0; p < 6; p++, k += ks) {
            if (!(p & 3) && r == 0) mbar_wait(bars + B_XD + p * 2, L);
            if (p) mbar_wait_c(bars + B_E3 + p * 8, ~r & 1); else mbar_wait(bars + B_E3, ~r & 1);
            expect_tx_p(el, bars + B_F3 + p * 8, 12288);
            tma3d_mc_h(el, dst + p * 12288, m, 0, k, a0, bars + B_F3 + p * 8, EF(2), pol);
          }
        }
        TRC(el, 2, L * 16 + 6);
        mbar_wait(bars + B_ZOK, L);
        fence_async_g();
        TRC(el, 2, L * 16 + 7);
        const uint8_t* src = z2_block(0, j) + rk * 18432;
#pragma unroll 1
        for (int r = 0; r < 8; r++) {
          const int k = (r & 3) * 512 + ((r >> 2) ^ 1) * 64;
#pragma unroll
          for (int p = 0; p < 4; p++, src += 8 * ZB) {
            if ((p == 1 || p == 2) && r == 0) mbar_wait(bars + B_E3 - 8 + p * 24, 1);
            mbar_wait_c(bars + B_AD + p * 8, ~r & 1);
            if (p) mbar_wait_c(bars + B_EMPTY + p * 8, c.ph); else mbar_wait(bars + B_EMPTY, c.ph);
            expect_tx_p(el, bars + B_FULL + p * 8, ST_BYTES);
            bulk_mc_h(el, sb + p * ST_BYTES + ST_B + rk * 18432, src, 18432, bars + B_FULL + p * 8, EF(4), pol);
            tma3d_h(el, sb + p * ST_BYTES, &P.wsp, k + p * 128, rb * 64, 0, bars + B_FULL + p * 8, EF(3), pol);
          }
          c.ph ^= 1;
        }
        mbar_wait(bars + B_Z1, L);
        fence_async_g();
#pragma unroll 1
        for (int i = 0; i < 11; i++) {
          const int cb = i - 2 + j;
          if (i < 4) mbar_wait(bars + B_AD + c.s * 8, 1);
          slot(ZB);
          if (i < 2) bulk_load_h(el, st + ST_B, z1_block(rb, i, j), ZB, full, true, pol);
          else tma2d_mc_h(el, st + ST_B + rk * 18432, &P.wout, (cb >= 9 ? cb - 9 : cb) * 64, 288 * j + rk * 144, full, EF(5), pol);
          c.next();
        }
      }
    } else if (wid < 11) {
      uint32_t id = bid * 2 + wid - 9;
#define AGENT_IDS asm volatile("" : "+r"(lane), "+r"(id)); const uint32_t w = id & 1, hw = id & 31, rb = hw >> 1, j = id >> 5, ev = bars + B_EVT + w * EV_N * 8; \
      uint32_t* const fr = Q.flags + hw * 32; uint32_t* const fj = Q.flags + FJ + j * 32; (void)fr; (void)fj; (void)ev; (void)rb
      uint32_t t8 = 0;
      Cur c{0, 1};
#pragma unroll 1
      for (int L = 0; L < 2; L++) {
        if (L) {
          AGENT_IDS;
          const uint32_t full = bars + B_FULLA + w * 32 + c.s * 8, dst = sb + c.s * ST_BYTES + w * 8192;
          expect_tx_p(el, full, 8192);
          mbar_wait_c(ev + EV_PT * 8, 1);
          TRC(el, 3, w * 32 + 16);
          flag_release_p(el, fr + FR_X2);
          TRC(el, 3, w * 32 + 17);
          mbar_wait_c(bars + B_EMPTY + c.s * 8, c.ph);
          flag_wait(fr + FR_X2, t8);
          fence_async_g();
          tma3d_h(el, dst, &P.act[1], 0, rb * 64, w, full, false, pol);
          c.next();
          TRC(el, 3, w * 32 + 18);
        }
#pragma unroll 1
        for (int i = L; i < 9; i++) {
          AGENT_IDS;
          const uint32_t full = bars + B_FULLA + w * 32 + c.s * 8, dst = sb + c.s * ST_BYTES + w * 8192;
          if (L == 0 && i == AEP) t8 = (ldcg32(fr + FR_EP + j) + 1) * 8;
          mbar_wait_c(bars + B_EMPTY + c.s * 8, c.ph);
          expect_tx_p(el, full, 8192);
          tma3d_h(el, dst, &P.act[L], i * 64, rb * 64, w, full, false, pol);
          c.next();
          if (i == PZI || i == PZI + 1) {
            uint8_t* d = (i == PZI ? xn_block(hw) : z1_block(rb, 0, 0) + w * 4608) + j * 9216 + lane * 16;
#pragma unroll 1
            for (int u = i == PZI ? 0 : 3; u < 6; u++, d += 1536) { stg128(d, ~0u, ~0u, ~0u, ~0u); stg128(d + 512, ~0u, ~0u, ~0u, ~0u); stg128(d + 1024, ~0u, ~0u, ~0u, ~0u); }
          }
          if (i == PZI) { stg128(Q.ST1 + (hw * 8 + j) * 32 + lane, ~0u, ~0u, ~0u, ~0u); stg128(Q.ZST + (hw * 8 + j) * 32 + lane, ~0u, ~0u, ~0u, ~0u); }
          if (i == RFI) {
            expect_tx_p(el, bars + B_WT + w * 8, 9216);
            tma3d_h(el, sb + SM_STG + w * 9216, &P.row[L], 0, 3 * w, rb * 64 + 8 * j, bars + B_WT + w * 8, false, pol);
          }
          if (i == 4 && L > w) {
            expect_tx_p(el, bars + B_XRW + 8, 864);
            bulk_load_p(el, sb + 3 * ST_BYTES + SM_CSQ, Q.CSP + (NCTA + (id >> 1)) * 216, 864, bars + B_XRW + 8);
          }
        }
        if (c.s) { c.s = 0; c.ph ^= 1; }
        {
          AGENT_IDS;
          const uint32_t tag = (t8 >> 2) - 1 + L;
          uint4* const xs = Q.XST + hw * 128;
          const uint32_t tab = sb + L * (3 * ST_BYTES) + SM_XST + w * 768 + lane * 8;
          TRC(el, 3, w * 32 + L * 16 + 13);
#pragma unroll 1
          for (int it = 0; it < (1 << 22); it++) {
            const uint4 a = ll_ld128(xs + 2 * lane), b = ll_ld128(xs + 64 + 2 * lane), h = ll_ld128(xs - (rb ? 192 : 0) + 2 * (lane | 24));
            if (__all_sync(~0u, a.z == tag && b.z == tag && h.z == tag)) { sts64(tab, h.x, h.y); sts64(tab + 256, a.x, a.y); sts64(tab + 512, b.x, b.y); break; }
          }
          __syncwarp();
          if (el) mbar_arrive(bars + B_CSQ);
          TRC(el, 3, w * 32 + L * 16 + 14);
          uint32_t* f = Q.flags + rb * 64 + FR_PZ + L;
          flag_release_p(el, f);
          expect_tx_p(el, bars + B_RES + w * 8, 9216);
          tma3d_h(el, sb + SM_STG + w * 9216, &P.res[L], j * 72, (hw ^ 1) * 32, 0, bars + B_RES + w * 8, !L, pol);
          pause<FD3>(Q.zero);
          flag_wait(f, t8 * 2);
          fence_async_g();
          TRC(el, 3, w * 32 + L * 16 + 15);
        }
        {
          AGENT_IDS;
          uint32_t* f = Q.flags + rb * 64 + FR_O + L;
#pragma unroll 1
          for (int e = 0; e < 5; e++) {
            const uint32_t nb = e ? 16384 : 8192, full = bars + B_OF + w * 40 + e * 8, dst = sb + o_place(w, e);
            const uint8_t* src = z1_block(rb, w, 0) + (e ? e * 16384 - 8192 : 0);
            expect_tx_p(el, full, nb);
            if (e == 0) {
              mbar_wait_c(ev + EV_O * 8, L);
              TRC(el, 3, w * 32 + L * 16 + 3);
              if (!w) flag_add_p(el, f);
              flag_wait(f + w * (FR_OL - FR_O), t8);
              if (w) fence_async_g();
            }
            if (w && (e == 0 || e == 3)) mbar_wait_c(bars + (e ? B_X3 : B_OF + YPACE * 8), L);
            bulk_load_h(el, dst, src, nb, full, EF(6), pol);
            TRC(el && e == 0, 3, w * 32 + L * 16 + 5);
          }
        }
        {
          AGENT_IDS;
          const uint8_t* src = xn_block(hw);
          uint32_t full = bars + B_AF3 + w * 96, dst = sb + w * 6144;
          if (L) flag_wait(fj + FJ_P4, t8 * 4);
          mbar_wait_c(bars + B_XD + 8, L);
          mbar_wait_c(ev + EV_X1 * 8, L);
          TRC(el, 3, w * 32 + L * 16 + 6);
          pause<SDEL>(Q.zero);
#pragma unroll 1
          for (int k = 0; k < 12; k++, src += 6144, dst += 12288, full += 8) {
            expect_tx_p(el, full, 6144);
            if (k >= APACE) mbar_wait_c(full - APACE * 8, L);
            bulk_load_h(el, dst, src, 6144, full, EF(7), pol);
            TRC(el && k == 0, 3, w * 32 + L * 16 + 8);
          }
        }
        if (wid == 10) {
          AGENT_IDS;
          mbar_wait_c(ev - (EV_N - EV_ZN) * 8, L);
          mbar_wait_c(ev + EV_ZN * 8, L);
          asm volatile("fence.release.gpu;" ::: "memory");
          flag_add_p(el, fj + FJ_ZN + L);
          flag_add_p(el, fr - 32 + FR_XR + L);
          flag_wait(fj + FJ_ZN + L, t8 * 2);
          flag_wait(fr - 32 + FR_XR + L, t8);
          if (el) mbar_arrive(bars + B_ZOK);
        } else {
          AGENT_IDS;
          mbar_wait_c(ev + EV_ZN * 8, L);
          if (el) asm volatile("cp.async.bulk.prefetch.tensor.3d.L2.global [%0, {%1, %2, %3}];" ::"l"(&P.wsp), "r"(j * 128 + 64), "r"(rb * 64), "r"(0) : "memory");

        }
        float cv;
        {
        AGENT_IDS;
        cv = (lane & 3) ? 0.f : -blo(ldnc16(Q.b_sp + 128 * rb + 16 * j + 2 * (lane >> 2) + w));
        const uint32_t ro = (w * 64 + 8 * j + (lane >> 2)) * 128, x0 = ((lane & 3) * 2) ^ (lane >> 2);
#pragma unroll 1
        for (int i = 0; i < 32; i++) {
          const bool tail = (i >> 1) == 12;
          const int kb = tail ? i + 6 : i < 24 ? i : i - 2;
          if (!(i & 7)) mbar_wait_c(bars + B_RT + i, L);
          if (i == 24) mbar_wait_c(bars + B_WT + w * 8, 1);
          if (!tail) mbar_wait(bars + B_FULL + c.s * 8, c.ph ^ 1);
          uint4 x[2];
#pragma unroll
          for (int e = 0; e < 2; e++) x[e] = lds128(!tail ? sb + c.s * ST_BYTES + ro + ((x0 ^ e) << 4) : sb + SM_WT + w * 3200 + (lane >> 2) * 400 + (i - 24) * 256 + (lane & 3) * 32 + e * 16);
          if (!tail) {
            __syncwarp();
            if (el) mbar_arrive(bars + B_AD + c.s * 8);
            c.next();
          }
#pragma unroll
          for (int e = 0; e < 2; e++) {
            const uint4 a = x[e], m = lds128(sb + SM_RT + 4096 + kb * 128 + (lane & 3) * 32 + e * 16);
            cv = fmaf(blo(a.x), blo(m.x), fmaf(bhi(a.x), bhi(m.x), fmaf(blo(a.y), blo(m.y), fmaf(bhi(a.y), bhi(m.y), cv))));
            cv = fmaf(blo(a.z), blo(m.z), fmaf(bhi(a.z), bhi(m.z), fmaf(blo(a.w), blo(m.w), fmaf(bhi(a.w), bhi(m.w), cv))));
          }
          if (i == WTI) {
            uint32_t id2 = id;
            asm volatile("" : "+r"(id2));
            expect_tx_p(el, bars + B_WT + w * 8, 3072);
#pragma unroll 1
            for (int r = 0; r < 8; r++)
              bulk_load_p(el, sb + SM_WT + w * 3200 + r * 400, (const uint8_t*)Q.w_sp + (64 * (id2 & 30) + 16 * (id2 >> 5) + 2 * r + w) * (SEQ * 2) + 28 * 128, 384, bars + B_WT + w * 8);
          }
        }
        }
        AGENT_IDS;
        TRC(el, 3, w * 32 + L * 16 + 11);
        asm volatile("" : "+r"(t8));
        const uint32_t tag = (t8 >> 2) - 1 + L;
        cv = qsum(cv);
        uint2* const cs = (uint2*)(Q.XST + hw * 128 + 1);
        if ((lane & 3) == 0) ll_st64(cs + 32 * j + (lane >> 2) * 4, __float_as_uint(cv), tag);
#pragma unroll 1
        for (int it = 0; it < (1 << 22); it++) {
          const uint2 a = ll_ld64(cs + 4 * lane), b = ll_ld64(cs + 128 + 4 * lane);
          if (__all_sync(~0u, a.y == tag && b.y == tag)) { sts32(sb + SM_CV + w * 256 + lane * 4, a.x); sts32(sb + SM_CV + w * 256 + 128 + lane * 4, b.x); break; }
        }
        __syncwarp();
        if (el) mbar_arrive(bars + B_CV + w * 8);
        TRC(el, 3, w * 32 + L * 16 + 12);
#pragma unroll 1
        for (int kb = 30; kb < 32; kb++) {
          mbar_wait_c(bars + B_FULL + c.s * 8, c.ph ^ 1);
          if (el) mbar_arrive(bars + B_AD + c.s * 8);
          c.next();
        }
        c.ph ^= ((c.s + 11) >> 2) & 1; c.s = (c.s + 11) & 3;
        if (L == 0) {
          mbar_wait_c(ev + EV_PT * 8, 0);
          flag_add_p(el, fj + FJ_P4);
        }
      }
    } else {
      const uint32_t epoch = ldcg32(fj + FJ_EP + rb);
      mbar_wait(bars + B_IMG, 0);
      TRC(el, 2, 41);
      flag_release_p(el, fj + FJ_WQ);
      TRC(el, 2, 42);
#pragma unroll 1
      for (int L = 0; L < 2; L++) {
        float* const csf = Q.CSP + (NCTA + bid) * 216;
        if (L == 0) {
          flag_wait(fj + FJ_WQ, (epoch + 1) * 16);
          fence_async_g();
          expect_tx_p(el, bars + B_XRW, 13824);
          bulk_load_p(el, sb + ST_BYTES + SM_WOI, Q.CSP + j * 16 * 216, 6912, bars + B_XRW);
          bulk_load_p(el, sb + 2 * ST_BYTES + SM_WOI, Q.CSP + (j * 16 + 8) * 216, 6912, bars + B_XRW);
          mbar_wait(bars + B_XRW, 0);
#pragma unroll 1
          for (int f = lane; f < 54; f += 32) {
            float s[4] = {0.f, 0.f, 0.f, 0.f};
#pragma unroll 2
            for (int r = 0; r < 16; r++) {
              const uint4 v = lds128(sb + ST_BYTES + SM_WOI + (r >> 3) * ST_BYTES + (r & 7) * 864 + f * 16);
              s[0] += __uint_as_float(v.x); s[1] += __uint_as_float(v.y); s[2] += __uint_as_float(v.z); s[3] += __uint_as_float(v.w);
            }
            sts128(sb + SM_CSQ + f * 16, __float_as_uint(s[0]), __float_as_uint(s[1]), __float_as_uint(s[2]), __float_as_uint(s[3]));
            stg128(csf + f * 4, __float_as_uint(s[0]), __float_as_uint(s[1]), __float_as_uint(s[2]), __float_as_uint(s[3]));
          }
          __syncwarp();
          if (el) mbar_arrive(bars + B_XRW + 8);
          TRC(el, 2, 43);
          mbar_wait(bars + B_WOI, 0);
          bulk_store_p(el, Q.WO + j * WO_SL + rb * (41 * 128), sb + SM_WOI, (rb < 15 ? 41 : 33) * 128);
          publish_p(el, fj + FJ_WO);
          TRC(el, 2, 44);
          if (el) prefetch_l2((const uint8_t*)Q.w_in + bid * 41472, 41472);
          float o0 = 0.f, o1 = 0.f;
#pragma unroll 1
          for (int u = 0; u < 2; u++) {
            const uint8_t* src = (u ? (const uint8_t*)Q.w_sp + 500 * (SEQ * 2) + 2048 : (const uint8_t*)Q.w_in + 100 * (2 * FH * 2) + FH * 2) + lane * 16;
            const uint4 a = ldnc128(src), b = ldnc128(src + 300 * (2 * FH * 2) + 2048);
            const uint32_t x[8] = {a.x, a.y, a.z, a.w, b.x, b.y, b.z, b.w};
            float sq = 0.f;
#pragma unroll
            for (int e = 0; e < 8; e++) sq = fmaf(blo(x[e]), blo(x[e]), fmaf(bhi(x[e]), bhi(x[e]), sq));
            o0 = o1;
            asm("sqrt.approx.f32 %0, %1;" : "=f"(o1) : "f"(wsum(sq) * (u ? C0S * C0S * SEQ / 512.f : 2.f * GA * GA * DM / 512.f)));
          }
          const uint32_t off = (__float_as_uint(o0) & 0x7f800000u) >> 16 | 0x8000u | OFM;
          const uint32_t c0 = min(max(__float_as_uint(o1) & 0x7f800000u, 0x04000000u), 0x7e000000u) | 0x00400000u;
          if (el) sts128(sb + SM_OFF, off * 0x10001u, c0, __float_as_uint(GB), ((c0 >> 16) - 0x200u) * 0x10001u);
        }
        mbar_wait(bars + B_EVT + EV_O * 8, L);
        mbar_wait(bars + B_EVT + (EV_N + EV_O) * 8, L);
        flag_release_p(el, Q.flags + rb * 64 + FR_OL + L);
#pragma unroll 1
        for (int w = 0; w < 2; w++) {
          mbar_wait(bars + B_EVT + (w * EV_N + EV_XS) * 8, L);
          if (!w) mbar_wait(bars + B_AF3 + 96 + XP0 * 8, L);
          if (el) asm volatile("cp.async.bulk.tensor.3d.global.shared::cta.tile.bulk_group [%0, {%2, %3, %4}], [%1];\ncp.async.bulk.commit_group;\ncp.async.bulk.wait_group.read 0;" ::"l"(&P.res[1]), "r"(sb + SM_STG + 9216), "r"(j * 72), "r"(rb * 64 + (w ^ 1) * 32), "r"(0) : "memory");
          __syncwarp();
          if (lane < 2 && !w) mbar_arrive(bars + B_S5);
        }
        sts64(sb + SM_CV + 512 + lane * 8, 0x3f803f80u, 0x3f803f80u);
        fence_async_s();
        __syncwarp();
        if (el) { asm volatile("cp.async.bulk.wait_group 0;" ::: "memory"); mbar_arrive(bars + B_GATE3); }
        const uint32_t tag = epoch * 2 + L + 1;
        asm volatile("" : "+r"(lane));
#pragma unroll 1
        for (int b = 0; b < 8; b++) {
          if (!(b & 3)) {
            const int mb = b >> 2;
            mbar_wait(bars + B_ZS + mb * 8, L);
            pause<ZD1>(Q.zero);
            TRC(el && !mb, 2, L * 16 + 8);
            uint4 v;
#pragma unroll 1
            for (int it = 0; it < (1 << 22); it++) {
              v = ll_ld128(Q.ZST + ((rb * 2 + mb) * 8 + (lane >> 2)) * 32 + 4 * j + (lane & 3));
              if (__all_sync(~0u, max(max(v.x, v.y), max(v.z, v.w)) != ~0u)) break;
            }
            const bool o = lane & 16;
            float ss = __uint_as_float(o ? v.y : v.x) + __shfl_xor_sync(~0u, __uint_as_float(o ? v.x : v.y), 16), sq = __uint_as_float(o ? v.w : v.z) + __shfl_xor_sync(~0u, __uint_as_float(o ? v.z : v.w), 16);
            ss += __shfl_xor_sync(~0u, ss, 4); sq += __shfl_xor_sync(~0u, sq, 4); ss += __shfl_xor_sync(~0u, ss, 8); sq += __shfl_xor_sync(~0u, sq, 8);
            const float mean = ss * (1.f / FH), rs = blo(pack2(rsq_fast(fmaxf(fmaf(sq, 1.f / FH, -mean * mean), 0.f) + 4.f * GA * GA * LN_EPS), 0.f));
            if (!(lane & 12)) ll_st64(Q.RT + (mb * 16 + rb) * 64 + 8 * j + 2 * (lane & 3) + (lane >> 4), pack2(rs, rs * (mean - blo(lds32(sb + SM_OFF)))), tag);
            TRC(el && !mb, 2, L * 16 + 10);
            pause<ZD2>(Q.zero);
          }
          uint4 v[4];
#pragma unroll 1
          for (int it = 0; it < (1 << 22); it++) {
            bool ok = true;
#pragma unroll
            for (int u = 0; u < 4; u++) { v[u] = ll_ld128((const uint4*)Q.RT + b * 128 + u * 32 + lane); ok = ok && v[u].y == tag && v[u].w == tag; }
            if (__all_sync(~0u, ok)) break;
          }
#pragma unroll
          for (int u = 0; u < 4; u++) {
            const uint32_t rt = sb + SM_RT + b * 512 + u * 128, ro = (lane >> 3) * 32 + (lane & 3) * 8 + ((lane >> 2) & 1) * 2;
            sts32(rt + 4096 + lane * 4, __byte_perm(v[u].x, v[u].z, 0x7632));
            asm volatile("st.shared.u16 [%0], %1;\nst.shared.u16 [%0 + 4], %2;" ::"r"(rt + ro), "h"((uint16_t)v[u].x), "h"((uint16_t)v[u].z) : "memory");
          }
          __syncwarp();
          if (el && (b & 1)) mbar_arrive(bars + B_RT + (b - 1) * 4);
          TRC(el && b < 2, 2, L * 16 + 11 + b);
        }
        TRC(el, 2, L * 16 + 9);
        mbar_wait(bars + B_EVT + EV_Z1 * 8, L);
        mbar_wait(bars + B_EVT + (EV_N + EV_Z1) * 8, L);
        fence_gpu();
        if (el) mbar_arrive(bars + B_Z1);
      }
    }
  } else {
    int w = wid >> 2, q = wid & 3, rb = bid & 15, j = bid >> 4;
    int g = lane >> 2, t = lane & 3;
#define PHASE asm volatile("" : "+r"(w), "+r"(q), "+r"(rb), "+r"(j))
#define stg (sb + SM_STG + w * 9216)
    const bool tr = (tid & 127) == 0;
    (void)tr;
    Cur c{0, 0};
    const uint32_t ebar = mapa(bars + B_EMPTY, (bid & 1) ^ (lane & 1));
    auto release = [&](uint32_t s) { if (lane < 2) mbar_arrive_cluster(ebar + s * 8); };
    uint32_t ia = 0;
    auto wait_ab = [&]() { mbar_wait_c(bars + B_FULL + c.s * 8, c.ph); mbar_wait_c(bars + B_FULLA + w * 32 + c.s * 8, (ia >> c.s) & 1); ia ^= 1u << c.s; };
    uint32_t lagph = 0;
    auto yield = [&](int left, int lag) { if (w == 1 && left == lag) mbar_wait_c(bars + B_LAG, lagph); };
    auto yield_done = [&]() { if (w == 0 && lane == 0) mbar_arrive(bars + B_LAG); };
    uint32_t rp = 0;
    auto check = [&](auto n, uint32_t dst, const uint8_t* src) {
      const uint32_t a = dst + lane * 32 + (lane >> 2) * 4;
#pragma unroll 1
      for (int it = 0; it < (1 << 16); it++) {
        uint32_t x = lds32(a);
#pragma unroll
        for (int e = 1; e < n.value; e++) x = max(x, lds32(a + e * 1024));
        if (!__any_sync(~0u, x == ~0u)) break;
        fence_async_s();
        __syncwarp();
        const uint32_t el = elect_one();
        expect_tx_p(el, bars + B_RB + q * 8, n.value * 1024);
        bulk_load_p(el, dst, src, n.value * 1024, bars + B_RB + q * 8);
        mbar_wait_c(bars + B_RB + q * 8, rp & 1);
        rp++;
      }
    };
    auto signal = [&](int e) { __syncwarp(); if (lane == 0) mbar_arrive(bars + B_EVT + w * EV_N * 8 + e * 8); };
    TRC(tr, w, 0);

    {
      uint8_t* dst = Q.WQ + j * WQ_SL + rb * 3456 + tid * 16;
#pragma unroll
      for (int u = 0; u < 5; u++) {
        stg128_if((u < 4 || rb < 8) && tid < 216, dst + u * (16 * 3456), wv[u].x, wv[u].y, wv[u].z, wv[u].w);
        if (u == 0) TRC(tr, w, 60);
      }
      if (Q.zero == 0) {
        float s[8];
#pragma unroll
        for (int u = 0; u < 5; u++) {
          const uint32_t x[4] = {wv[u].x, wv[u].y, wv[u].z, wv[u].w};
#pragma unroll
          for (int e = 0; e < 4; e++) { s[2 * e] = u ? s[2 * e] + blo(x[e]) : blo(x[e]); s[2 * e + 1] = u ? s[2 * e + 1] + bhi(x[e]) : bhi(x[e]); }
        }
#pragma unroll
        for (int m = 4; m; m >>= 1) {
#pragma unroll
          for (int e = 0; e < m; e++) s[e] = ((tid & m) ? s[e + m] : s[e]) + __shfl_xor_sync(~0u, (tid & m) ? s[e] : s[e + m], m);
        }
        stg32_if(tid < 216, Q.CSP + bid * 216 + tid, __float_as_uint(s[0]));
      }
      __syncwarp();
      if (lane == 0) mbar_arrive(bars + B_IMG);
    }
    reg_alloc<224>();
    auto fetch_wo = [&]() {
#pragma unroll 1
      for (int u = tid; u < 328; u += 256) {
        const int m = min(41 * rb + (u >> 3), 647), k8 = m / 9;
        cp_async16(sb + SM_WOI + u * 16, (const uint8_t*)Q.wo + (8 * k8 + (u & 7)) * (DM * 2) + (72 * j + 8 * (m - k8 * 9)) * 2);
      }
    };
    const uint32_t epoch = ldcg32(Q.flags + (rb * 2 + w) * 32 + FR_EP + j);
    TRC(tr, w, 1);

#pragma unroll 1
    for (int L = 0; L < 2; L++) {
      const int tb = 2 + L * 24;
      asm volatile("" : "+r"(lane), "+r"(g), "+r"(t));
      PHASE;
      (void)tb;
      const uint32_t tag = epoch * 2 + L + 1;
      {
        uint32_t Pk[27][2];
        float rk[2][2], sc[2][2];
        const bool up0 = 2 * t > g, up1 = 2 * t + 1 > g;
        constexpr int HA_[6] = {0, 2, 4, 7, 12, 15}, HC_[6] = {6, 9, 10, 11, 14, 17};
        const bool remote = q == 0 && rb > 0;
        uint4* hp = Q.HALO + ((((rb - (q == 0)) * 2 + w) * 8 + j) * 6) * 32 + lane;
        const uint32_t att = 2 * ST_BYTES + w * 8192 + lane * 16;
        const uint8_t* hs = remote ? (const uint8_t*)hp : smem_raw + att + (q == 3 ? ST_BYTES : q == 2 ? 3072 : 0);
        uint8_t* od = z1_block(rb, (q >> 1) ^ 1, 0) + (9 * j) * 1024 + (4 * (q & 1) + w) * 128 + lane * 4;
        ACLK_INIT;
        {
          float acc[108];
#pragma unroll
          for (int i = 0; i < 108; i++) acc[i] = 0.f;
          float sx[2] = {0.f, 0.f}, sq[2] = {0.f, 0.f};
          uint32_t prev = 0;
#pragma unroll 1
          for (int kb = 0; kb < 7; kb++) {
            wait_ab();
            TRC(tr && kb == 0, w, tb + 0);
            PCLK(kb * 4);
            const uint32_t st = sb + c.s * ST_BYTES, da = dlo(st + w * 8192, 16), db = dlo(st + ST_B, 3456);
            wgmma_fence();
#pragma unroll
            for (int kk = 0; kk < 4; kk++) {
              wgmma_ss_n216(acc, dsc<1024, 1>(da, kk * 32), dsc<128, 0>(db, kk * 6912), 1);
              if (kk == 0) { wgmma_commit(); wgmma_wait<1>(); if (kb > 0) release(prev); }
              if (kk == 3) wgmma_commit();
              if (kk == XK1) {
            if (kb >= KS && kb < KS + 3) {
              mbar_wait_c(bars + B_WT + w * 8, 0);
#pragma unroll
              for (int u = 0; u < 3; u++) {
                const uint2 x = lds64(stg + (2 * q + (lane >> 4)) * 1152 + (lane & 15) * 8 + (kb - KS) * 384 + u * 128);
                sx[0] += blo(x.x) + bhi(x.x); sx[1] += blo(x.y) + bhi(x.y);
                sq[0] = fmaf(blo(x.x), blo(x.x), fmaf(bhi(x.x), bhi(x.x), sq[0])); sq[1] = fmaf(blo(x.y), blo(x.y), fmaf(bhi(x.y), bhi(x.y), sq[1]));
              }
            }
            if (kb == KS + 3) {
              const bool o = lane & 1;
              float v = (o ? sq[0] + sq[1] : sx[0] + sx[1]) + __shfl_xor_sync(~0u, o ? sx[0] + sx[1] : sq[0] + sq[1], 1);
              v += __shfl_xor_sync(~0u, v, 2); v += __shfl_xor_sync(~0u, v, 4); v += __shfl_xor_sync(~0u, v, 8);
              const float m = v * (-1.f / DM), r = rsq_fast(fmaxf(fmaf(__shfl_xor_sync(~0u, v, 1), 1.f / DM, -m * m), 0.f) + LN_EPS);
              ll_st128_if(!(lane & 15), Q.XST + (rb * 2 + w) * 128 + 16 * j + 4 * q + (lane >> 3), m, r, tag);
            }
              }
              if (kk == XK2 && L == 0) {
            if (kb == 0) fetch_wo();
            if (kb == 3) {
              asm volatile("cp.async.wait_all;" ::: "memory");
              fence_async_s();
              __syncwarp();
              if (lane == 0) mbar_arrive(bars + B_WOI);
            }
              }
            }
            prev = c.s; c.next();
          }
          const uint32_t ls = sb + L * (3 * ST_BYTES), cs = ls + SM_CSQ + t * 8;
          float2 cv[27];
          mbar_wait_c(bars + B_XRW + 8, L);
#pragma unroll
          for (int kb = 7; kb < 9; kb++) {
            wait_ab();
            yield(9 - kb, LAG1);
            PCLK(kb * 4);
            const uint32_t st = sb + c.s * ST_BYTES, da = dlo(st + w * 8192, 16), db = dlo(st + ST_B, 3456);
            wgmma_fence();
#pragma unroll
            for (int kk = 0; kk < 4; kk++) {
              wgmma_ss_n216(acc, dsc<1024, 1>(da, kk * 32), dsc<128, 0>(db, kk * 6912), 1);
              if (kk == 0) { wgmma_commit(); wgmma_wait<1>(); release(prev); }
              if (kb == 7 && kk < 3) {
#pragma unroll
                for (int G = 9 * kk; G < 9 * kk + 9; G++) cv[G] = lds64f(cs + G * 32);
                wgmma_fence();
              }
            }
            wgmma_commit();
            prev = c.s; c.next();
          }
          yield_done();
          mbar_wait_c(bars + B_CSQ, L);
          const uint32_t xs = ls + SM_XST + w * 768 + 256 + q * 128;
          const float2 n0 = lds64f(xs + g * 8), n1 = lds64f(xs + g * 8 + 64);
          const float m0 = n0.x, m1 = n1.x;
#pragma unroll
          for (int u = 0; u < 4; u++) {
            rk[u >> 1][u & 1] = __uint_as_float(lds32(xs + t * 16 + ((u & 1 ? up1 : up0) ? -64 : 0) + (u & 1) * 8 + (u >> 1) * 64 + 4));
            sc[u >> 1][u & 1] = rk[u >> 1][u & 1] * ((u >> 1 ? n1.y : n0.y) * (0.23570226039551584f * 1.4426950408889634f));
          }
          PCLK(36);
          wgmma_wait<0>();
          PCLK(37);
          release(prev);
          lagph ^= 1;
          TRC(tr, w, tb + 1);
          ACLK(0);
#pragma unroll
          for (int G = 9; G < 27; G++) Pk[G][1] = pack2(fmaf(m1, cv[G].x, acc[4 * G + 2]), fmaf(m1, cv[G].y, acc[4 * G + 3]));
          if (q < 3) {
#pragma unroll
            for (int i = 0; i < 6; i++) sts128(sb + att + (q >> 1) * ST_BYTES + (q & 1) * 3072 + i * 512, Pk[9 + HA_[i]][1], Pk[10 + HA_[i]][1], tag, Pk[9 + HC_[i]][1]);
          } else if (rb < 15) {
#pragma unroll
            for (int i = 0; i < 6; i++) ll_st128(hp + i * 32, __uint_as_float(Pk[9 + HA_[i]][1]), __uint_as_float(Pk[10 + HA_[i]][1]), tag, __uint_as_float(Pk[9 + HC_[i]][1]));
          }
#pragma unroll
          for (int G = 0; G < 27; G++) {
            Pk[G][0] = pack2(fmaf(m0, cv[G].x, acc[4 * G]), fmaf(m0, cv[G].y, acc[4 * G + 1]));
            if (G < 9) Pk[G][1] = pack2(fmaf(m1, cv[G].x, acc[4 * G + 2]), fmaf(m1, cv[G].y, acc[4 * G + 3]));
          }
        }
        ACLK(1);
        constexpr int GA_[4] = {0, 2, 4, 7}, GB_[4] = {1, 3, 5, 8}, GC_[4] = {2, 4, 6, 6};
        float S1[4][4], S2[4][4];
        uint32_t qa[4][2], qc[4][2];
#pragma unroll
        for (int h = 0; h < 4; h++) {
#pragma unroll
          for (int r = 0; r < 2; r++) {
            qa[h][r] = (h == 0 || h == 3 || t >= h) ? Pk[GA_[h]][r] : 0u;
            qc[h][r] = (h == 3 ? t == 3 : t <= h) ? Pk[GC_[h]][r] : 0u;
          }
#pragma unroll
          for (int i = 0; i < 4; i++) S1[h][i] = S2[h][i] = 0.f;
          mma16(S1[h], qa[h][0], qa[h][1], Pk[GB_[h]][0], Pk[GB_[h]][1], Pk[9 + GA_[h]][0], Pk[9 + GB_[h]][0]);
          mma16(S2[h], qa[h][0], qa[h][1], Pk[GB_[h]][0], Pk[GB_[h]][1], Pk[9 + GA_[h]][1], Pk[9 + GB_[h]][1]);
        }
#pragma unroll
        for (int h = 0; h < 4; h++) {
          mma8(S1[h], qc[h][0], qc[h][1], Pk[9 + GC_[h]][0]);
          mma8(S2[h], qc[h][0], qc[h][1], Pk[9 + GC_[h]][1]);
        }
        uint32_t V1[9], V2[9];
#pragma unroll
        for (int i = 0; i < 9; i++) { V1[i] = movm(Pk[18 + i][0]); V2[i] = movm(Pk[18 + i][1]); }
        uint4 hv[6];
#pragma unroll
        for (int i = 0; i < 6; i++) hv[i] = ll_ld128g(hs + i * 512);
        const uint32_t mup = (up0 ? 0xffffu : 0u) | (up1 ? 0xffff0000u : 0u);
        auto finish = [&](const float (&x0)[4], const float (&x1)[4], const uint32_t (&Vb)[9], uint32_t ma, int hi) {
          uint32_t p[4], n[4];
          float rs[4];
#pragma unroll
          for (int h = 0; h < 4; h++) {
            const float m = qmax(fmaxf(x0[h], x1[h])), e0 = ex2(x0[h] - m), e1 = ex2(x1[h] - m);
            n[h] = pack2(e0, e1);
            p[h] = pack2(e0 * rk[hi][0], e1 * rk[hi][1]);
          }
#pragma unroll
          for (int h = 0; h < 4; h += 2) {
            float D[4] = {0.f, 0.f, 0.f, 0.f};
            mma8(D, n[h], n[h + 1], 0x3f803f80u);
            rs[h] = rcp_fast(D[0]); rs[h + 1] = rcp_fast(D[2]);
          }
#pragma unroll
          for (int i = 0; i < 9; i++) {
            const int h = i < 4 ? 0 : i == 4 ? 1 : 2;
            const bool nx = (i == 2 || i == 4 || i == 6) ? 2 * t >= i : i == 3 || i > 6;
            float O[4] = {0.f, 0.f, 0.f, 0.f};
            mma16(O, p[h] & ma, p[h + 1] & ma, p[h] & ~ma, p[h + 1] & ~ma, V1[i], Vb[i]);
            const float r = nx ? rs[h + 1] : rs[h];
            stg32(od + i * 1024 + hi * 256, pack2((nx ? O[2] : O[0]) * r, (nx ? O[3] : O[1]) * r));
          }
        };
        {
          float x0[4], x1[4];
#pragma unroll
          for (int h = 0; h < 4; h++) { x0[h] = (up0 ? S1[h][2] : S2[h][2]) * sc[1][0]; x1[h] = (up1 ? S1[h][3] : S2[h][3]) * sc[1][1]; }
          finish(x0, x1, V2, mup, 1);
        }
        ACLK(2);
        bar_sync(1 + w, 128);
#pragma unroll 1
        for (int it = 0; it < (1 << 20); it++) {
          if (remote) {
            bool ok = true;
#pragma unroll
            for (int i = 0; i < 6; i++) ok = ok && hv[i].z == tag;
            if (__all_sync(~0u, ok)) break;
          }
#pragma unroll
          for (int i = 0; i < 6; i++) hv[i] = ll_ld128g(hs + i * 512);
          if (!remote) break;
        }
        uint32_t H[18];
#pragma unroll
        for (int i = 0; i < 6; i++) { H[HA_[i]] = hv[i].x; H[HA_[i] + 1] = hv[i].y; H[HC_[i]] = hv[i].w; }
        float S0[4][4];
#pragma unroll
        for (int h = 0; h < 4; h++) {
#pragma unroll
          for (int i = 0; i < 4; i++) S0[h][i] = 0.f;
          mma16(S0[h], qa[h][0], qa[h][1], Pk[GB_[h]][0], Pk[GB_[h]][1], H[GA_[h]], H[GB_[h]]);
        }
#pragma unroll
        for (int h = 0; h < 4; h++) mma8(S0[h], qc[h][0], qc[h][1], H[GC_[h]]);
        uint32_t V0[9];
#pragma unroll
        for (int i = 0; i < 9; i++) V0[i] = movm(H[9 + i]);
        ACLK(3);
        {
          const bool nohalo = (rb | q) == 0;
          const float b0 = up0 && nohalo ? -INFINITY : 0.f, b1 = up1 && nohalo ? -INFINITY : 0.f;
          float x0[4], x1[4];
#pragma unroll
          for (int h = 0; h < 4; h++) { x0[h] = fmaf(up0 ? S0[h][0] : S1[h][0], sc[0][0], b0); x1[h] = fmaf(up1 ? S0[h][1] : S1[h][1], sc[0][1], b1); }
          finish(x0, x1, V0, ~mup, 0);
        }
        ACLK(4);
        __syncwarp();
        if (lane == 0) mbar_arrive(bars + B_EVT + (EV_N * (q < 2) + EV_O) * 8);
        ACLK_OUT;
        TRC(tr, w, tb + 2);
      }
      if (c.s) { c.s = 0; c.ph ^= 1; }
      PHASE;
      {
        float acc[36];
        const int hw = rb * 2 + w;
        const uint32_t xt = stg + (8 * q + g) * 144 + t * 4;
        uint32_t xm = sb + SM_STG + 9216 + (8 * q + (lane & 7)) * 144 + (lane & 8) * 576 + (lane & 16);
        uint8_t* xn = xn_block(hw) + j * 9216 + q * 256 + lane * 4;
        uint32_t* sp = (uint32_t*)(Q.ST1 + (hw * 8 + j) * 32 + 8 * q) + lane;
        const uint4* sg = Q.ST1 + (hw * 8 + t) * 32 + 8 * q + g;
        asm volatile("" : "+r"(xm), "+l"(xn), "+l"(sp), "+l"(sg));
        mbar_wait_c(bars + B_RES + w * 8, L);
        TRC(tr, w, tb + 21);
#pragma unroll
        for (int i = 0; i < 18; i++) { const uint32_t x = lds32(xt + (i >> 1) * 16 + (i & 1) * 4608); acc[2 * i] = blo(x); acc[2 * i + 1] = bhi(x); asm volatile("" : "+f"(acc[2 * i]), "+f"(acc[2 * i + 1])); }
        mbar_wait_c(bars + B_WF, L);
        const uint32_t db = dlo(sb, 1152), of = bars + (w ? B_OF + 40 : B_AV + 96);
        uint32_t da[5];
#pragma unroll
        for (int e = 0; e < 5; e++) da[e] = __shfl_sync(~0u, dlo(sb + o_place(w, e), 1024), 0);
        if (w) {
#pragma unroll 1
          for (int kb = q ^ 2; kb < 9; kb += 4) {
            const uint32_t e = (kb + 1) >> 1;
            mbar_wait_c(bars + B_OF + e * 8, L);
            check(Int<8>{}, sb + o_place(0, e) + (kb && !(kb & 1)) * 8192, z1_block(rb, 0, 0) + kb * 8192);
            if (lane <= !kb) mbar_arrive(bars + B_AV + (12 + e) * 8);
          }
          bar_sync(7, 256);
        }
        mbar_wait_c(of, L & w);
        TRC(tr, w, tb + 3);
        wgmma_fence();
#pragma unroll
        for (int kk = 0; kk < 4; kk++) wgmma_ss_n72(acc, dsc<128, 0>(da[0], kk * 2048), dsc<128, 0>(db, kk * 2304), 1);
        wgmma_commit();
#pragma unroll 1
        for (int h = 0; h < 2; h++) {
#pragma unroll
          for (int u = 0; u < 4; u++) {
            if (!(u & 1)) { mbar_wait_c(of + 8 + h * 16 + u * 4, 1 + 2 * h + (u >> 1) < SPL ? L & w : L); wgmma_fence(); }
            if (u == 3 && h && !w) bar_arrive(7, 256);
#pragma unroll
            for (int kk = 0; kk < 4; kk++) wgmma_ss_n72(acc, dsc<128, 0>(da[1 + (u >> 1)], (u & 1) * 8192 + kk * 2048), dsc<128, 0>(db + h * 2304, (1 + u) * 9216 + kk * 2304), 1);
            if (u != 2) wgmma_commit();
            if (u == 0) { wgmma_wait<1>(); if (lane + w == 0 && h) mbar_arrive(bars + B_X3); }
          }
          da[1] = da[3]; da[2] = da[4];
        }
        RCLK_INIT;
        wgmma_wait<0>();
        RCLK(0);
        if (lane < 2) mbar_arrive_cluster(ebar + B_XD - B_EMPTY + w * 8);
        TRC(tr && P5TRACE != 5, w, tb + 4);
        {
          float s0 = 0.f, s1 = 0.f, q0 = 0.f, q1 = 0.f;
#pragma unroll
          for (int i = 0; i < 36; i++) {
            if (i & 2) { s1 += acc[i]; q1 = fmaf(acc[i], acc[i], q1); } else { s0 += acc[i]; q0 = fmaf(acc[i], acc[i], q0); }
          }
          const bool o1 = t & 1, o2 = t & 2;
          const float ss = (o1 ? s1 : s0) + __shfl_xor_sync(~0u, o1 ? s0 : s1, 1), sq = (o1 ? q1 : q0) + __shfl_xor_sync(~0u, o1 ? q0 : q1, 1);
          const float v = (o2 ? sq : ss) + __shfl_xor_sync(~0u, o2 ? ss : sq, 2);
          asm volatile("st.relaxed.gpu.global.u32 [%0], %1;" ::"l"(sp), "r"(__float_as_uint(v)) : "memory");
        }
        RCLK(1);
        RCLK(2);
        pause<PDEL>(Q.zero);
        uint4 pa, pb;
        auto there = [&](const uint4& a, const uint4& b) { return __all_sync(~0u, max(max(max(a.x, a.y), max(a.z, a.w)), max(max(b.x, b.y), max(b.z, b.w))) != ~0u); };
#pragma unroll 1
        for (int it = 0; it < (1 << 20); it++) {
          pa = ll_ld128(sg); pb = ll_ld128(sg + 128);
          if (there(pa, pb)) break;
        }
        RCLK(3);
        float mean0 = qsum(__uint_as_float(pa.x) + __uint_as_float(pb.x)) * (-1.f / DM), mean1 = qsum(__uint_as_float(pa.y) + __uint_as_float(pb.y)) * (-1.f / DM);
        const float rs0 = GA * rsq_fast(fmaxf(fmaf(qsum(__uint_as_float(pa.z) + __uint_as_float(pb.z)), 1.f / DM, -mean0 * mean0), 0.f) + LN_EPS);
        const float rs1 = GA * rsq_fast(fmaxf(fmaf(qsum(__uint_as_float(pa.w) + __uint_as_float(pb.w)), 1.f / DM, -mean1 * mean1), 0.f) + LN_EPS);
        mean0 *= rs0; mean1 *= rs1;
#pragma unroll
        for (int i = 0; i < 18; i++) {
          const float a = (i & 1) ? rs1 : rs0, b = (i & 1) ? mean1 : mean0;
          stg32(xn + (i >> 1) * 1024 + (i & 1) * 128, pack2(fmaf(acc[2 * i], a, b), fmaf(acc[2 * i + 1], a, b)));
        }
        signal(EV_X1);
        RCLK(4);
        if (w) {
#pragma unroll 1
          for (int u = q; u < 24; u += 4) {
            const uint32_t mb = u < 2 * SPL ? u >= SPL : u & 1, k = u < 2 * SPL ? u - mb * SPL : u >> 1;
            mbar_wait_c(bars + B_AF3 + mb * 96 + k * 8, L);
            SCLK3(u);
            check(Int<6>{}, sb + k * 12288 + mb * 6144, xn_block(rb * 2 + mb) + k * 6144);
            SCLK3(24 + u);
            if (lane <= (u < 2 * SPL)) mbar_arrive(bars + B_AV + (u < SPL ? 12 + k : k) * 8);
          }
          TRVI(lane == 0 && P5TRACE != 5, 5, 56 + L * 4 + q, rp);
          mbar_wait_c(bars + B_S5, L);
        }
#pragma unroll
        for (int u = 0; u < 4; u++)
          stsm4(xm + u * 32, pack2(acc[8 * u], acc[8 * u + 1]), pack2(acc[8 * u + 2], acc[8 * u + 3]), pack2(acc[8 * u + 4], acc[8 * u + 5]), pack2(acc[8 * u + 6], acc[8 * u + 7]));
        asm volatile("stmatrix.sync.aligned.m8n8.x2.shared.b16 [%0], {%1,%2};" ::"r"(xm + 128), "r"(pack2(acc[32], acc[33])), "r"(pack2(acc[34], acc[35])) : "memory");
        fence_async_s();
        signal(EV_XS);
        RCLK(5);
        TRC(tr, w, tb + 5);
        RCLK(6);
        RCLK_OUT;
      }
      PHASE;
      {
      float acc[160];
#pragma unroll
      for (int i = 0; i < 160; i++) acc[i] = 0.f;
      float s[2] = {0.f, 0.f}, qq[2] = {0.f, 0.f}, zo = 0.f;
      const uint32_t zp = sb + SM_ZP3 + (tid & 127) * 4;
      auto zstat = [&](int mb, bool on) {
        const bool o1 = t & 1, o2 = t & 2;
        const float ss = ((o1 ? s[1] : s[0]) + __shfl_xor_sync(~0u, o1 ? s[0] : s[1], 1)) * 0x1p60f, sq = (o1 ? qq[1] : qq[0]) + __shfl_xor_sync(~0u, o1 ? qq[0] : qq[1], 1);
        const uint32_t v = __float_as_uint((o2 ? sq : ss) + zo + __shfl_xor_sync(~0u, o2 ? ss : sq, 2));
        asm volatile("{\n.reg .pred p, q, r;\nsetp.eq.u32 p, %4, 1;\nsetp.eq.u32 q, %4, 2;\nsetp.eq.and.u32 r, %5, 0, q;\n@p st.shared.u32 [%0], %2;\n@p bar.arrive 13, 256;\n"
                     "@q st.relaxed.gpu.global.u32 [%1], %2;\n@r mbarrier.arrive.shared::cta.b64 _, [%3];\n}" ::"r"(zp + mb * 512), "l"((uint32_t*)(Q.ZST + ((rb * 2 + mb) * 8 + j) * 32) + (tid & 127)),
                     "r"(v), "r"(bars + B_ZS + mb * 8), "r"(on ? 1 + w : 0), "r"(lane) : "memory");
        s[0] = s[1] = qq[0] = qq[1] = 0.f;
      };
      const uint32_t ebar3 = ebar + (B_E3 - B_EMPTY);
#pragma unroll 1
      for (int half = 0; half < 2; half++) {
        const bool big = half != w;
        auto rel3 = [&](int p) { if (lane < 2) mbar_arrive_cluster(ebar3 + p * 8); };
        auto pass = [&](auto nk) {
          constexpr int NK = nk.value;
          uint32_t d0 = dlo(sb, 1024), ph = half & ~w, af = bars + B_AV;
          const uint32_t db = dlo(sb + SM_B3, NK == 3 ? 6144 : 2048);
          const bool lead = NK == 3 && !half;
          if (lead) {
#pragma unroll
            for (int u = 0; u < 2 * SPL; u++) {
              const int mb = u / SPL, p = u % SPL;
              if (!mb) mbar_wait_c(bars + B_F3 + p * 8, 0);
              mbar_wait_c(af + (mb ? p : 12 + p) * 8, mb || p > 4 ? L : 1);
              TRC(tr && u == 0, w, tb + 6);
              SCLK2(u);
              if (p == 0) SCLK(mb * 4);
              wgmma_fence();
#pragma unroll
              for (int kk = 0; kk < 3; kk++) {
                wgmma_ss_n128(acc + mb * 80, dsc<128, 0>(d0, p * 12288 + kk * 2048 + mb * 6144), dsc<1024, 1>(db, p * 12288 + kk * 2048), p + kk > 0);
                if (kk == 0 && u > SPL) { wgmma_commit(); wgmma_wait<1>(); rel3(p - 1); }
              }
              wgmma_commit();
            }
          }
#pragma unroll 1
          for (int it = 0; it < 6 / NK; it++) {
#pragma unroll
            for (int p = 0; p < 6; p++) {
              if (p < SPL && lead && it == 0) continue;
              if (NK == 3) mbar_wait_c(af + p * 8, L);
              if (p == 0 && it == 0) bar_sync(6 + w, 256);
              mbar_wait_c(bars + B_F3 + p * 8, ph);
              TRC(tr && p == 0 && it == 0, w, tb + 6 + half * 4);
              if (lead) SCLK2(12 + it * 6 + p);
              if (NK == 2 ? !(p & 1) : p % 3 == 0) SCLK(half * 11 + (NK == 2 ? it * 3 + p / 2 : it * 2 + p / 3));
              wgmma_fence();
#pragma unroll
              for (int u = 0; u < 2 * NK; u++) {
                const int kk = u >> 1, mb = u & 1, e = p * NK + kk;
                const uint64_t da = dsc<128, 0>(d0, (e / 3) * 12288 + (e % 3) * 2048 + mb * 6144);
                if (NK == 3) wgmma_ss_n128(acc + mb * 80, da, dsc<1024, 1>(db, p * 12288 + kk * 2048), e > 0 || it > 0);
                else wgmma_ss_n160(acc + mb * 80, da, dsc<1024, 1>(db, p * 12288 + kk * 6144), e > 0 || it > 0);
                if (u == 0) { wgmma_commit(); wgmma_wait<1>(); if (p > 0 || it > 0) rel3((p + 5) % 6); }
                if (p * 8 + u == (NK == 2 ? HO3 : HO4) && it == 6 / NK - 1) bar_arrive(7 - w, 256);
              }
              wgmma_commit();
            }
            d0 += NK * 1536; af += 48;
            ph ^= 1;
          }
        };
        const int go = (j & 1) ? (big ? 0 : 20) : (big ? 16 : 0);
        const float* gbp = (const float*)(smem_raw + SM_OFF + 8);
        asm volatile("" : "+l"(gbp));
        uint8_t* zd = half ? z1_block(rb, 0, j) + go * 1024 + (q & 1) * 2048 + 1024 + (q >> 1) * 512 + lane * 16 : z2_block(rb, j) + q * 9216 + go * 128 + ((g & 3) * 2 + (g >> 2)) * 16 + t * 4;
        asm volatile("" : "+l"(zd));
        if (big) pass(Int<2>{}); else pass(Int<3>{});
        if (w) { bar_sync(13, 256); zo = __uint_as_float(lds32(zp + half * 512)); }
        if (half) zstat(1, true);
        const uint32_t off2 = lds32(sb + SM_OFF);
        wgmma_wait<0>();
        SCLK(half * 11 + 9);
        rel3(5);
        TRC(tr, w, tb + 7 + half * 4);
        auto gelu = [&](auto z2) {
          constexpr int NC = z2.value ? NC2 : NC1;
          float gate[NC], gb = GB, gn = GB;
          uint32_t qa[2][3] = {{0, 0, 0}, {0, 0, 0}};
#pragma unroll
          for (int e = 0; e < NC; e++) gate[e] = GB;
#pragma unroll
          for (int G = 0; G < 20; G++) {
            if (G == 16 && !big) break;
            if (G % (z2.value ? LD2 : LD1) == 0) { gb = gn; if (G < 20 - (z2.value ? LD2 : LD1)) asm volatile("ld.f32 %0, [%1];" : "=f"(gn) : "l"(gbp) : "memory"); }
#pragma unroll
            for (int r = 0; r < 2; r++) {
              float z[2];
              float& gt = gate[(G * 2 + r) % NC];
#pragma unroll
              for (int e = 0; e < 2; e++) {
                const float v = acc[4 * G + 2 * r + e];
                z[e] = fmaf(v, tanh_fast(v * fmaf(v, v, gt)), v);
                if (z2.value) { s[r] = fmaf(z[e], 0x1p-60f, s[r]); qq[r] = fmaf(z[e], z[e], qq[r]); }
              }
              const uint32_t pk = pack2(z[0], z[1]);
              if (z2.value) {
                stg32(zd + G * 128 + r * 4608, hsub2(pk, off2));
                gt = fmaf(qq[r], s[r], gb);
              } else {
                gt = fmaf(__uint_as_float(pk), 0x1p-60f, gb);
                if ((G & 3) == 3) stg128(zd + (G >> 2) * 4096 + r * (8 * ZB), qa[r][0], qa[r][1], qa[r][2], pk);
                else qa[r][G & 3] = pk;
              }
            }
          }
        };
#pragma unroll 1
        for (int mb = 0;; mb++) {
          if (half) gelu(Int<0>{}); else gelu(Int<1>{});
          if (mb) break;
          zstat(0, !half);
#pragma unroll
          for (int i = 0; i < 80; i++) acc[i] = acc[80 + i];
          zd += half ? -1024 : (int)(128 * ZB);
        }
        mbar_wait_c(bars + B_GATE3, L);
        signal(half ? EV_Z1 : EV_ZN);
        SCLK(half * 11 + 10);
        TRC(tr, w, tb + 8 + half * 4);
      }
      }
      PHASE;
      const uint32_t aoff = (w * 64 + q * 16 + (lane & 15)) * 128 + (((lane >> 4) ^ (lane & 7)) << 4);
      uint32_t hA[18][4];
      {
        float acc[144];
        {
          const uint32_t c16 = lds32(sb + SM_OFF + 12), a[4] = {c16, c16, c16, c16};
          wgmma_fence();
          wgmma_rs_n144(acc, a, dsc<0, 0>(dlo(sb + SM_CV + 512, 0), 0), 0);
          wgmma_rs_n144(acc + 72, a, dsc<0, 0>(dlo(sb + SM_CV + 512, 0), 128), 0);
          wgmma_commit();
        }
        uint32_t prev = 0;
        auto stage = [&](int kb, bool odd) {
          mbar_wait_c(bars + B_FULL + c.s * 8, c.ph);
          TRC(tr && kb == 0, w, tb + 13);
          SCLK(22 + kb);
          const uint32_t st = sb + c.s * ST_BYTES, db = dlo(st + ST_B, 4608), rt = sb + SM_RT + kb * 128 + t * 8;
          uint32_t a[4][4];
#pragma unroll
          for (int kk = 0; kk < 4; kk++) {
            uint32_t r[4];
            ldsm4(r, st + (aoff ^ (kk << 5)));
            const uint2 sc = lds64(rt + kk * 32);
            a[kk][0] = hmul2(__byte_perm(r[0], r[2], 0x5410), sc.x); a[kk][2] = hmul2(__byte_perm(r[0], r[2], 0x7632), sc.y);
            a[kk][1] = hmul2(__byte_perm(r[1], r[3], 0x5410), sc.x); a[kk][3] = hmul2(__byte_perm(r[1], r[3], 0x7632), sc.y);
          }
          if (!odd && kb + w == 0) bar_sync(6, 256);
          wgmma_fence();
#pragma unroll
          for (int i = 0; i < 8; i++) {
            const int kk = i & 3, hf = i >> 2;
            wgmma_rs_n144(acc + hf * 72, a[kk], dsc<128, 0>(db, kk * 9216 + hf * 2304), 1);
            if (i == 0) { wgmma_commit(); wgmma_wait<1>(); if (kb) release(prev); }
            if (i == 3) wgmma_commit();
          }
          wgmma_commit();
          prev = c.s; c.next();
        };
#pragma unroll 1
        for (int kb = 0; kb < 32; kb += 2) {
          if (!(kb & 7)) mbar_wait_c(bars + B_RT + kb, L);
          stage(kb, false);
          stage(kb + 1, true);
        }
        mbar_wait_c(bars + B_CV + w * 8, L);
        const float gk = 0.5f / GA;
        const float c1 = __uint_as_float(lds32(sb + SM_OFF + 4));
        const float gb0 = -gk * (c1 + __uint_as_float(lds32(sb + SM_CV + w * 256 + (16 * q + g) * 4))), gb1 = -gk * (c1 + __uint_as_float(lds32(sb + SM_CV + w * 256 + (16 * q + g + 8) * 4)));
        if (w == 1) { mbar_wait_c(bars + B_FULL + c.s * 8, c.ph); release(c.s); c.next(); }
        mbar_wait_c(bars + B_FULL + c.s * 8, c.ph);
        const uint32_t zs = sb + c.s * ST_BYTES + ST_B + (tid & 127) * 16;
        uint4 zl, zh;
#pragma unroll
        for (int u = 0; u < 18; u++) {
          if (u == 0) wgmma_wait<1>();
          if (u == 9) {
            wgmma_wait<0>();
            release(prev);
            if (L == 0) signal(EV_PT);
            TRC(tr, w, tb + 14);
            SCLK(54);
          }
          if (!(u & 1)) { zl = lds128(zs + u * 2048); zh = lds128(zs + u * 2048 + 2048); }
          const uint4 z = (u & 1) ? make_uint4(zl.z, zh.z, zl.w, zh.w) : make_uint4(zl.x, zh.x, zl.y, zh.y);
          hA[u][0] = hmul2(z.x, pack2(fmaf(acc[8 * u], gk, gb0), fmaf(acc[8 * u + 1], gk, gb0)));
          hA[u][1] = hmul2(z.y, pack2(fmaf(acc[8 * u + 2], gk, gb1), fmaf(acc[8 * u + 3], gk, gb1)));
          hA[u][2] = hmul2(z.z, pack2(fmaf(acc[8 * u + 4], gk, gb0), fmaf(acc[8 * u + 5], gk, gb0)));
          hA[u][3] = hmul2(z.w, pack2(fmaf(acc[8 * u + 6], gk, gb1), fmaf(acc[8 * u + 7], gk, gb1)));
        }
        __syncwarp();
        release(c.s);
        c.next();
        if (w == 0) { mbar_wait_c(bars + B_FULL + c.s * 8, c.ph); release(c.s); c.next(); }
        TRC(tr, w, tb + 15);
      }
      {
        CLK_INIT;
        if (w == 1) bar_arrive(6, 256);
        uint4 v[4];
#pragma unroll
        for (int u = 0; u < 4; u++) v[u] = make_uint4(0u, 0u, 0u, 0u);
        uint32_t rl = sb + SM_STG + w * 8192 + q * 2048 + (lane >> 3) * 128 + (((lane & 7) ^ (lane >> 3)) << 4);
        uint8_t* rd = Q.out + (128 * rb + 32 * q + 2 * (lane >> 3) + w) * (DM * 2) + j * 128 + (lane & 7) * 16;
        asm volatile("" : "+r"(rl), "+l"(rd));
        auto send = [&](int u0, int u1) {
#pragma unroll
          for (int u = u0; u < u1; u++)
            asm volatile("red.relaxed.gpu.global.add.noftz.v4.bf16x2 [%0], {%1,%2,%3,%4};" ::"l"(rd + u * (8 * DM * 2)), "r"(v[u].x), "r"(v[u].y), "r"(v[u].z), "r"(v[u].w) : "memory");
        };
#pragma unroll 1
        for (int p = 0; p < 9; p++) {
          float acc[32];
          CLK(0);
          mbar_wait_c(bars + B_FULL + c.s * 8, c.ph);
          const uint32_t db = dlo(sb + c.s * ST_BYTES + ST_B, 0);
          CLK(1);
          bar_sync(6 + w, 256);
          CLK(2);
          wgmma_fence();
#pragma unroll
          for (int kk = 0; kk < 18; kk++) {
            wgmma_rs_n64(acc, hA[kk], dsc<1024, 1>(db, kk * 2048), kk != 0);
            if (kk == PPK && (w == 0 || p < 8)) bar_arrive(7 - w, 256);
          }
          wgmma_commit();
          CLK(3);
          if (p > 0) { send(NOW, 4); rd += p + j == 9 ? -1024 : 128; }
          CLK(5);
          wgmma_wait<0>();
          CLK(4);
          if (L == 0 || p < 5) release(c.s);
          c.next();
          TRC(tr && p == 8, w, tb + 16);
#pragma unroll
          for (int u = 0; u < 4; u++)
            stsm4(sb + SM_STG + (aoff ^ (u << 5)), pack2(acc[8 * u], acc[8 * u + 1]), pack2(acc[8 * u + 2], acc[8 * u + 3]), pack2(acc[8 * u + 4], acc[8 * u + 5]), pack2(acc[8 * u + 6], acc[8 * u + 7]));
          __syncwarp();
#pragma unroll
          for (int u = 0; u < 4; u++) v[u] = lds128(rl + u * 512 ^ (u & 1) << 6);
          send(0, NOW);
        }
        send(NOW, 4);
        TRC(tr, w, tb + 17);
        if (L == 0) signal(EV_PT);
        CLK_OUT;
        TRC(tr, w, tb + 18);
      }
    }
    if ((tid & 127) == 0) Q.flags[(rb * 2 + w) * 32 + FR_EP + j] = epoch + 1;
    if (tid == 0) Q.flags[FJ + j * 32 + FJ_EP + rb] = epoch + 1;
  }
}

typedef CUresult (*EncodeFn)(CUtensorMap*, CUtensorMapDataType, cuuint32_t, void*, const cuuint64_t*, const cuuint64_t*, const cuuint32_t*,
                             const cuuint32_t*, CUtensorMapInterleave, CUtensorMapSwizzle, CUtensorMapL2promotion, CUtensorMapFloatOOBfill);

static void make_map(EncodeFn fn, CUtensorMap* m, const void* ptr, int rank, uint64_t d0, uint64_t d1, uint64_t d2, uint64_t s1, uint64_t s2,
                     uint32_t b0, uint32_t b1, uint32_t b2, CUtensorMapSwizzle swz) {
  cuuint64_t dims[3] = {d0, d1, d2}, strides[2] = {s1, s2};
  cuuint32_t box[3] = {b0, b1, b2}, es[3] = {1, 1, 1};
  fn(m, CU_TENSOR_MAP_DATA_TYPE_BFLOAT16, rank, const_cast<void*>(ptr), dims, strides, box, es, CU_TENSOR_MAP_INTERLEAVE_NONE, swz,
     CU_TENSOR_MAP_L2_PROMOTION_L2_128B, CU_TENSOR_MAP_FLOAT_OOB_FILL_NONE);
}

}

extern "C" void kernel_launch(void* const* d_in, const int* in_sizes, int n_in, void* d_out, int out_size) {
  using namespace mk;
  (void)in_sizes; (void)n_in; (void)out_size;
  static EncodeFn fn = nullptr;
  static Scratch* sc = nullptr;
  if (!fn) {
    cudaDriverEntryPointQueryResult qr;
    cudaGetDriverEntryPoint("cuTensorMapEncodeTiled", (void**)&fn, cudaEnableDefault, &qr);
    cudaGetSymbolAddress((void**)&sc, g_scratch);
    cudaFuncSetAttribute(mega_kernel, cudaFuncAttributeMaxDynamicSharedMemorySize, SM_TOTAL);
  }
  Params p;
  Ptrs a;
  a.x = (const uint8_t*)d_in[0];
  a.wqkv = (const __nv_bfloat16*)d_in[1];
  a.wo = (const __nv_bfloat16*)d_in[2];
  a.w_in = (const __nv_bfloat16*)d_in[4];
  a.w_sp = (const __nv_bfloat16*)d_in[5];
  a.b_sp = (const __nv_bfloat16*)d_in[6];
  a.out = (uint8_t*)d_out;
  a.zero = 0;
  a.WQ = sc->WQ; a.flags = sc->flags; a.CSP = sc->CSP; a.XST = sc->XST; a.HALO = sc->HALO; a.ST1 = sc->ST1; a.ZST = sc->ZST; a.RT = sc->RT; a.Z = sc->Z; a.WO = sc->WO;
  make_map(fn, &p.wsp, a.w_sp, 3, 2048, 1024, 2, 8192, 4096, 64, 64, 2, CU_TENSOR_MAP_SWIZZLE_128B);
  for (int i = 0; i < 2; i++) {
    make_map(fn, &p.act[i], i ? a.out : a.x, 3, DM, 1024, 2, 2304, 1152, 64, 64, 1, CU_TENSOR_MAP_SWIZZLE_128B);
    make_map(fn, &p.row[i], i ? a.out : a.x, 3, 192, 6, 1024, 384, 2304, 192, 3, 8, CU_TENSOR_MAP_SWIZZLE_NONE);
    make_map(fn, &p.res[i], i ? a.out : a.x, 3, DM, 1024, 2, 2304, 1152, 72, 32, 2, CU_TENSOR_MAP_SWIZZLE_NONE);
  }
  for (int i = 0; i < 2; i++) make_map(fn, &p.winb[i], a.w_in + 32 * i, 3, 64, 576, 72 - i, 9216, 128, 64, 16, 3, CU_TENSOR_MAP_SWIZZLE_128B);
  make_map(fn, &p.wins, a.w_in, 3, 64, 576, 72, 9216, 128, 64, 48, 1, CU_TENSOR_MAP_SWIZZLE_128B);
  make_map(fn, &p.wout, d_in[7], 2, 576, 2304, 1, 1152, 0, 64, 144, 1, CU_TENSOR_MAP_SWIZZLE_128B);
  mega_kernel<<<NGRID, 384, SM_TOTAL, cudaStreamPerThread>>>(a, p);
}
```

```cpp
#include <cuda_runtime.h>
#include <cuda.h>
#include <cuda_bf16.h>
#include <stdint.h>

#define MK_TRACE 0
#define MK_DBG 0
#define P5TRACE 0

#define LAG1 0
#define C0S 32.f
#define OFM 0x10u
#define NC2 2
#define NC1 40
#define LD1 4
#define LD2 2
#define PDEL 8
#define SDEL 10
#define ZD1 8
#define ZD2 20
#define FD3 14
#define YPACE 2
#define SPL 3
#define XP0 10
#define APACE 7
#define AEP 2
#define PZI 4
#define RFI 3
#define KS 1
#define XK1 1
#define XK2 2
#define HO3 41
#define HO4 41
#define PPK 17
#define HOLD 2
#define HREL 0
#define XAL 0
#define VQ 0
#define NOW 2
#define WTI 12
#define EFM 0x23333022
#define EF(i) ((((EFM >> (4 * (i))) & 3) == 3) || (((EFM >> (4 * (i))) >> L) & 1))

namespace mk {

constexpr int SEQ = 2048, DM = 576, FH = 2304;
constexpr int NCTA = 128;
constexpr int NGRID = 132;
constexpr uint32_t ZB = 36864;
constexpr uint32_t WQ_SL = 72 * 3456;
constexpr uint32_t WO_SL = 72 * 1152;
constexpr float LN_EPS = 1e-5f;
constexpr float GA = 0.3292034911525734f, GB = 2.423681954311584f;

constexpr uint32_t ST_BYTES = 53248, ST_B = 16384, NST = 4;
constexpr uint32_t SM_STG = NST * ST_BYTES;
constexpr uint32_t SM_BAR = SM_STG + 2 * 9216, B_OFF = 896;
constexpr uint32_t SM_OFF = SM_BAR + B_OFF;
constexpr uint32_t SM_TOTAL = SM_BAR + 1024;
constexpr uint32_t SM_RT = SM_STG + 9216, SM_CV = SM_STG + 17408, SM_WT = SM_STG;
constexpr uint32_t SM_WOI = 44032, SM_CSQ = 49280, SM_XST = 50176;
enum { EV_PT = 0, EV_O = 1, EV_X1 = 2, EV_ZN = 3, EV_Z1 = 4, EV_XS = 5, EV_N = 6 };
constexpr uint32_t B_FULL = 0, B_FULLA = 32, B_RES = 96, B_WT = 112, B_GATE3 = 128, B_Z1 = 136, B_ZOK = 144, B_CV = 152, B_XRW = 168, B_F3 = 184, B_WF = 232, B_OF = 240,
                   B_RT = 320, B_AF3 = 352, B_RB = 544,
                   B_AD = 576, B_S5 = 608, B_AV = 616, B_CSQ = 760,
                   B_LAG = 768, B_X3 = 776, B_ZS = 784, B_EVT = 800,
                   B_IMG = 912, B_WOI = 920, B_E3 = 928, B_XD = 976,
                   B_EMPTY = 992;
constexpr uint32_t SM_B3 = 9 * 16384, SM_ZP3 = SM_STG + 8192;

enum { FR_X2 = 0, FR_O = 1, FR_XR = 5, FR_OL = 7, FR_PZ = 9, FR_EP = 16, FJ = 32 * 32, FJ_WQ = 0, FJ_WO = 1, FJ_ZN = 3, FJ_P4 = 5, FJ_EP = 16, F_N = FJ + 8 * 32 };

struct Scratch {
  alignas(1024) uint32_t flags[F_N];
  alignas(1024) float CSP[2 * NCTA * 216];
  alignas(1024) uint2 RT[SEQ];
  alignas(1024) uint4 XST[2 * SEQ];
  alignas(1024) uint4 ST1[SEQ * 4];
  alignas(1024) uint4 ZST[SEQ * 4];
  alignas(1024) uint4 HALO[32 * 8 * 6 * 32];
  alignas(1024) uint8_t WO[8 * WO_SL];
  alignas(1024) uint8_t WQ[8 * WQ_SL];
  alignas(1024) uint8_t Z[(XAL ? 512 : 576) * ZB];
};
__device__ Scratch g_scratch;

struct Ptrs {
  const __nv_bfloat16* wqkv;
  uint8_t* WQ;
  uint32_t* flags;
  float* CSP;
  const uint8_t* x;
  uint32_t zero;
  uint4 *XST, *HALO, *ST1, *ZST;
  uint2* RT;
  uint8_t *Z, *WO, *out;
  const __nv_bfloat16 *wo, *w_in, *w_sp, *b_sp;
};
struct Params {
  CUtensorMap wsp, winb[2], wins, wout;
  CUtensorMap act[2];
  CUtensorMap res[2];
};

__device__ __forceinline__ uint32_t smem_u32(const void* p) { return (uint32_t)__cvta_generic_to_shared(p); }
__device__ __forceinline__ void mbar_init(uint32_t bar, uint32_t cnt) { asm volatile("mbarrier.init.shared::cta.b64 [%0], %1;" ::"r"(bar), "r"(cnt)); }
__device__ __forceinline__ void mbar_arrive(uint32_t bar) { asm volatile("mbarrier.arrive.shared::cta.b64 _, [%0];" ::"r"(bar) : "memory"); }
__device__ __forceinline__ void mbar_wait(uint32_t bar, uint32_t parity) {
  asm volatile(
      "{\n.reg .pred p;\n.reg .u32 c;\nmov.u32 c, 0;\nLAB_WAIT:\n"
      "mbarrier.try_wait.parity.shared::cta.b64 p, [%0], %1;\n@p bra LAB_DONE;\n"
      "add.u32 c, c, 1;\nsetp.lt.u32 p, c, 0x100000;\n@p bra LAB_WAIT;\ntrap;\nLAB_DONE:\n}" ::"r"(bar), "r"(parity)
      : "memory");
}
__device__ __forceinline__ void mbar_wait_c(uint32_t bar, uint32_t parity) {
  asm volatile("{\n.reg .pred p;\nLAB_WAIT:\nmbarrier.try_wait.parity.shared::cta.b64 p, [%0], %1;\n@!p bra LAB_WAIT;\n}" ::"r"(bar), "r"(parity) : "memory");
}
__device__ __forceinline__ void flag_wait(const uint32_t* f, uint32_t target) {
  asm volatile(
      "{\n.reg .pred p;\n.reg .u32 c, v;\nmov.u32 c, 0;\nLAB_WAIT:\n"
      "ld.relaxed.gpu.global.u32 v, [%0];\nsub.u32 v, v, %1;\nsetp.ge.s32 p, v, 0;\n@p bra LAB_DONE;\n"
      "add.u32 c, c, 1;\nsetp.lt.u32 p, c, 0x400000;\n@p bra LAB_WAIT;\ntrap;\nLAB_DONE:\nfence.acquire.gpu;\n}" ::"l"(f), "r"(target)
      : "memory");
}
__device__ __forceinline__ void fence_gpu() { asm volatile("fence.acq_rel.gpu;" ::: "memory"); }
__device__ __forceinline__ void fence_async_g() { asm volatile("fence.proxy.async.global;" ::: "memory"); }
__device__ __forceinline__ void fence_async_s() { asm volatile("fence.proxy.async.shared::cta;" ::: "memory"); }
__device__ __forceinline__ uint32_t elect_one() {
  uint32_t p; asm volatile("{\n.reg .pred P;\nelect.sync _|P, 0xffffffff;\nselp.u32 %0, 1, 0, P;\n}" : "=r"(p)); return p;
}
__device__ __forceinline__ void expect_tx_p(uint32_t el, uint32_t bar, uint32_t bytes) {
  asm volatile("{\n.reg .pred P;\nsetp.ne.u32 P, %2, 0;\n@P mbarrier.arrive.expect_tx.shared::cta.b64 _, [%0], %1;\n}" ::"r"(bar), "r"(bytes), "r"(el) : "memory");
}
__device__ __forceinline__ void bulk_load_p(uint32_t el, uint32_t dst, const void* src, uint32_t bytes, uint32_t bar) {
  asm volatile("{\n.reg .pred P;\nsetp.ne.u32 P, %4, 0;\n@P cp.async.bulk.shared::cluster.global.mbarrier::complete_tx::bytes [%0], [%1], %2, [%3];\n}" ::"r"(dst), "l"(src), "r"(bytes), "r"(bar), "r"(el) : "memory");
}
__device__ __forceinline__ uint64_t policy_evict_first() { uint64_t p; asm("createpolicy.fractional.L2::evict_first.b64 %0, 1.0;" : "=l"(p)); return p; }
__device__ __forceinline__ void bulk_load_h(uint32_t el, uint32_t dst, const void* src, uint32_t bytes, uint32_t bar, bool ef, uint64_t pol) {
  if (ef) {
    asm volatile("{\n.reg .pred P;\nsetp.ne.u32 P, %4, 0;\n@P cp.async.bulk.shared::cluster.global.mbarrier::complete_tx::bytes.L2::cache_hint [%0], [%1], %2, [%3], %5;\n}" ::"r"(dst), "l"(src), "r"(bytes), "r"(bar), "r"(el), "l"(pol) : "memory");
  } else {
    asm volatile("{\n.reg .pred P;\nsetp.ne.u32 P, %4, 0;\n@P cp.async.bulk.shared::cluster.global.mbarrier::complete_tx::bytes [%0], [%1], %2, [%3];\n}" ::"r"(dst), "l"(src), "r"(bytes), "r"(bar), "r"(el) : "memory");
  }
}
__device__ __forceinline__ void bulk_mc_h(uint32_t el, uint32_t dst, const void* src, uint32_t bytes, uint32_t bar, bool ef, uint64_t pol) {
  if (ef) {
    asm volatile("{\n.reg .pred P;\nsetp.ne.u32 P, %4, 0;\n@P cp.async.bulk.shared::cluster.global.mbarrier::complete_tx::bytes.multicast::cluster.L2::cache_hint [%0], [%1], %2, [%3], %5, %6;\n}" ::"r"(dst), "l"(src), "r"(bytes), "r"(bar), "r"(el), "h"((uint16_t)3), "l"(pol) : "memory");
  } else {
    asm volatile("{\n.reg .pred P;\nsetp.ne.u32 P, %4, 0;\n@P cp.async.bulk.shared::cluster.global.mbarrier::complete_tx::bytes.multicast::cluster [%0], [%1], %2, [%3], %5;\n}" ::"r"(dst), "l"(src), "r"(bytes), "r"(bar), "r"(el), "h"((uint16_t)3) : "memory");
  }
}
__device__ __forceinline__ void tma3d_h(uint32_t el, uint32_t dst, const CUtensorMap* m, int c0, int c1, int c2, uint32_t bar, bool ef, uint64_t pol) {
  if (ef) {
    asm volatile("{\n.reg .pred P;\nsetp.ne.u32 P, %6, 0;\n@P cp.async.bulk.tensor.3d.shared::cluster.global.mbarrier::complete_tx::bytes.L2::cache_hint [%0], [%1, {%3, %4, %5}], [%2], %7;\n}" ::"r"(dst), "l"(m), "r"(bar), "r"(c0), "r"(c1), "r"(c2), "r"(el), "l"(pol) : "memory");
  } else {
    asm volatile("{\n.reg .pred P;\nsetp.ne.u32 P, %6, 0;\n@P cp.async.bulk.tensor.3d.shared::cluster.global.mbarrier::complete_tx::bytes [%0], [%1, {%3, %4, %5}], [%2];\n}" ::"r"(dst), "l"(m), "r"(bar), "r"(c0), "r"(c1), "r"(c2), "r"(el) : "memory");
  }
}
__device__ __forceinline__ void tma2d_mc_h(uint32_t el, uint32_t dst, const CUtensorMap* m, int c0, int c1, uint32_t bar, bool ef, uint64_t pol) {
  if (ef) {
    asm volatile("{\n.reg .pred P;\nsetp.ne.u32 P, %5, 0;\n@P cp.async.bulk.tensor.2d.shared::cluster.global.mbarrier::complete_tx::bytes.multicast::cluster.L2::cache_hint [%0], [%1, {%3, %4}], [%2], %6, %7;\n}" ::"r"(dst), "l"(m), "r"(bar), "r"(c0), "r"(c1), "r"(el), "h"((uint16_t)3), "l"(pol) : "memory");
  } else {
    asm volatile("{\n.reg .pred P;\nsetp.ne.u32 P, %5, 0;\n@P cp.async.bulk.tensor.2d.shared::cluster.global.mbarrier::complete_tx::bytes.multicast::cluster [%0], [%1, {%3, %4}], [%2], %6;\n}" ::"r"(dst), "l"(m), "r"(bar), "r"(c0), "r"(c1), "r"(el), "h"((uint16_t)3) : "memory");
  }
}
__device__ __forceinline__ void tma3d_mc_h(uint32_t el, uint32_t dst, const CUtensorMap* m, int c0, int c1, int c2, uint32_t bar, bool ef, uint64_t pol) {
  if (ef) {
    asm volatile("{\n.reg .pred P;\nsetp.ne.u32 P, %6, 0;\n@P cp.async.bulk.tensor.3d.shared::cluster.global.mbarrier::complete_tx::bytes.multicast::cluster.L2::cache_hint [%0], [%1, {%3, %4, %5}], [%2], %7, %8;\n}" ::"r"(dst), "l"(m), "r"(bar), "r"(c0), "r"(c1), "r"(c2), "r"(el), "h"((uint16_t)3), "l"(pol) : "memory");
  } else {
    asm volatile("{\n.reg .pred P;\nsetp.ne.u32 P, %6, 0;\n@P cp.async.bulk.tensor.3d.shared::cluster.global.mbarrier::complete_tx::bytes.multicast::cluster [%0], [%1, {%3, %4, %5}], [%2], %7;\n}" ::"r"(dst), "l"(m), "r"(bar), "r"(c0), "r"(c1), "r"(c2), "r"(el), "h"((uint16_t)3) : "memory");
  }
}
__device__ __forceinline__ void mbar_arrive_cluster(uint32_t addr) { asm volatile("mbarrier.arrive.shared::cluster.b64 _, [%0];" ::"r"(addr) : "memory"); }
__device__ __forceinline__ uint32_t mapa(uint32_t addr, uint32_t rank) { uint32_t r; asm("mapa.shared::cluster.u32 %0, %1, %2;" : "=r"(r) : "r"(addr), "r"(rank)); return r; }
__device__ __forceinline__ void bulk_store_p(uint32_t el, void* dst, uint32_t src, uint32_t bytes) {
  asm volatile("{\n.reg .pred P;\nsetp.ne.u32 P, %3, 0;\n@P cp.async.bulk.global.shared::cta.bulk_group [%0], [%1], %2;\n}" ::"l"(dst), "r"(src), "r"(bytes), "r"(el) : "memory");
}
__device__ __forceinline__ void flag_release_p(uint32_t el, uint32_t* f) {
  asm volatile("{\n.reg .pred P;\nsetp.ne.u32 P, %1, 0;\nfence.proxy.async;\n@P red.relaxed.gpu.global.add.u32 [%0], 1;\n}" ::"l"(f), "r"(el) : "memory");
}
__device__ __forceinline__ void flag_add_p(uint32_t el, uint32_t* f) {
  asm volatile("{\n.reg .pred P;\nsetp.ne.u32 P, %1, 0;\n@P red.relaxed.gpu.global.add.u32 [%0], 1;\n}" ::"l"(f), "r"(el) : "memory");
}
__device__ __forceinline__ void prefetch_l2(const void* src, uint32_t bytes) { asm volatile("cp.async.bulk.prefetch.L2.global [%0], %1;" ::"l"(src), "r"(bytes) : "memory"); }
__device__ __forceinline__ void prefetch_map(const CUtensorMap* m) { asm volatile("prefetch.tensormap [%0];" ::"l"(m) : "memory"); }
__device__ __forceinline__ void wgmma_fence() { asm volatile("wgmma.fence.sync.aligned;" ::: "memory"); }
__device__ __forceinline__ void wgmma_commit() { asm volatile("wgmma.commit_group.sync.aligned;" ::: "memory"); }
template <int N> __device__ __forceinline__ void wgmma_wait() { asm volatile("wgmma.wait_group.sync.aligned %0;" ::"n"(N) : "memory"); }
__device__ __forceinline__ uint32_t dlo(uint32_t addr, uint32_t lbo) { return ((addr & 0x3FFFF) >> 4) + ((lbo >> 4) << 16); }
template <uint32_t SBO, uint32_t SWZ> __device__ __forceinline__ uint64_t dsc(uint32_t lo, uint32_t off) {
  uint64_t d; asm("mov.b64 %0, {%1, %2};" : "=l"(d) : "r"(lo + (off >> 4)), "n"((SBO >> 4) | (SWZ << 30))); return d;
}
template <int R> __device__ __forceinline__ void reg_alloc() { asm volatile("setmaxnreg.inc.sync.aligned.u32 %0;" ::"n"(R)); }
template <int R> __device__ __forceinline__ void reg_dealloc() { asm volatile("setmaxnreg.dec.sync.aligned.u32 %0;" ::"n"(R)); }
__device__ __forceinline__ void bar_sync(int id, int n) { asm volatile("bar.sync %0, %1;" ::"r"(id), "r"(n) : "memory"); }
__device__ __forceinline__ void bar_arrive(int id, int n) { asm volatile("bar.arrive %0, %1;" ::"r"(id), "r"(n) : "memory"); }
__device__ __forceinline__ void ldsm4(uint32_t* r, uint32_t addr) {
  asm volatile("ldmatrix.sync.aligned.m8n8.x4.shared.b16 {%0,%1,%2,%3}, [%4];" : "=r"(r[0]), "=r"(r[1]), "=r"(r[2]), "=r"(r[3]) : "r"(addr) : "memory");
}
__device__ __forceinline__ uint32_t movm(uint32_t a) { uint32_t d; asm volatile("movmatrix.sync.aligned.m8n8.trans.b16 %0, %1;" : "=r"(d) : "r"(a)); return d; }
__device__ __forceinline__ void mma16(float* c, uint32_t a0, uint32_t a1, uint32_t a2, uint32_t a3, uint32_t b0, uint32_t b1) {
  asm volatile("mma.sync.aligned.m16n8k16.row.col.f32.bf16.bf16.f32 {%0,%1,%2,%3}, {%4,%5,%6,%7}, {%8,%9}, {%0,%1,%2,%3};"
               : "+f"(c[0]), "+f"(c[1]), "+f"(c[2]), "+f"(c[3]) : "r"(a0), "r"(a1), "r"(a2), "r"(a3), "r"(b0), "r"(b1));
}
__device__ __forceinline__ void mma8(float* c, uint32_t a0, uint32_t a1, uint32_t b0) {
  asm volatile("mma.sync.aligned.m16n8k8.row.col.f32.bf16.bf16.f32 {%0,%1,%2,%3}, {%4,%5}, {%6}, {%0,%1,%2,%3};"
               : "+f"(c[0]), "+f"(c[1]), "+f"(c[2]), "+f"(c[3]) : "r"(a0), "r"(a1), "r"(b0));
}
__device__ __forceinline__ uint32_t pack2(float lo, float hi) { uint32_t r; asm("cvt.rn.bf16x2.f32 %0, %1, %2;" : "=r"(r) : "f"(hi), "f"(lo)); return r; }
__device__ __forceinline__ float blo(uint32_t v) { return __uint_as_float(v << 16); }
__device__ __forceinline__ float bhi(uint32_t v) { return __uint_as_float(v & 0xffff0000u); }
__device__ __forceinline__ float tanh_fast(float x) { float y; asm("tanh.approx.f32 %0, %1;" : "=f"(y) : "f"(x)); return y; }
__device__ __forceinline__ float rcp_fast(float x) { float y; asm("rcp.approx.ftz.f32 %0, %1;" : "=f"(y) : "f"(x)); return y; }
__device__ __forceinline__ float rsq_fast(float x) { float y; asm("rsqrt.approx.ftz.f32 %0, %1;" : "=f"(y) : "f"(x)); return y; }
__device__ __forceinline__ float ex2(float x) { float y; asm("ex2.approx.ftz.f32 %0, %1;" : "=f"(y) : "f"(x)); return y; }
__device__ __forceinline__ float qsum(float v) { v += __shfl_xor_sync(~0u, v, 1); v += __shfl_xor_sync(~0u, v, 2); return v; }
__device__ __forceinline__ float qmax(float v) { v = fmaxf(v, __shfl_xor_sync(~0u, v, 1)); v = fmaxf(v, __shfl_xor_sync(~0u, v, 2)); return v; }
__device__ __forceinline__ void stg32(void* p, uint32_t v) { asm volatile("st.global.u32 [%0], %1;" ::"l"(p), "r"(v) : "memory"); }
__device__ __forceinline__ void stg128(void* p, uint32_t a, uint32_t b, uint32_t c, uint32_t d) { asm volatile("st.global.v4.u32 [%0], {%1,%2,%3,%4};" ::"l"(p), "r"(a), "r"(b), "r"(c), "r"(d) : "memory"); }
__device__ __forceinline__ uint32_t ldcg32(const void* p) { uint32_t v; asm volatile("ld.global.L1::no_allocate.u32 %0, [%1];" : "=r"(v) : "l"(p) : "memory"); return v; }
__device__ __forceinline__ void stg128_if(bool c, void* p, uint32_t a, uint32_t b, uint32_t cc, uint32_t d) {
  asm volatile("{\n.reg .pred P;\nsetp.ne.u32 P, %5, 0;\n@P st.global.v4.u32 [%0], {%1,%2,%3,%4};\n}" ::"l"(p), "r"(a), "r"(b), "r"(cc), "r"(d), "r"((uint32_t)c) : "memory");
}
__device__ __forceinline__ uint2 lds64(uint32_t a) { uint2 v; asm volatile("ld.shared.v2.u32 {%0,%1}, [%2];" : "=r"(v.x), "=r"(v.y) : "r"(a) : "memory"); return v; }
__device__ __forceinline__ uint32_t ldnc16(const void* p) { uint16_t v; asm volatile("ld.global.nc.u16 %0, [%1];" : "=h"(v) : "l"(p)); return v; }
__device__ __forceinline__ uint4 ldnc128(const void* p) { uint4 v; asm volatile("ld.global.nc.v4.u32 {%0,%1,%2,%3}, [%4];" : "=r"(v.x), "=r"(v.y), "=r"(v.z), "=r"(v.w) : "l"(p)); return v; }
__device__ __forceinline__ void cp_async16(uint32_t dst, const void* src) { asm volatile("cp.async.cg.shared.global [%0], [%1], 16;" ::"r"(dst), "l"(src) : "memory"); }
__device__ __forceinline__ uint32_t hsub2(uint32_t a, uint32_t b) { uint32_t d; asm("sub.rn.bf16x2 %0, %1, %2;" : "=r"(d) : "r"(a), "r"(b)); return d; }
__device__ __forceinline__ void stg32_if(bool c, void* p, uint32_t v) {
  asm volatile("{\n.reg .pred P;\nsetp.ne.u32 P, %2, 0;\n@P st.global.u32 [%0], %1;\n}" ::"l"(p), "r"(v), "r"((uint32_t)c) : "memory");
}
__device__ __forceinline__ float wsum(float v) { for (int o = 16; o; o >>= 1) v += __shfl_xor_sync(~0u, v, o); return v; }
__device__ __forceinline__ uint32_t hmul2(uint32_t a, uint32_t b) { uint32_t d; asm("mul.rn.bf16x2 %0, %1, %2;" : "=r"(d) : "r"(a), "r"(b)); return d; }
__device__ __forceinline__ void sts32(uint32_t a, uint32_t v) { asm volatile("st.shared.u32 [%0], %1;" ::"r"(a), "r"(v) : "memory"); }
__device__ __forceinline__ uint32_t lds32(uint32_t a) { uint32_t v; asm volatile("ld.shared.u32 %0, [%1];" : "=r"(v) : "r"(a) : "memory"); return v; }
__device__ __forceinline__ void sts128(uint32_t a, uint32_t x, uint32_t y, uint32_t z, uint32_t w) { asm volatile("st.shared.v4.u32 [%0], {%1,%2,%3,%4};" ::"r"(a), "r"(x), "r"(y), "r"(z), "r"(w) : "memory"); }
__device__ __forceinline__ uint4 lds128(uint32_t a) { uint4 v; asm volatile("ld.shared.v4.u32 {%0,%1,%2,%3}, [%4];" : "=r"(v.x), "=r"(v.y), "=r"(v.z), "=r"(v.w) : "r"(a) : "memory"); return v; }
__device__ __forceinline__ void ll_st64(uint2* p, uint32_t v, uint32_t tag) {
  asm volatile("{\n.reg .b64 r;\nmov.b64 r, {%1,%2};\nst.relaxed.gpu.global.b64 [%0], r;\n}" ::"l"(p), "r"(v), "r"(tag) : "memory");
}
__device__ __forceinline__ uint2 ll_ld64(const uint2* p) {
  uint2 v; asm volatile("{\n.reg .b64 r;\nld.relaxed.gpu.global.b64 r, [%2];\nmov.b64 {%0,%1}, r;\n}" : "=r"(v.x), "=r"(v.y) : "l"(p) : "memory"); return v;
}
__device__ __forceinline__ void ll_st128(uint4* p, float a, float b, uint32_t tag, float c = 0.f) {
  asm volatile("{\n.reg .b128 r;\n.reg .b64 lo, hi;\nmov.b64 lo, {%1,%2};\nmov.b64 hi, {%3,%4};\nmov.b128 r, {lo, hi};\nst.relaxed.gpu.global.b128 [%0], r;\n}" ::"l"(p), "r"(__float_as_uint(a)), "r"(__float_as_uint(b)), "r"(tag), "r"(__float_as_uint(c)) : "memory");
}
__device__ __forceinline__ uint4 ll_ld128g(const void* p) {
  uint4 v; asm volatile("{\n.reg .b128 r;\n.reg .b64 lo, hi;\nld.relaxed.gpu.b128 r, [%4];\nmov.b128 {lo, hi}, r;\nmov.b64 {%0,%1}, lo;\nmov.b64 {%2,%3}, hi;\n}" : "=r"(v.x), "=r"(v.y), "=r"(v.z), "=r"(v.w) : "l"(p) : "memory"); return v;
}
__device__ __forceinline__ uint4 ll_ld128(const uint4* p) {
  uint4 v; asm volatile("{\n.reg .b128 r;\n.reg .b64 lo, hi;\nld.relaxed.gpu.global.b128 r, [%4];\nmov.b128 {lo, hi}, r;\nmov.b64 {%0,%1}, lo;\nmov.b64 {%2,%3}, hi;\n}" : "=r"(v.x), "=r"(v.y), "=r"(v.z), "=r"(v.w) : "l"(p) : "memory"); return v;
}
__device__ __forceinline__ void publish_p(uint32_t el, uint32_t* f) {
  asm volatile("{\n.reg .pred P;\nsetp.ne.u32 P, %1, 0;\n@P cp.async.bulk.commit_group;\n@P cp.async.bulk.wait_group 0;\n@P red.release.gpu.global.add.u32 [%0], 1;\n}" ::"l"(f), "r"(el) : "memory");
}
__device__ __forceinline__ void stsm4(uint32_t addr, uint32_t a, uint32_t b, uint32_t c, uint32_t d) {
  asm volatile("stmatrix.sync.aligned.m8n8.x4.shared.b16 [%0], {%1,%2,%3,%4};" ::"r"(addr), "r"(a), "r"(b), "r"(c), "r"(d) : "memory");
}
__device__ __forceinline__ void sts64(uint32_t a, uint32_t x, uint32_t y) { asm volatile("st.shared.v2.u32 [%0], {%1,%2};" ::"r"(a), "r"(x), "r"(y) : "memory"); }
__device__ __forceinline__ void ll_st128_if(bool on, uint4* p, float a, float b, uint32_t tag) {
  asm volatile("{\n.reg .pred P;\n.reg .b128 r;\n.reg .b64 lo, hi;\nsetp.ne.u32 P, %4, 0;\nmov.b64 lo, {%1,%2};\nmov.b64 hi, {%3,%3};\nmov.b128 r, {lo, hi};\n@P st.relaxed.gpu.global.b128 [%0], r;\n}" ::"l"(p), "r"(__float_as_uint(a)), "r"(__float_as_uint(b)), "r"(tag), "r"((uint32_t)on) : "memory");
}
__device__ __forceinline__ uint4 ldnc128_if(bool c, const void* p) {
  uint4 v = make_uint4(0u, 0u, 0u, 0u);
  asm volatile("{\n.reg .pred P;\nsetp.ne.u32 P, %5, 0;\n@P ld.global.nc.v4.u32 {%0,%1,%2,%3}, [%4];\n}" : "+r"(v.x), "+r"(v.y), "+r"(v.z), "+r"(v.w) : "l"(p), "r"((uint32_t)c));
  return v;
}
__device__ __forceinline__ float2 lds64f(uint32_t a) { float2 v; asm volatile("ld.shared.v2.f32 {%0,%1}, [%2];" : "=f"(v.x), "=f"(v.y) : "r"(a) : "memory"); return v; }
#define TRC(cond, role, idx) do {} while (0)
#define TRV(role, idx, v) do {} while (0)
#define TRVI(c, role, idx, v) do {} while (0)

#define ACLK_INIT do {} while (0)
#define ACLK(i) do {} while (0)
#define ACLK_OUT do {} while (0)
#define RCLK(i) do {} while (0)
#define RCLK_INIT do {} while (0)
#define RCLK_OUT do {} while (0)
#define SCLK(i) do {} while (0)
#define SCLK2(i) do {} while (0)
#define SCLK3(i) do {} while (0)
#define PL 1
#define PCLK(i) do {} while (0)
#define PQ 1
#define CLK_INIT do {} while (0)
#define CLK(i) do {} while (0)
#define CLK_OUT do {} while (0)

__device__ __forceinline__ void wgmma_ss_n216(float* d, uint64_t da, uint64_t db, int scaleD) {
  asm volatile("{\n.reg .pred p;\nsetp.ne.b32 p, %110, 0;\nwgmma.mma_async.sync.aligned.m64n216k16.f32.bf16.bf16 "
    "{%0,%1,%2,%3,%4,%5,%6,%7,%8,%9,%10,%11,%12,%13,%14,%15,%16,%17,%18,%19,%20,%21,%22,%23,%24,%25,%26,%27,%28,%29,%30,%31,%32,%33,%34,%35,%36,%37,%38,%39,%40,%41,%42,%43,%44,%45,%46,%47,%48,%49,%50,%51,%52,%53,%54,%55,%56,%57,%58,%59,%60,%61,%62,%63,%64,%65,%66,%67,%68,%69,%70,%71,%72,%73,%74,%75,%76,%77,%78,%79,%80,%81,%82,%83,%84,%85,%86,%87,%88,%89,%90,%91,%92,%93,%94,%95,%96,%97,%98,%99,%100,%101,%102,%103,%104,%105,%106,%107}, "
    "%108, %109, p, 1, 1, 0, 1;\n}\n"
    : "+f"(d[0]), "+f"(d[1]), "+f"(d[2]), "+f"(d[3]), "+f"(d[4]), "+f"(d[5]), "+f"(d[6]), "+f"(d[7]), "+f"(d[8]), "+f"(d[9]), "+f"(d[10]), "+f"(d[11]), "+f"(d[12]), "+f"(d[13]), "+f"(d[14]), "+f"(d[15]), "+f"(d[16]), "+f"(d[17]), "+f"(d[18]), "+f"(d[19]), "+f"(d[20]), "+f"(d[21]), "+f"(d[22]), "+f"(d[23]), "+f"(d[24]), "+f"(d[25]), "+f"(d[26]), "+f"(d[27]), "+f"(d[28]), "+f"(d[29]), "+f"(d[30]), "+f"(d[31]), "+f"(d[32]), "+f"(d[33]), "+f"(d[34]), "+f"(d[35]), "+f"(d[36]), "+f"(d[37]), "+f"(d[38]), "+f"(d[39]), "+f"(d[40]), "+f"(d[41]), "+f"(d[42]), "+f"(d[43]), "+f"(d[44]), "+f"(d[45]), "+f"(d[46]), "+f"(d[47]), "+f"(d[48]), "+f"(d[49]), "+f"(d[50]), "+f"(d[51]), "+f"(d[52]), "+f"(d[53]), "+f"(d[54]), "+f"(d[55]), "+f"(d[56]), "+f"(d[57]), "+f"(d[58]), "+f"(d[59]), "+f"(d[60]), "+f"(d[61]), "+f"(d[62]), "+f"(d[63]), "+f"(d[64]), "+f"(d[65]), "+f"(d[66]), "+f"(d[67]), "+f"(d[68]), "+f"(d[69]), "+f"(d[70]), "+f"(d[71]), "+f"(d[72]), "+f"(d[73]), "+f"(d[74]), "+f"(d[75]), "+f"(d[76]), "+f"(d[77]), "+f"(d[78]), "+f"(d[79]), "+f"(d[80]), "+f"(d[81]), "+f"(d[82]), "+f"(d[83]), "+f"(d[84]), "+f"(d[85]), "+f"(d[86]), "+f"(d[87]), "+f"(d[88]), "+f"(d[89]), "+f"(d[90]), "+f"(d[91]), "+f"(d[92]), "+f"(d[93]), "+f"(d[94]), "+f"(d[95]), "+f"(d[96]), "+f"(d[97]), "+f"(d[98]), "+f"(d[99]), "+f"(d[100]), "+f"(d[101]), "+f"(d[102]), "+f"(d[103]), "+f"(d[104]), "+f"(d[105]), "+f"(d[106]), "+f"(d[107])
    : "l"(da), "l"(db), "r"(scaleD));
}
__device__ __forceinline__ void wgmma_ss_n72(float* d, uint64_t da, uint64_t db, int scaleD) {
  asm volatile("{\n.reg .pred p;\nsetp.ne.b32 p, %38, 0;\nwgmma.mma_async.sync.aligned.m64n72k16.f32.bf16.bf16 "
    "{%0,%1,%2,%3,%4,%5,%6,%7,%8,%9,%10,%11,%12,%13,%14,%15,%16,%17,%18,%19,%20,%21,%22,%23,%24,%25,%26,%27,%28,%29,%30,%31,%32,%33,%34,%35}, "
    "%36, %37, p, 1, 1, 0, 1;\n}\n"
    : "+f"(d[0]), "+f"(d[1]), "+f"(d[2]), "+f"(d[3]), "+f"(d[4]), "+f"(d[5]), "+f"(d[6]), "+f"(d[7]), "+f"(d[8]), "+f"(d[9]), "+f"(d[10]), "+f"(d[11]), "+f"(d[12]), "+f"(d[13]), "+f"(d[14]), "+f"(d[15]), "+f"(d[16]), "+f"(d[17]), "+f"(d[18]), "+f"(d[19]), "+f"(d[20]), "+f"(d[21]), "+f"(d[22]), "+f"(d[23]), "+f"(d[24]), "+f"(d[25]), "+f"(d[26]), "+f"(d[27]), "+f"(d[28]), "+f"(d[29]), "+f"(d[30]), "+f"(d[31]), "+f"(d[32]), "+f"(d[33]), "+f"(d[34]), "+f"(d[35])
    : "l"(da), "l"(db), "r"(scaleD));
}
__device__ __forceinline__ void wgmma_ss_n128(float* d, uint64_t da, uint64_t db, int scaleD) {
  asm volatile("{\n.reg .pred p;\nsetp.ne.b32 p, %66, 0;\nwgmma.mma_async.sync.aligned.m64n128k16.f32.bf16.bf16 "
    "{%0,%1,%2,%3,%4,%5,%6,%7,%8,%9,%10,%11,%12,%13,%14,%15,%16,%17,%18,%19,%20,%21,%22,%23,%24,%25,%26,%27,%28,%29,%30,%31,%32,%33,%34,%35,%36,%37,%38,%39,%40,%41,%42,%43,%44,%45,%46,%47,%48,%49,%50,%51,%52,%53,%54,%55,%56,%57,%58,%59,%60,%61,%62,%63}, "
    "%64, %65, p, 1, 1, 0, 1;\n}\n"
    : "+f"(d[0]), "+f"(d[1]), "+f"(d[2]), "+f"(d[3]), "+f"(d[4]), "+f"(d[5]), "+f"(d[6]), "+f"(d[7]), "+f"(d[8]), "+f"(d[9]), "+f"(d[10]), "+f"(d[11]), "+f"(d[12]), "+f"(d[13]), "+f"(d[14]), "+f"(d[15]), "+f"(d[16]), "+f"(d[17]), "+f"(d[18]), "+f"(d[19]), "+f"(d[20]), "+f"(d[21]), "+f"(d[22]), "+f"(d[23]), "+f"(d[24]), "+f"(d[25]), "+f"(d[26]), "+f"(d[27]), "+f"(d[28]), "+f"(d[29]), "+f"(d[30]), "+f"(d[31]), "+f"(d[32]), "+f"(d[33]), "+f"(d[34]), "+f"(d[35]), "+f"(d[36]), "+f"(d[37]), "+f"(d[38]), "+f"(d[39]), "+f"(d[40]), "+f"(d[41]), "+f"(d[42]), "+f"(d[43]), "+f"(d[44]), "+f"(d[45]), "+f"(d[46]), "+f"(d[47]), "+f"(d[48]), "+f"(d[49]), "+f"(d[50]), "+f"(d[51]), "+f"(d[52]), "+f"(d[53]), "+f"(d[54]), "+f"(d[55]), "+f"(d[56]), "+f"(d[57]), "+f"(d[58]), "+f"(d[59]), "+f"(d[60]), "+f"(d[61]), "+f"(d[62]), "+f"(d[63])
    : "l"(da), "l"(db), "r"(scaleD));
}
__device__ __forceinline__ void wgmma_ss_n160(float* d, uint64_t da, uint64_t db, int scaleD) {
  asm volatile("{\n.reg .pred p;\nsetp.ne.b32 p, %82, 0;\nwgmma.mma_async.sync.aligned.m64n160k16.f32.bf16.bf16 "
    "{%0,%1,%2,%3,%4,%5,%6,%7,%8,%9,%10,%11,%12,%13,%14,%15,%16,%17,%18,%19,%20,%21,%22,%23,%24,%25,%26,%27,%28,%29,%30,%31,%32,%33,%34,%35,%36,%37,%38,%39,%40,%41,%42,%43,%44,%45,%46,%47,%48,%49,%50,%51,%52,%53,%54,%55,%56,%57,%58,%59,%60,%61,%62,%63,%64,%65,%66,%67,%68,%69,%70,%71,%72,%73,%74,%75,%76,%77,%78,%79}, "
    "%80, %81, p, 1, 1, 0, 1;\n}\n"
    : "+f"(d[0]), "+f"(d[1]), "+f"(d[2]), "+f"(d[3]), "+f"(d[4]), "+f"(d[5]), "+f"(d[6]), "+f"(d[7]), "+f"(d[8]), "+f"(d[9]), "+f"(d[10]), "+f"(d[11]), "+f"(d[12]), "+f"(d[13]), "+f"(d[14]), "+f"(d[15]), "+f"(d[16]), "+f"(d[17]), "+f"(d[18]), "+f"(d[19]), "+f"(d[20]), "+f"(d[21]), "+f"(d[22]), "+f"(d[23]), "+f"(d[24]), "+f"(d[25]), "+f"(d[26]), "+f"(d[27]), "+f"(d[28]), "+f"(d[29]), "+f"(d[30]), "+f"(d[31]), "+f"(d[32]), "+f"(d[33]), "+f"(d[34]), "+f"(d[35]), "+f"(d[36]), "+f"(d[37]), "+f"(d[38]), "+f"(d[39]), "+f"(d[40]), "+f"(d[41]), "+f"(d[42]), "+f"(d[43]), "+f"(d[44]), "+f"(d[45]), "+f"(d[46]), "+f"(d[47]), "+f"(d[48]), "+f"(d[49]), "+f"(d[50]), "+f"(d[51]), "+f"(d[52]), "+f"(d[53]), "+f"(d[54]), "+f"(d[55]), "+f"(d[56]), "+f"(d[57]), "+f"(d[58]), "+f"(d[59]), "+f"(d[60]), "+f"(d[61]), "+f"(d[62]), "+f"(d[63]), "+f"(d[64]), "+f"(d[65]), "+f"(d[66]), "+f"(d[67]), "+f"(d[68]), "+f"(d[69]), "+f"(d[70]), "+f"(d[71]), "+f"(d[72]), "+f"(d[73]), "+f"(d[74]), "+f"(d[75]), "+f"(d[76]), "+f"(d[77]), "+f"(d[78]), "+f"(d[79])
    : "l"(da), "l"(db), "r"(scaleD));
}
__device__ __forceinline__ void wgmma_rs_n144(float* d, const uint32_t* a, uint64_t db, int scaleD) {
  asm volatile("{\n.reg .pred p;\nsetp.ne.b32 p, %77, 0;\nwgmma.mma_async.sync.aligned.m64n144k16.f32.bf16.bf16 "
    "{%0,%1,%2,%3,%4,%5,%6,%7,%8,%9,%10,%11,%12,%13,%14,%15,%16,%17,%18,%19,%20,%21,%22,%23,%24,%25,%26,%27,%28,%29,%30,%31,%32,%33,%34,%35,%36,%37,%38,%39,%40,%41,%42,%43,%44,%45,%46,%47,%48,%49,%50,%51,%52,%53,%54,%55,%56,%57,%58,%59,%60,%61,%62,%63,%64,%65,%66,%67,%68,%69,%70,%71}, "
    "{%72,%73,%74,%75}, %76, p, 1, 1, 1;\n}\n"
    : "+f"(d[0]), "+f"(d[1]), "+f"(d[2]), "+f"(d[3]), "+f"(d[4]), "+f"(d[5]), "+f"(d[6]), "+f"(d[7]), "+f"(d[8]), "+f"(d[9]), "+f"(d[10]), "+f"(d[11]), "+f"(d[12]), "+f"(d[13]), "+f"(d[14]), "+f"(d[15]), "+f"(d[16]), "+f"(d[17]), "+f"(d[18]), "+f"(d[19]), "+f"(d[20]), "+f"(d[21]), "+f"(d[22]), "+f"(d[23]), "+f"(d[24]), "+f"(d[25]), "+f"(d[26]), "+f"(d[27]), "+f"(d[28]), "+f"(d[29]), "+f"(d[30]), "+f"(d[31]), "+f"(d[32]), "+f"(d[33]), "+f"(d[34]), "+f"(d[35]), "+f"(d[36]), "+f"(d[37]), "+f"(d[38]), "+f"(d[39]), "+f"(d[40]), "+f"(d[41]), "+f"(d[42]), "+f"(d[43]), "+f"(d[44]), "+f"(d[45]), "+f"(d[46]), "+f"(d[47]), "+f"(d[48]), "+f"(d[49]), "+f"(d[50]), "+f"(d[51]), "+f"(d[52]), "+f"(d[53]), "+f"(d[54]), "+f"(d[55]), "+f"(d[56]), "+f"(d[57]), "+f"(d[58]), "+f"(d[59]), "+f"(d[60]), "+f"(d[61]), "+f"(d[62]), "+f"(d[63]), "+f"(d[64]), "+f"(d[65]), "+f"(d[66]), "+f"(d[67]), "+f"(d[68]), "+f"(d[69]), "+f"(d[70]), "+f"(d[71])
    : "r"(a[0]), "r"(a[1]), "r"(a[2]), "r"(a[3]), "l"(db), "r"(scaleD));
}
__device__ __forceinline__ void wgmma_rs_n64(float* d, const uint32_t* a, uint64_t db, int scaleD) {
  asm volatile("{\n.reg .pred p;\nsetp.ne.b32 p, %37, 0;\nwgmma.mma_async.sync.aligned.m64n64k16.f32.bf16.bf16 "
    "{%0,%1,%2,%3,%4,%5,%6,%7,%8,%9,%10,%11,%12,%13,%14,%15,%16,%17,%18,%19,%20,%21,%22,%23,%24,%25,%26,%27,%28,%29,%30,%31}, "
    "{%32,%33,%34,%35}, %36, p, 1, 1, 1;\n}\n"
    : "+f"(d[0]), "+f"(d[1]), "+f"(d[2]), "+f"(d[3]), "+f"(d[4]), "+f"(d[5]), "+f"(d[6]), "+f"(d[7]), "+f"(d[8]), "+f"(d[9]), "+f"(d[10]), "+f"(d[11]), "+f"(d[12]), "+f"(d[13]), "+f"(d[14]), "+f"(d[15]), "+f"(d[16]), "+f"(d[17]), "+f"(d[18]), "+f"(d[19]), "+f"(d[20]), "+f"(d[21]), "+f"(d[22]), "+f"(d[23]), "+f"(d[24]), "+f"(d[25]), "+f"(d[26]), "+f"(d[27]), "+f"(d[28]), "+f"(d[29]), "+f"(d[30]), "+f"(d[31])
    : "r"(a[0]), "r"(a[1]), "r"(a[2]), "r"(a[3]), "l"(db), "r"(scaleD));
}

template <int V> struct Int { static constexpr int value = V; };
struct Cur {
  uint32_t s, ph;
  __device__ __forceinline__ void next() { if (++s == NST) { s = 0; ph ^= 1; } }
};

__device__ __forceinline__ uint32_t o_place(uint32_t w, uint32_t e) { return (((w ? 0xd5310u : 0xa8d57u) >> (4 * e)) & 15) * 8192 + 90112; }
#define z1_block(rb, w, j) (Q.Z + ((rb) * 16 + (w) * 8 + (j)) * ZB)
#define xn_block(hw) (Q.Z + (XAL ? (hw) * 8 + 2 : 512 + (hw) * 2) * ZB)
#define z2_block(kb, j) (Q.Z + (256 + (kb) * 8 + (j)) * ZB)
template <int N> __device__ __forceinline__ void pause(uint32_t zero) {
  if (N <= 0) return;
  uint32_t z = clock() + threadIdx.x;
  do {
#pragma unroll (N > 8 ? 1 : 8)
    for (int i = 0; i < N; i++) asm volatile("shfl.sync.bfly.b32 %0, %0, 1, 0x1f, 0xffffffff;" : "+r"(z)::"memory");
  } while (__any_sync(~0u, z & zero));
}

__global__ void __cluster_dims__(2, 1, 1) __launch_bounds__(384, 1) mega_kernel(const Ptrs Q, const __grid_constant__ Params P) {
  extern __shared__ __align__(1024) uint8_t smem_raw[];
  const uint32_t sb = smem_u32(smem_raw);
  const uint32_t bars = sb + SM_BAR;
  const int tid = threadIdx.x;
  int lane = tid & 31;
  const int wid = __shfl_sync(~0u, tid >> 5, 0);
  const int cl = blockIdx.x >> 1;
  const int bid = (cl < 4 ? cl * 8 + 32 : cl - 4 + (max(cl - 29, 0) * 37 >> 8)) * 2 + (blockIdx.x & 1);
  const int rb = bid & 15, j = bid >> 4;
  uint4 wv[5];
  {
    const int n8 = min(tid >> 3, 26), part = n8 / 9;
    const uint8_t* src = (const uint8_t*)Q.wqkv + (8 * rb + (tid & 7)) * (3 * DM * 2) + (part * (DM - 72) + 72 * j + 8 * n8) * 2;
#pragma unroll
    for (int u = 0; u < 5; u++) wv[u] = ldnc128_if(tid < 216 && cl < 64 && (u < 4 || rb < 8), src + u * (128 * 3 * DM * 2));
  }
  if (cl >= 64) return;
  if (wid >= 7 && lane == 0) {
    if (wid < 10) {
#pragma unroll
      for (uint32_t b = 0; b < B_AD / 3; b += 8) mbar_init(bars + (wid - 7) * (B_AD / 3) + b, 1);
    } else if (wid == 10) {
#pragma unroll
      for (uint32_t b = B_AD; b < B_EVT; b += 8) mbar_init(bars + b, b < B_LAG ? 2 : 4);
    } else {
#pragma unroll
      for (uint32_t b = B_EVT; b < 1024; b += 8) if (b < B_OFF || b >= B_IMG) mbar_init(bars + b, b < B_IMG ? 4 : b < B_EMPTY ? 8 : 16);
    }
    asm volatile("fence.mbarrier_init.release.cluster;" ::: "memory");
  }
  __syncthreads();

  if (wid >= 8) {
    reg_dealloc<56>();
    const uint32_t el = elect_one();
    const uint64_t pol = policy_evict_first();
    uint32_t* const fj = Q.flags + FJ + j * 32;
    if (wid == 8) {
      if (el) { prefetch_map(&P.wsp); prefetch_map(&P.winb[j & 1]); prefetch_map(&P.wins); prefetch_map(&P.wout); prefetch_map(&P.act[1]); prefetch_map(&P.res[0]); prefetch_map(&P.res[1]); }
      const uint32_t epoch = ldcg32(fj + FJ_EP + rb);
      Cur c{0, 1};
      const uint32_t rk = bid & 1;
      uint32_t st, full;
      auto slot = [&](uint32_t bytes) {
        st = sb + c.s * ST_BYTES; full = bars + B_FULL + c.s * 8;
        mbar_wait(full, c.ph);
        expect_tx_p(el, full, bytes);
        mbar_wait(full - B_FULL + B_EMPTY, c.ph);
      };
#pragma unroll 1
      for (int L = 0; L < 2; L++) {
#pragma unroll 1
        for (int i = 0; i < 9; i++) {
          if (L == 0 && i == 0) {
            flag_wait(fj + FJ_WQ, (epoch + 1) * 16);
            fence_async_g();
            TRC(el, 2, 45);
          }
          slot(27648);
          bulk_mc_h(el, st + ST_B + rk * 13824, Q.WQ + j * WQ_SL + i * 27648 + rk * 13824, 13824, full, EF(0), pol);
          c.next();
        }
        if (L == 0) {
          flag_wait(fj + FJ_WO, (epoch + 1) * 16);
          fence_async_g();
          TRC(el, 2, 46);
        }
#pragma unroll 1
        while (c.s) {
          mbar_wait(bars + B_EMPTY + c.s * 8, c.ph);
          if (el) { mbar_arrive(bars + B_FULL + c.s * 8); asm volatile("mbarrier.arrive.shared::cta.b64 _, [%0], 16;" ::"r"(bars + B_EMPTY + c.s * 8) : "memory"); }
          c.next();
        }
        expect_tx_p(el, bars + B_WF, WO_SL);
        mbar_wait(bars + B_EMPTY, c.ph);
        mbar_wait(bars + B_EMPTY + 8, c.ph);
        bulk_mc_h(el, sb + rk * (WO_SL / 2), Q.WO + j * WO_SL + rk * (WO_SL / 2), WO_SL / 2, bars + B_WF, EF(1), pol);
#pragma unroll 1
        for (int r = 0; r < 10; r++) {
          const bool big = r >= 2 && r < 8;
          const int a0 = (r < 5 ? 36 : 0) + ((9 * j) >> 1) + (big ? 2 - 2 * (j & 1) : 3 * (j & 1) + rk), ks = big ? 32 : 48;
          int k = big ? (r < 5 ? r - 2 : r - 5) * 192 + rk * 16 : (r & 1) * 288;
          const CUtensorMap* m = big ? &P.winb[j & 1] : &P.wins;
          const uint32_t dst = sb + SM_B3 + rk * 6144;
#pragma unroll
          for (int p = 0; p < 6; p++, k += ks) {
            if (!(p & 3) && r == 0) mbar_wait(bars + B_XD + p * 2, L);
            if (p) mbar_wait_c(bars + B_E3 + p * 8, ~r & 1); else mbar_wait(bars + B_E3, ~r & 1);
            expect_tx_p(el, bars + B_F3 + p * 8, 12288);
            tma3d_mc_h(el, dst + p * 12288, m, 0, k, a0, bars + B_F3 + p * 8, EF(2), pol);
          }
        }
        TRC(el, 2, L * 16 + 6);
        mbar_wait(bars + B_ZOK, L);
        fence_async_g();
        TRC(el, 2, L * 16 + 7);
        const uint8_t* src = z2_block(0, j) + rk * 18432;
#pragma unroll 1
        for (int r = 0; r < 8; r++) {
          const int k = (r & 3) * 512 + ((r >> 2) ^ 1) * 64;
#pragma unroll
          for (int p = 0; p < 4; p++, src += 8 * ZB) {
            if ((p == 1 || p == 2) && r == 0) mbar_wait(bars + B_E3 - 8 + p * 24, 1);
            mbar_wait_c(bars + B_AD + p * 8, ~r & 1);
            if (p) mbar_wait_c(bars + B_EMPTY + p * 8, c.ph); else mbar_wait(bars + B_EMPTY, c.ph);
            expect_tx_p(el, bars + B_FULL + p * 8, ST_BYTES);
            bulk_mc_h(el, sb + p * ST_BYTES + ST_B + rk * 18432, src, 18432, bars + B_FULL + p * 8, EF(4), pol);
            tma3d_h(el, sb + p * ST_BYTES, &P.wsp, k + p * 128, rb * 64, 0, bars + B_FULL + p * 8, EF(3), pol);
          }
          c.ph ^= 1;
        }
        mbar_wait(bars + B_Z1, L);
        fence_async_g();
#pragma unroll 1
        for (int i = 0; i < 11; i++) {
          const int cb = i - 2 + j;
          if (i < 4) mbar_wait(bars + B_AD + c.s * 8, 1);
          slot(ZB);
          if (i < 2) bulk_load_h(el, st + ST_B, z1_block(rb, i, j), ZB, full, true, pol);
          else tma2d_mc_h(el, st + ST_B + rk * 18432, &P.wout, (cb >= 9 ? cb - 9 : cb) * 64, 288 * j + rk * 144, full, EF(5), pol);
          c.next();
        }
      }
    } else if (wid < 11) {
      uint32_t id = bid * 2 + wid - 9;
#define AGENT_IDS asm volatile("" : "+r"(lane), "+r"(id)); const uint32_t w = id & 1, hw = id & 31, rb = hw >> 1, j = id >> 5, ev = bars + B_EVT + w * EV_N * 8; \
      uint32_t* const fr = Q.flags + hw * 32; uint32_t* const fj = Q.flags + FJ + j * 32; (void)fr; (void)fj; (void)ev; (void)rb
      uint32_t t8 = 0;
      Cur c{0, 1};
#pragma unroll 1
      for (int L = 0; L < 2; L++) {
        if (L) {
          AGENT_IDS;
          const uint32_t full = bars + B_FULLA + w * 32 + c.s * 8, dst = sb + c.s * ST_BYTES + w * 8192;
          expect_tx_p(el, full, 8192);
          mbar_wait_c(ev + EV_PT * 8, 1);
          TRC(el, 3, w * 32 + 16);
          flag_release_p(el, fr + FR_X2);
          TRC(el, 3, w * 32 + 17);
          mbar_wait_c(bars + B_EMPTY + c.s * 8, c.ph);
          flag_wait(fr + FR_X2, t8);
          fence_async_g();
          tma3d_h(el, dst, &P.act[1], 0, (hw ^ 1) * 32, 0, full, false, pol);
          c.next();
          TRC(el, 3, w * 32 + 18);
        }
#pragma unroll 1
        for (int i = L; i < 9; i++) {
          AGENT_IDS;
          const uint32_t full = bars + B_FULLA + w * 32 + c.s * 8, dst = sb + c.s * ST_BYTES + w * 8192;
          if (L == 0 && i == AEP) t8 = (ldcg32(fr + FR_EP + j) + 1) * 8;
          mbar_wait_c(bars + B_EMPTY + c.s * 8, c.ph);
          expect_tx_p(el, full, 8192);
          tma3d_h(el, dst, &P.act[L], i * 64, (hw ^ 1) * 32, 0, full, false, pol);
          c.next();
          if (i == PZI || i == PZI + 1) {
            uint8_t* d = (i == PZI ? xn_block(hw) : z1_block(rb, 0, 0) + w * 4608) + j * 9216 + lane * 16;
#pragma unroll 1
            for (int u = i == PZI ? 0 : 3; u < 6; u++, d += 1536) { stg128(d, ~0u, ~0u, ~0u, ~0u); stg128(d + 512, ~0u, ~0u, ~0u, ~0u); stg128(d + 1024, ~0u, ~0u, ~0u, ~0u); }
          }
          if (i == PZI) { stg128(Q.ST1 + (hw * 8 + j) * 32 + lane, ~0u, ~0u, ~0u, ~0u); stg128(Q.ZST + (hw * 8 + j) * 32 + lane, ~0u, ~0u, ~0u, ~0u); }
          if (i == RFI) {
            if (L) mbar_wait_c(bars + B_EVT + (EV_N * (1 - w) + EV_PT) * 8, 1);
            expect_tx_p(el, bars + B_WT + w * 8, 9216);
            bulk_load_p(el, sb + SM_STG + w * 9216, (L ? Q.out : Q.x) + ((hw ^ 1) * 64 + 8 * j) * (DM * 2), 9216, bars + B_WT + w * 8);
          }
          if (i == 4 && L > w) {
            expect_tx_p(el, bars + B_XRW + 8, 864);
            bulk_load_p(el, sb + 3 * ST_BYTES + SM_CSQ, Q.CSP + (NCTA + (id >> 1)) * 216, 864, bars + B_XRW + 8);
          }
        }
        if (c.s) { c.s = 0; c.ph ^= 1; }
        {
          AGENT_IDS;
          const uint32_t tag = (t8 >> 2) - 1 + L;
          uint4* const xs = Q.XST + hw * 128;
          const uint32_t tab = sb + L * (3 * ST_BYTES) + SM_XST + w * 768 + lane * 8;
          TRC(el, 3, w * 32 + L * 16 + 13);
#pragma unroll 1
          for (int it = 0; it < (1 << 22); it++) {
            const uint4 a = ll_ld128(xs + 2 * lane), b = ll_ld128(xs + 64 + 2 * lane), h = ll_ld128(xs - (rb ? 192 : 0) + 2 * (lane | 24));
            if (__all_sync(~0u, a.z == tag && b.z == tag && h.z == tag)) { sts64(tab, h.x, h.y); sts64(tab + 256, a.x, a.y); sts64(tab + 512, b.x, b.y); break; }
          }
          __syncwarp();
          if (el) mbar_arrive(bars + B_CSQ);
          TRC(el, 3, w * 32 + L * 16 + 14);
          uint32_t* f = Q.flags + rb * 64 + FR_PZ + L;
          flag_release_p(el, f);
          expect_tx_p(el, bars + B_RES + w * 8, 9216);
          tma3d_h(el, sb + SM_STG + w * 9216, &P.res[L], j * 72, (hw ^ 1) * 32, 0, bars + B_RES + w * 8, !L, pol);
          pause<FD3>(Q.zero);
          flag_wait(f, t8 * 2);
          fence_async_g();
          TRC(el, 3, w * 32 + L * 16 + 15);
        }
        {
          AGENT_IDS;
          uint32_t* f = Q.flags + rb * 64 + FR_O + L;
#pragma unroll 1
          for (int e = 0; e < 5; e++) {
            const uint32_t nb = e ? 16384 : 8192, full = bars + B_OF + w * 40 + e * 8, dst = sb + o_place(w, e);
            const uint8_t* src = z1_block(rb, w, 0) + (e ? e * 16384 - 8192 : 0);
            expect_tx_p(el, full, nb);
            if (e == 0) {
              mbar_wait_c(ev + EV_O * 8, L);
              TRC(el, 3, w * 32 + L * 16 + 3);
              if (!w) flag_add_p(el, f);
              flag_wait(f + w * (FR_OL - FR_O), t8);
              if (w) fence_async_g();
            }
            if (w && (e == 0 || e == 3)) mbar_wait_c(bars + (e ? B_X3 : B_OF + YPACE * 8), L);
            bulk_load_h(el, dst, src, nb, full, EF(6), pol);
            TRC(el && e == 0, 3, w * 32 + L * 16 + 5);
          }
        }
        {
          AGENT_IDS;
          const uint8_t* src = xn_block(hw);
          uint32_t full = bars + B_AF3 + w * 96, dst = sb + w * 6144;
          if (L) flag_wait(fj + FJ_P4, t8 * 4);
          mbar_wait_c(bars + B_XD + 8, L);
          mbar_wait_c(ev + EV_X1 * 8, L);
          TRC(el, 3, w * 32 + L * 16 + 6);
          pause<SDEL>(Q.zero);
#pragma unroll 1
          for (int k = 0; k < 12; k++, src += 6144, dst += 12288, full += 8) {
            expect_tx_p(el, full, 6144);
            if (k >= APACE) mbar_wait_c(full - APACE * 8, L);
            bulk_load_h(el, dst, src, 6144, full, EF(7), pol);
            TRC(el && k == 0, 3, w * 32 + L * 16 + 8);
          }
        }
        if (wid == 10) {
          AGENT_IDS;
          mbar_wait_c(ev - (EV_N - EV_ZN) * 8, L);
          mbar_wait_c(ev + EV_ZN * 8, L);
          asm volatile("fence.release.gpu;" ::: "memory");
          flag_add_p(el, fj + FJ_ZN + L);
          flag_add_p(el, fr - 32 + FR_XR + L);
          flag_wait(fj + FJ_ZN + L, t8 * 2);
          flag_wait(fr - 32 + FR_XR + L, t8);
          if (el) mbar_arrive(bars + B_ZOK);
        } else {
          AGENT_IDS;
          mbar_wait_c(ev + EV_ZN * 8, L);
          if (el) asm volatile("cp.async.bulk.prefetch.tensor.3d.L2.global [%0, {%1, %2, %3}];" ::"l"(&P.wsp), "r"(j * 128 + 64), "r"(rb * 64), "r"(0) : "memory");

        }
        float cv;
        {
        AGENT_IDS;
        cv = (lane & 3) ? 0.f : -blo(ldnc16(Q.b_sp + 128 * rb + 16 * j + 2 * (lane >> 2) + w));
        const uint32_t ro = (w * 64 + 8 * j + (lane >> 2)) * 128, x0 = ((lane & 3) * 2) ^ (lane >> 2);
#pragma unroll 1
        for (int i = 0; i < 32; i++) {
          const bool tail = (i >> 1) == 12;
          const int kb = tail ? i + 6 : i < 24 ? i : i - 2;
          if (!(i & 7)) mbar_wait_c(bars + B_RT + i, L);
          if (i == 24) mbar_wait_c(bars + B_WT + w * 8, 1);
          if (!tail) mbar_wait(bars + B_FULL + c.s * 8, c.ph ^ 1);
          uint4 x[2];
#pragma unroll
          for (int e = 0; e < 2; e++) x[e] = lds128(!tail ? sb + c.s * ST_BYTES + ro + ((x0 ^ e) << 4) : sb + SM_WT + w * 3200 + (lane >> 2) * 400 + (i - 24) * 256 + (lane & 3) * 32 + e * 16);
          if (!tail) {
            __syncwarp();
            if (el) mbar_arrive(bars + B_AD + c.s * 8);
            c.next();
          }
#pragma unroll
          for (int e = 0; e < 2; e++) {
            const uint4 a = x[e], m = lds128(sb + SM_RT + 4096 + kb * 128 + (lane & 3) * 32 + e * 16);
            cv = fmaf(blo(a.x), blo(m.x), fmaf(bhi(a.x), bhi(m.x), fmaf(blo(a.y), blo(m.y), fmaf(bhi(a.y), bhi(m.y), cv))));
            cv = fmaf(blo(a.z), blo(m.z), fmaf(bhi(a.z), bhi(m.z), fmaf(blo(a.w), blo(m.w), fmaf(bhi(a.w), bhi(m.w), cv))));
          }
          if (i == WTI) {
            uint32_t id2 = id;
            asm volatile("" : "+r"(id2));
            expect_tx_p(el, bars + B_WT + w * 8, 3072);
#pragma unroll 1
            for (int r = 0; r < 8; r++)
              bulk_load_p(el, sb + SM_WT + w * 3200 + r * 400, (const uint8_t*)Q.w_sp + (64 * (id2 & 30) + 16 * (id2 >> 5) + 2 * r + w) * (SEQ * 2) + 28 * 128, 384, bars + B_WT + w * 8);
          }
        }
        }
        AGENT_IDS;
        TRC(el, 3, w * 32 + L * 16 + 11);
        asm volatile("" : "+r"(t8));
        const uint32_t tag = (t8 >> 2) - 1 + L;
        cv = qsum(cv);
        uint2* const cs = (uint2*)(Q.XST + hw * 128 + 1);
        if ((lane & 3) == 0) ll_st64(cs + 32 * j + (lane >> 2) * 4, __float_as_uint(cv), tag);
#pragma unroll 1
        for (int it = 0; it < (1 << 22); it++) {
          const uint2 a = ll_ld64(cs + 4 * lane), b = ll_ld64(cs + 128 + 4 * lane);
          if (__all_sync(~0u, a.y == tag && b.y == tag)) { sts32(sb + SM_CV + w * 256 + lane * 4, a.x); sts32(sb + SM_CV + w * 256 + 128 + lane * 4, b.x); break; }
        }
        __syncwarp();
        if (el) mbar_arrive(bars + B_CV + w * 8);
        TRC(el, 3, w * 32 + L * 16 + 12);
#pragma unroll 1
        for (int kb = 30; kb < 32; kb++) {
          mbar_wait_c(bars + B_FULL + c.s * 8, c.ph ^ 1);
          if (el) mbar_arrive(bars + B_AD + c.s * 8);
          c.next();
        }
        c.ph ^= ((c.s + 11) >> 2) & 1; c.s = (c.s + 11) & 3;
        if (L == 0) {
          mbar_wait_c(ev + EV_PT * 8, 0);
          flag_add_p(el, fj + FJ_P4);
        }
      }
    } else {
      const uint32_t epoch = ldcg32(fj + FJ_EP + rb);
      mbar_wait(bars + B_IMG, 0);
      TRC(el, 2, 41);
      flag_release_p(el, fj + FJ_WQ);
      TRC(el, 2, 42);
#pragma unroll 1
      for (int L = 0; L < 2; L++) {
        float* const csf = Q.CSP + (NCTA + bid) * 216;
        if (L == 0) {
          flag_wait(fj + FJ_WQ, (epoch + 1) * 16);
          fence_async_g();
          expect_tx_p(el, bars + B_XRW, 13824);
          bulk_load_p(el, sb + ST_BYTES + SM_WOI, Q.CSP + j * 16 * 216, 6912, bars + B_XRW);
          bulk_load_p(el, sb + 2 * ST_BYTES + SM_WOI, Q.CSP + (j * 16 + 8) * 216, 6912, bars + B_XRW);
          mbar_wait(bars + B_XRW, 0);
#pragma unroll 1
          for (int f = lane; f < 54; f += 32) {
            float s[4] = {0.f, 0.f, 0.f, 0.f};
#pragma unroll 2
            for (int r = 0; r < 16; r++) {
              const uint4 v = lds128(sb + ST_BYTES + SM_WOI + (r >> 3) * ST_BYTES + (r & 7) * 864 + f * 16);
              s[0] += __uint_as_float(v.x); s[1] += __uint_as_float(v.y); s[2] += __uint_as_float(v.z); s[3] += __uint_as_float(v.w);
            }
            sts128(sb + SM_CSQ + f * 16, __float_as_uint(s[0]), __float_as_uint(s[1]), __float_as_uint(s[2]), __float_as_uint(s[3]));
            stg128(csf + f * 4, __float_as_uint(s[0]), __float_as_uint(s[1]), __float_as_uint(s[2]), __float_as_uint(s[3]));
          }
          __syncwarp();
          if (el) mbar_arrive(bars + B_XRW + 8);
          TRC(el, 2, 43);
          mbar_wait(bars + B_WOI, 0);
          bulk_store_p(el, Q.WO + j * WO_SL + rb * (41 * 128), sb + SM_WOI, (rb < 15 ? 41 : 33) * 128);
          publish_p(el, fj + FJ_WO);
          TRC(el, 2, 44);
          if (el) prefetch_l2((const uint8_t*)Q.w_in + bid * 41472, 41472);
          float o0 = 0.f, o1 = 0.f;
#pragma unroll 1
          for (int u = 0; u < 2; u++) {
            const uint8_t* src = (u ? (const uint8_t*)Q.w_sp + 500 * (SEQ * 2) + 2048 : (const uint8_t*)Q.w_in + 100 * (2 * FH * 2) + FH * 2) + lane * 16;
            const uint4 a = ldnc128(src), b = ldnc128(src + 300 * (2 * FH * 2) + 2048);
            const uint32_t x[8] = {a.x, a.y, a.z, a.w, b.x, b.y, b.z, b.w};
            float sq = 0.f;
#pragma unroll
            for (int e = 0; e < 8; e++) sq = fmaf(blo(x[e]), blo(x[e]), fmaf(bhi(x[e]), bhi(x[e]), sq));
            o0 = o1;
            asm("sqrt.approx.f32 %0, %1;" : "=f"(o1) : "f"(wsum(sq) * (u ? C0S * C0S * SEQ / 512.f : 2.f * GA * GA * DM / 512.f)));
          }
          const uint32_t off = (__float_as_uint(o0) & 0x7f800000u) >> 16 | 0x8000u | OFM;
          const uint32_t c0 = min(max(__float_as_uint(o1) & 0x7f800000u, 0x04000000u), 0x7e000000u) | 0x00400000u;
          if (el) sts128(sb + SM_OFF, off * 0x10001u, c0, __float_as_uint(GB), ((c0 >> 16) - 0x200u) * 0x10001u);
        }
        mbar_wait(bars + B_EVT + EV_O * 8, L);
        mbar_wait(bars + B_EVT + (EV_N + EV_O) * 8, L);
        flag_release_p(el, Q.flags + rb * 64 + FR_OL + L);
#pragma unroll 1
        for (int w = 0; w < 2; w++) {
          mbar_wait(bars + B_EVT + (w * EV_N + EV_XS) * 8, L);
          if (!w) mbar_wait(bars + B_AF3 + 96 + XP0 * 8, L);
          if (el) asm volatile("cp.async.bulk.tensor.3d.global.shared::cta.tile.bulk_group [%0, {%2, %3, %4}], [%1];\ncp.async.bulk.commit_group;\ncp.async.bulk.wait_group.read 0;" ::"l"(&P.res[1]), "r"(sb + SM_STG + 9216), "r"(j * 72), "r"(rb * 64 + (w ^ 1) * 32), "r"(0) : "memory");
          __syncwarp();
          if (lane < 2 && !w) mbar_arrive(bars + B_S5);
        }
        sts64(sb + SM_CV + 512 + lane * 8, 0x3f803f80u, 0x3f803f80u);
        fence_async_s();
        __syncwarp();
        if (el) { asm volatile("cp.async.bulk.wait_group 0;" ::: "memory"); mbar_arrive(bars + B_GATE3); }
        const uint32_t tag = epoch * 2 + L + 1;
        asm volatile("" : "+r"(lane));
#pragma unroll 1
        for (int b = 0; b < 8; b++) {
          if (!(b & 3)) {
            const int mb = b >> 2;
            mbar_wait(bars + B_ZS + mb * 8, L);
            pause<ZD1>(Q.zero);
            TRC(el && !mb, 2, L * 16 + 8);
            uint4 v;
#pragma unroll 1
            for (int it = 0; it < (1 << 22); it++) {
              v = ll_ld128(Q.ZST + ((rb * 2 + mb) * 8 + (lane >> 2)) * 32 + 4 * j + (lane & 3));
              if (__all_sync(~0u, max(max(v.x, v.y), max(v.z, v.w)) != ~0u)) break;
            }
            if (XAL && lane < 2 && !mb) mbar_arrive(bars + B_S5);
            const bool o = lane & 16;
            float ss = __uint_as_float(o ? v.y : v.x) + __shfl_xor_sync(~0u, __uint_as_float(o ? v.x : v.y), 16), sq = __uint_as_float(o ? v.w : v.z) + __shfl_xor_sync(~0u, __uint_as_float(o ? v.z : v.w), 16);
            ss += __shfl_xor_sync(~0u, ss, 4); sq += __shfl_xor_sync(~0u, sq, 4); ss += __shfl_xor_sync(~0u, ss, 8); sq += __shfl_xor_sync(~0u, sq, 8);
            const float mean = ss * (1.f / FH), rs = blo(pack2(rsq_fast(fmaxf(fmaf(sq, 1.f / FH, -mean * mean), 0.f) + 4.f * GA * GA * LN_EPS), 0.f));
            if (!(lane & 12)) ll_st64(Q.RT + (mb * 16 + rb) * 64 + 8 * j + 2 * (lane & 3) + (lane >> 4), pack2(rs, rs * (mean - blo(lds32(sb + SM_OFF)))), tag);
            TRC(el && !mb, 2, L * 16 + 10);
            pause<ZD2>(Q.zero);
          }
          uint4 v[4];
#pragma unroll 1
          for (int it = 0; it < (1 << 22); it++) {
            bool ok = true;
#pragma unroll
            for (int u = 0; u < 4; u++) { v[u] = ll_ld128((const uint4*)Q.RT + b * 128 + u * 32 + lane); ok = ok && v[u].y == tag && v[u].w == tag; }
            if (__all_sync(~0u, ok)) break;
          }
#pragma unroll
          for (int u = 0; u < 4; u++) {
            const uint32_t rt = sb + SM_RT + b * 512 + u * 128, ro = (lane >> 3) * 32 + (lane & 3) * 8 + ((lane >> 2) & 1) * 2;
            sts32(rt + 4096 + lane * 4, __byte_perm(v[u].x, v[u].z, 0x7632));
            asm volatile("st.shared.u16 [%0], %1;\nst.shared.u16 [%0 + 4], %2;" ::"r"(rt + ro), "h"((uint16_t)v[u].x), "h"((uint16_t)v[u].z) : "memory");
          }
          __syncwarp();
          if (el && (b & 1)) mbar_arrive(bars + B_RT + (b - 1) * 4);
          TRC(el && b < 2, 2, L * 16 + 11 + b);
        }
        TRC(el, 2, L * 16 + 9);
        mbar_wait(bars + B_EVT + EV_Z1 * 8, L);
        mbar_wait(bars + B_EVT + (EV_N + EV_Z1) * 8, L);
        fence_gpu();
        if (el) mbar_arrive(bars + B_Z1);
      }
    }
  } else {
    int w = wid >> 2, q = wid & 3, rb = bid & 15, j = bid >> 4;
    int g = lane >> 2, t = lane & 3;
#define PHASE asm volatile("" : "+r"(w), "+r"(q), "+r"(rb), "+r"(j))
#define stg (sb + SM_STG + w * 9216)
#define pw (q >> 1)
#define pq (2 - 2 * w + (q & 1))
    const bool tr = (tid & 127) == 0;
    (void)tr;
    Cur c{0, 0};
    const uint32_t ebar = mapa(bars + B_EMPTY, (bid & 1) ^ (lane & 1));
    auto release = [&](uint32_t s) { if (lane < 2) mbar_arrive_cluster(ebar + s * 8); };
    uint32_t ia = 0;
    auto wait_ab = [&]() { mbar_wait_c(bars + B_FULL + c.s * 8, c.ph); mbar_wait_c(bars + B_FULLA + w * 32 + c.s * 8, (ia >> c.s) & 1); ia ^= 1u << c.s; };
    uint32_t lagph = 0;
    auto yield = [&](int left, int lag) { if (w == 1 && left == lag) mbar_wait_c(bars + B_LAG, lagph); };
    auto yield_done = [&]() { if (w == 0 && lane == 0) mbar_arrive(bars + B_LAG); };
    uint32_t rp = 0;
    auto check = [&](auto n, uint32_t dst, const uint8_t* src) {
      const uint32_t a = dst + lane * 32 + (lane >> 2) * 4;
#pragma unroll 1
      for (int it = 0; it < (1 << 16); it++) {
        uint32_t x = lds32(a);
#pragma unroll
        for (int e = 1; e < n.value; e++) x = max(x, lds32(a + e * 1024));
        if (!__any_sync(~0u, x == ~0u)) break;
        fence_async_s();
        __syncwarp();
        const uint32_t el = elect_one();
        expect_tx_p(el, bars + B_RB + q * 8, n.value * 1024);
        bulk_load_p(el, dst, src, n.value * 1024, bars + B_RB + q * 8);
        mbar_wait_c(bars + B_RB + q * 8, rp & 1);
        rp++;
      }
    };
    auto signal = [&](int e) { __syncwarp(); if (lane == 0) mbar_arrive(bars + B_EVT + w * EV_N * 8 + e * 8); };
    TRC(tr, w, 0);

    {
      uint8_t* dst = Q.WQ + j * WQ_SL + rb * 3456 + tid * 16;
#pragma unroll
      for (int u = 0; u < 5; u++) {
        stg128_if((u < 4 || rb < 8) && tid < 216, dst + u * (16 * 3456), wv[u].x, wv[u].y, wv[u].z, wv[u].w);
        if (u == 0) TRC(tr, w, 60);
      }
      if (Q.zero == 0) {
        float s[8];
#pragma unroll
        for (int u = 0; u < 5; u++) {
          const uint32_t x[4] = {wv[u].x, wv[u].y, wv[u].z, wv[u].w};
#pragma unroll
          for (int e = 0; e < 4; e++) { s[2 * e] = u ? s[2 * e] + blo(x[e]) : blo(x[e]); s[2 * e + 1] = u ? s[2 * e + 1] + bhi(x[e]) : bhi(x[e]); }
        }
#pragma unroll
        for (int m = 4; m; m >>= 1) {
#pragma unroll
          for (int e = 0; e < m; e++) s[e] = ((tid & m) ? s[e + m] : s[e]) + __shfl_xor_sync(~0u, (tid & m) ? s[e] : s[e + m], m);
        }
        stg32_if(tid < 216, Q.CSP + bid * 216 + tid, __float_as_uint(s[0]));
      }
      __syncwarp();
      if (lane == 0) mbar_arrive(bars + B_IMG);
    }
    reg_alloc<224>();
    auto fetch_wo = [&]() {
#pragma unroll 1
      for (int u = tid; u < 328; u += 256) {
        const int m = min(41 * rb + (u >> 3), 647), k8 = m / 9;
        cp_async16(sb + SM_WOI + u * 16, (const uint8_t*)Q.wo + (8 * k8 + (u & 7)) * (DM * 2) + (72 * j + 8 * (m - k8 * 9)) * 2);
      }
    };
    const uint32_t epoch = ldcg32(Q.flags + (rb * 2 + w) * 32 + FR_EP + j);
    TRC(tr, w, 1);

#pragma unroll 1
    for (int L = 0; L < 2; L++) {
      const int tb = 2 + L * 24;
      asm volatile("" : "+r"(lane), "+r"(g), "+r"(t));
      PHASE;
      (void)tb;
      const uint32_t tag = epoch * 2 + L + 1;
      {
        uint32_t Pk[27][2];
        float rk[2][2], sc[2][2];
        const bool up0 = 2 * t > g, up1 = 2 * t + 1 > g;
        constexpr int HA_[6] = {0, 2, 4, 7, 12, 15}, HC_[6] = {6, 9, 10, 11, 14, 17};
        const bool remote = pq == 0 && rb > 0;
        uint4* hp = Q.HALO + ((((rb - (pq == 0)) * 2 + pw) * 8 + j) * 6) * 32 + lane;
        const uint32_t att = 2 * ST_BYTES + pw * 3072 + lane * 16;
        const uint8_t* hs = remote ? (const uint8_t*)hp : smem_raw + att + (pq == 3 ? 0 : pq == 2 ? ST_BYTES + 8192 : 8192);
        uint8_t* od = z1_block(rb, w, 0) + (9 * j) * 1024 + (4 * (q & 1) + pw) * 128 + lane * 4;
        ACLK_INIT;
        {
          float acc[108];
#pragma unroll
          for (int i = 0; i < 108; i++) acc[i] = 0.f;
          float sx[2] = {0.f, 0.f}, sq[2] = {0.f, 0.f};
          uint32_t prev = 0;
#pragma unroll 1
          for (int kb = 0; kb < 7; kb++) {
            wait_ab();
            TRC(tr && kb == 0, w, tb + 0);
            PCLK(kb * 4);
            const uint32_t st = sb + c.s * ST_BYTES, da = dlo(st + w * 8192, 16), db = dlo(st + ST_B, 3456);
            wgmma_fence();
#pragma unroll
            for (int kk = 0; kk < 4; kk++) {
              wgmma_ss_n216(acc, dsc<1024, 1>(da, kk * 32), dsc<128, 0>(db, kk * 6912), 1);
              if (kk == 0) { wgmma_commit(); wgmma_wait<1>(); if (kb > 0) release(prev); }
              if (kk == 3) wgmma_commit();
              if (kk == XK1) {
            if (kb >= KS && kb < KS + 3) {
              mbar_wait_c(bars + B_WT + w * 8, 0);
#pragma unroll
              for (int u = 0; u < 3; u++) {
                const uint2 x = lds64(stg + (2 * q + (lane >> 4)) * 1152 + (lane & 15) * 8 + (kb - KS) * 384 + u * 128);
                sx[0] += blo(x.x) + bhi(x.x); sx[1] += blo(x.y) + bhi(x.y);
                sq[0] = fmaf(blo(x.x), blo(x.x), fmaf(bhi(x.x), bhi(x.x), sq[0])); sq[1] = fmaf(blo(x.y), blo(x.y), fmaf(bhi(x.y), bhi(x.y), sq[1]));
              }
            }
            if (kb == KS + 3) {
              const bool o = lane & 1;
              float v = (o ? sq[0] + sq[1] : sx[0] + sx[1]) + __shfl_xor_sync(~0u, o ? sx[0] + sx[1] : sq[0] + sq[1], 1);
              v += __shfl_xor_sync(~0u, v, 2); v += __shfl_xor_sync(~0u, v, 4); v += __shfl_xor_sync(~0u, v, 8);
              const float m = v * (-1.f / DM), r = rsq_fast(fmaxf(fmaf(__shfl_xor_sync(~0u, v, 1), 1.f / DM, -m * m), 0.f) + LN_EPS);
              ll_st128_if(!(lane & 15), Q.XST + rb * 256 + (lane >> 4) * 128 + (1 - w) * 64 + 8 * j + 2 * q, m, r, tag);
            }
              }
              if (kk == XK2 && L == 0) {
            if (kb == 0) fetch_wo();
            if (kb == 3) {
              asm volatile("cp.async.wait_all;" ::: "memory");
              fence_async_s();
              __syncwarp();
              if (lane == 0) mbar_arrive(bars + B_WOI);
            }
              }
            }
            prev = c.s; c.next();
          }
          const uint32_t ls = sb + L * (3 * ST_BYTES), cs = ls + SM_CSQ + t * 8;
          float2 cv[27];
          mbar_wait_c(bars + B_XRW + 8, L);
#pragma unroll
          for (int kb = 7; kb < 9; kb++) {
            wait_ab();
            yield(9 - kb, LAG1);
            PCLK(kb * 4);
            const uint32_t st = sb + c.s * ST_BYTES, da = dlo(st + w * 8192, 16), db = dlo(st + ST_B, 3456);
            wgmma_fence();
#pragma unroll
            for (int kk = 0; kk < 4; kk++) {
              wgmma_ss_n216(acc, dsc<1024, 1>(da, kk * 32), dsc<128, 0>(db, kk * 6912), 1);
              if (kk == 0) { wgmma_commit(); wgmma_wait<1>(); release(prev); }
              if (kb == 7 && kk < 3) {
#pragma unroll
                for (int G = 9 * kk; G < 9 * kk + 9; G++) cv[G] = lds64f(cs + G * 32);
                wgmma_fence();
              }
            }
            wgmma_commit();
            prev = c.s; c.next();
          }
          yield_done();
          mbar_wait_c(bars + B_CSQ, L);
          const uint32_t xs = ls + SM_XST + pw * 768 + 256 + pq * 128;
          const float2 n0 = lds64f(xs + g * 8), n1 = lds64f(xs + g * 8 + 64);
          const float m0 = n0.x, m1 = n1.x;
#pragma unroll
          for (int u = 0; u < 4; u++) {
            rk[u >> 1][u & 1] = __uint_as_float(lds32(xs + t * 16 + ((u & 1 ? up1 : up0) ? -64 : 0) + (u & 1) * 8 + (u >> 1) * 64 + 4));
            sc[u >> 1][u & 1] = rk[u >> 1][u & 1] * ((u >> 1 ? n1.y : n0.y) * (0.23570226039551584f * 1.4426950408889634f));
          }
          PCLK(36);
          wgmma_wait<0>();
          PCLK(37);
          release(prev);
          lagph ^= 1;
          TRC(tr, w, tb + 1);
          ACLK(0);
#pragma unroll
          for (int G = 9; G < 27; G++) Pk[G][1] = pack2(fmaf(m1, cv[G].x, acc[4 * G + 2]), fmaf(m1, cv[G].y, acc[4 * G + 3]));
          if (pq < 3) {
#pragma unroll
            for (int i = 0; i < 6; i++) sts128(sb + att + (pq & 1) * ST_BYTES + w * 8192 + i * 512, Pk[9 + HA_[i]][1], Pk[10 + HA_[i]][1], tag, Pk[9 + HC_[i]][1]);
          } else if (rb < 15) {
#pragma unroll
            for (int i = 0; i < 6; i++) ll_st128(hp + i * 32, __uint_as_float(Pk[9 + HA_[i]][1]), __uint_as_float(Pk[10 + HA_[i]][1]), tag, __uint_as_float(Pk[9 + HC_[i]][1]));
          }
          if (w) bar_arrive(1, 256);
          if (HOLD == 1 && w) bar_sync(3, 256);
#pragma unroll
          for (int G = 0; G < 27; G++) {
            Pk[G][0] = pack2(fmaf(m0, cv[G].x, acc[4 * G]), fmaf(m0, cv[G].y, acc[4 * G + 1]));
            if (G < 9) Pk[G][1] = pack2(fmaf(m1, cv[G].x, acc[4 * G + 2]), fmaf(m1, cv[G].y, acc[4 * G + 3]));
          }
        }
        if (HOLD == 2 && w) bar_sync(3, 256);
        ACLK(1);
        constexpr int GA_[4] = {0, 2, 4, 7}, GB_[4] = {1, 3, 5, 8}, GC_[4] = {2, 4, 6, 6};
        float S1[4][4], S2[4][4];
        uint32_t qa[4][2], qc[4][2];
#pragma unroll
        for (int h = 0; h < 4; h++) {
#pragma unroll
          for (int r = 0; r < 2; r++) {
            qa[h][r] = (h == 0 || h == 3 || t >= h) ? Pk[GA_[h]][r] : 0u;
            qc[h][r] = (h == 3 ? t == 3 : t <= h) ? Pk[GC_[h]][r] : 0u;
          }
#pragma unroll
          for (int i = 0; i < 4; i++) S1[h][i] = S2[h][i] = 0.f;
          mma16(S1[h], qa[h][0], qa[h][1], Pk[GB_[h]][0], Pk[GB_[h]][1], Pk[9 + GA_[h]][0], Pk[9 + GB_[h]][0]);
          mma16(S2[h], qa[h][0], qa[h][1], Pk[GB_[h]][0], Pk[GB_[h]][1], Pk[9 + GA_[h]][1], Pk[9 + GB_[h]][1]);
        }
#pragma unroll
        for (int h = 0; h < 4; h++) {
          mma8(S1[h], qc[h][0], qc[h][1], Pk[9 + GC_[h]][0]);
          mma8(S2[h], qc[h][0], qc[h][1], Pk[9 + GC_[h]][1]);
        }
        if (HOLD && HREL == 2 && !w) bar_arrive(3, 256);
        uint32_t V1[9], V2[9];
#pragma unroll
        for (int i = 0; i < 9; i++) { V1[i] = movm(Pk[18 + i][0]); V2[i] = movm(Pk[18 + i][1]); }
        uint4 hv[6];
#pragma unroll
        for (int i = 0; i < 6; i++) hv[i] = ll_ld128g(hs + i * 512);
        const uint32_t mup = (up0 ? 0xffffu : 0u) | (up1 ? 0xffff0000u : 0u);
        auto finish = [&](const float (&x0)[4], const float (&x1)[4], const uint32_t (&Vb)[9], uint32_t ma, int hi) {
          uint32_t p[4], n[4];
          float rs[4];
#pragma unroll
          for (int h = 0; h < 4; h++) {
            const float m = qmax(fmaxf(x0[h], x1[h])), e0 = ex2(x0[h] - m), e1 = ex2(x1[h] - m);
            n[h] = pack2(e0, e1);
            p[h] = pack2(e0 * rk[hi][0], e1 * rk[hi][1]);
          }
#pragma unroll
          for (int h = 0; h < 4; h += 2) {
            float D[4] = {0.f, 0.f, 0.f, 0.f};
            mma8(D, n[h], n[h + 1], 0x3f803f80u);
            rs[h] = rcp_fast(D[0]); rs[h + 1] = rcp_fast(D[2]);
          }
#pragma unroll
          for (int i = 0; i < 9; i++) {
            const int h = i < 4 ? 0 : i == 4 ? 1 : 2;
            const bool nx = (i == 2 || i == 4 || i == 6) ? 2 * t >= i : i == 3 || i > 6;
            float O[4] = {0.f, 0.f, 0.f, 0.f};
            mma16(O, p[h] & ma, p[h + 1] & ma, p[h] & ~ma, p[h + 1] & ~ma, V1[i], Vb[i]);
            const float r = nx ? rs[h + 1] : rs[h];
            stg32(od + i * 1024 + hi * 256, pack2((nx ? O[2] : O[0]) * r, (nx ? O[3] : O[1]) * r));
          }
        };
        {
          float x0[4], x1[4];
#pragma unroll
          for (int h = 0; h < 4; h++) { x0[h] = (up0 ? S1[h][2] : S2[h][2]) * sc[1][0]; x1[h] = (up1 ? S1[h][3] : S2[h][3]) * sc[1][1]; }
          finish(x0, x1, V2, mup, 1);
        }
        ACLK(2);
        if (HOLD && HREL == 0 && !w) bar_arrive(3, 256);
        bar_sync(1 + w, 256 - 128 * w);
#pragma unroll 1
        for (int it = 0; it < (1 << 20); it++) {
          if (remote) {
            bool ok = true;
#pragma unroll
            for (int i = 0; i < 6; i++) ok = ok && hv[i].z == tag;
            if (__all_sync(~0u, ok)) break;
          }
#pragma unroll
          for (int i = 0; i < 6; i++) hv[i] = ll_ld128g(hs + i * 512);
          if (!remote) break;
        }
        if (HOLD && HREL == 3 && !w) bar_arrive(3, 256);
        uint32_t H[18];
#pragma unroll
        for (int i = 0; i < 6; i++) { H[HA_[i]] = hv[i].x; H[HA_[i] + 1] = hv[i].y; H[HC_[i]] = hv[i].w; }
        float S0[4][4];
#pragma unroll
        for (int h = 0; h < 4; h++) {
#pragma unroll
          for (int i = 0; i < 4; i++) S0[h][i] = 0.f;
          mma16(S0[h], qa[h][0], qa[h][1], Pk[GB_[h]][0], Pk[GB_[h]][1], H[GA_[h]], H[GB_[h]]);
        }
#pragma unroll
        for (int h = 0; h < 4; h++) mma8(S0[h], qc[h][0], qc[h][1], H[GC_[h]]);
        uint32_t V0[9];
#pragma unroll
        for (int i = 0; i < 9; i++) V0[i] = movm(H[9 + i]);
        if (HOLD && HREL == 1 && !w) bar_arrive(3, 256);
        ACLK(3);
        {
          const bool nohalo = (rb | pq) == 0;
          const float b0 = up0 && nohalo ? -INFINITY : 0.f, b1 = up1 && nohalo ? -INFINITY : 0.f;
          float x0[4], x1[4];
#pragma unroll
          for (int h = 0; h < 4; h++) { x0[h] = fmaf(up0 ? S0[h][0] : S1[h][0], sc[0][0], b0); x1[h] = fmaf(up1 ? S0[h][1] : S1[h][1], sc[0][1], b1); }
          finish(x0, x1, V0, ~mup, 0);
        }
        ACLK(4);
        signal(EV_O);
        ACLK_OUT;
        TRC(tr, w, tb + 2);
      }
      if (c.s) { c.s = 0; c.ph ^= 1; }
      PHASE;
      {
        float acc[36];
        const int hw = rb * 2 + w;
        const uint32_t xt = stg + (8 * q + g) * 144 + t * 4;
        uint32_t xm = sb + SM_STG + 9216 + (8 * q + (lane & 7)) * 144 + (lane & 8) * 576 + (lane & 16);
        uint8_t* xn = xn_block(hw) + j * 9216 + q * 256 + lane * 4;
        uint32_t* sp = (uint32_t*)(Q.ST1 + (hw * 8 + j) * 32 + 8 * q) + lane;
        const uint4* sg = Q.ST1 + (hw * 8 + t) * 32 + 8 * q + g;
        asm volatile("" : "+r"(xm), "+l"(xn), "+l"(sp), "+l"(sg));
        mbar_wait_c(bars + B_RES + w * 8, L);
        TRC(tr, w, tb + 21);
#pragma unroll
        for (int i = 0; i < 18; i++) { const uint32_t x = lds32(xt + (i >> 1) * 16 + (i & 1) * 4608); acc[2 * i] = blo(x); acc[2 * i + 1] = bhi(x); asm volatile("" : "+f"(acc[2 * i]), "+f"(acc[2 * i + 1])); }
        mbar_wait_c(bars + B_WF, L);
        const uint32_t db = dlo(sb, 1152), of = bars + (w ? B_OF + 40 : B_AV + 96);
        uint32_t da[5];
#pragma unroll
        for (int e = 0; e < 5; e++) da[e] = __shfl_sync(~0u, dlo(sb + o_place(w, e), 1024), 0);
        if (w) {
#pragma unroll 1
          for (int kb = q ^ VQ; kb < 9; kb += 4) {
            const uint32_t e = (kb + 1) >> 1;
            mbar_wait_c(bars + B_OF + e * 8, L);
            check(Int<8>{}, sb + o_place(0, e) + (kb && !(kb & 1)) * 8192, z1_block(rb, 0, 0) + kb * 8192);
            if (lane <= !kb) mbar_arrive(bars + B_AV + (12 + e) * 8);
          }
          bar_sync(7, 256);
        }
        mbar_wait_c(of, L & w);
        TRC(tr, w, tb + 3);
        wgmma_fence();
#pragma unroll
        for (int kk = 0; kk < 4; kk++) wgmma_ss_n72(acc, dsc<128, 0>(da[0], kk * 2048), dsc<128, 0>(db, kk * 2304), 1);
        wgmma_commit();
#pragma unroll 1
        for (int h = 0; h < 2; h++) {
#pragma unroll
          for (int u = 0; u < 4; u++) {
            if (!(u & 1)) { mbar_wait_c(of + 8 + h * 16 + u * 4, 1 + 2 * h + (u >> 1) < SPL ? L & w : L); wgmma_fence(); }
            if (u == 3 && h && !w) bar_arrive(7, 256);
#pragma unroll
            for (int kk = 0; kk < 4; kk++) wgmma_ss_n72(acc, dsc<128, 0>(da[1 + (u >> 1)], (u & 1) * 8192 + kk * 2048), dsc<128, 0>(db + h * 2304, (1 + u) * 9216 + kk * 2304), 1);
            if (u != 2) wgmma_commit();
            if (u == 0) { wgmma_wait<1>(); if (lane + w == 0 && h) mbar_arrive(bars + B_X3); }
          }
          da[1] = da[3]; da[2] = da[4];
        }
        RCLK_INIT;
        wgmma_wait<0>();
        RCLK(0);
        if (lane < 2) mbar_arrive_cluster(ebar + B_XD - B_EMPTY + w * 8);
        TRC(tr && P5TRACE != 5, w, tb + 4);
        {
          float s0 = 0.f, s1 = 0.f, q0 = 0.f, q1 = 0.f;
#pragma unroll
          for (int i = 0; i < 36; i++) {
            if (i & 2) { s1 += acc[i]; q1 = fmaf(acc[i], acc[i], q1); } else { s0 += acc[i]; q0 = fmaf(acc[i], acc[i], q0); }
          }
          const bool o1 = t & 1, o2 = t & 2;
          const float ss = (o1 ? s1 : s0) + __shfl_xor_sync(~0u, o1 ? s0 : s1, 1), sq = (o1 ? q1 : q0) + __shfl_xor_sync(~0u, o1 ? q0 : q1, 1);
          const float v = (o2 ? sq : ss) + __shfl_xor_sync(~0u, o2 ? ss : sq, 2);
          asm volatile("st.relaxed.gpu.global.u32 [%0], %1;" ::"l"(sp), "r"(__float_as_uint(v)) : "memory");
        }
        RCLK(1);
        RCLK(2);
        pause<PDEL>(Q.zero);
        uint4 pa, pb;
        auto there = [&](const uint4& a, const uint4& b) { return __all_sync(~0u, max(max(max(a.x, a.y), max(a.z, a.w)), max(max(b.x, b.y), max(b.z, b.w))) != ~0u); };
#pragma unroll 1
        for (int it = 0; it < (1 << 20); it++) {
          pa = ll_ld128(sg); pb = ll_ld128(sg + 128);
          if (there(pa, pb)) break;
        }
        RCLK(3);
        float mean0 = qsum(__uint_as_float(pa.x) + __uint_as_float(pb.x)) * (-1.f / DM), mean1 = qsum(__uint_as_float(pa.y) + __uint_as_float(pb.y)) * (-1.f / DM);
        const float rs0 = GA * rsq_fast(fmaxf(fmaf(qsum(__uint_as_float(pa.z) + __uint_as_float(pb.z)), 1.f / DM, -mean0 * mean0), 0.f) + LN_EPS);
        const float rs1 = GA * rsq_fast(fmaxf(fmaf(qsum(__uint_as_float(pa.w) + __uint_as_float(pb.w)), 1.f / DM, -mean1 * mean1), 0.f) + LN_EPS);
        mean0 *= rs0; mean1 *= rs1;
#pragma unroll
        for (int i = 0; i < 18; i++) {
          const float a = (i & 1) ? rs1 : rs0, b = (i & 1) ? mean1 : mean0;
          stg32(xn + (i >> 1) * 1024 + (i & 1) * 128, pack2(fmaf(acc[2 * i], a, b), fmaf(acc[2 * i + 1], a, b)));
        }
        signal(EV_X1);
        RCLK(4);
        if (w) {
#pragma unroll 1
          for (int u = q; u < 24; u += 4) {
            const uint32_t mb = u < 2 * SPL ? u >= SPL : u & 1, k = u < 2 * SPL ? u - mb * SPL : u >> 1;
            mbar_wait_c(bars + B_AF3 + mb * 96 + k * 8, L);
            SCLK3(u);
            check(Int<6>{}, sb + k * 12288 + mb * 6144, xn_block(rb * 2 + mb) + k * 6144);
            SCLK3(24 + u);
            if (lane <= (u < 2 * SPL)) mbar_arrive(bars + B_AV + (u < SPL ? 12 + k : k) * 8);
          }
          TRVI(lane == 0 && P5TRACE != 5, 5, 56 + L * 4 + q, rp);
          mbar_wait_c(bars + B_S5, XAL ? 0 : L);
        }
#pragma unroll
        for (int u = 0; u < 4; u++)
          stsm4(xm + u * 32, pack2(acc[8 * u], acc[8 * u + 1]), pack2(acc[8 * u + 2], acc[8 * u + 3]), pack2(acc[8 * u + 4], acc[8 * u + 5]), pack2(acc[8 * u + 6], acc[8 * u + 7]));
        asm volatile("stmatrix.sync.aligned.m8n8.x2.shared.b16 [%0], {%1,%2};" ::"r"(xm + 128), "r"(pack2(acc[32], acc[33])), "r"(pack2(acc[34], acc[35])) : "memory");
        fence_async_s();
        signal(EV_XS);
        RCLK(5);
        TRC(tr, w, tb + 5);
        RCLK(6);
        RCLK_OUT;
      }
      PHASE;
      {
      float acc[160];
#pragma unroll
      for (int i = 0; i < 160; i++) acc[i] = 0.f;
      float s[2] = {0.f, 0.f}, qq[2] = {0.f, 0.f}, zo = 0.f;
      const uint32_t zp = sb + SM_ZP3 + (tid & 127) * 4;
      auto zstat = [&](int mb, bool on) {
        const bool o1 = t & 1, o2 = t & 2;
        const float ss = ((o1 ? s[1] : s[0]) + __shfl_xor_sync(~0u, o1 ? s[0] : s[1], 1)) * 0x1p60f, sq = (o1 ? qq[1] : qq[0]) + __shfl_xor_sync(~0u, o1 ? qq[0] : qq[1], 1);
        const uint32_t v = __float_as_uint((o2 ? sq : ss) + zo + __shfl_xor_sync(~0u, o2 ? ss : sq, 2));
        asm volatile("{\n.reg .pred p, q, r;\nsetp.eq.u32 p, %4, 1;\nsetp.eq.u32 q, %4, 2;\nsetp.eq.and.u32 r, %5, 0, q;\n@p st.shared.u32 [%0], %2;\n@p bar.arrive 13, 256;\n"
                     "@q st.relaxed.gpu.global.u32 [%1], %2;\n@r mbarrier.arrive.shared::cta.b64 _, [%3];\n}" ::"r"(zp + mb * 512), "l"((uint32_t*)(Q.ZST + ((rb * 2 + mb) * 8 + j) * 32) + (tid & 127)),
                     "r"(v), "r"(bars + B_ZS + mb * 8), "r"(on ? 1 + w : 0), "r"(lane) : "memory");
        s[0] = s[1] = qq[0] = qq[1] = 0.f;
      };
      const uint32_t ebar3 = ebar + (B_E3 - B_EMPTY);
#pragma unroll 1
      for (int half = 0; half < 2; half++) {
        const bool big = half != w;
        auto rel3 = [&](int p) { if (lane < 2) mbar_arrive_cluster(ebar3 + p * 8); };
        auto pass = [&](auto nk) {
          constexpr int NK = nk.value;
          uint32_t d0 = dlo(sb, 1024), ph = half & ~w, af = bars + B_AV;
          const uint32_t db = dlo(sb + SM_B3, NK == 3 ? 6144 : 2048);
          const bool lead = NK == 3 && !half;
          if (lead) {
#pragma unroll
            for (int u = 0; u < 2 * SPL; u++) {
              const int mb = u / SPL, p = u % SPL;
              if (!mb) mbar_wait_c(bars + B_F3 + p * 8, 0);
              mbar_wait_c(af + (mb ? p : 12 + p) * 8, mb || p > 4 ? L : 1);
              TRC(tr && u == 0, w, tb + 6);
              SCLK2(u);
              if (p == 0) SCLK(mb * 4);
              wgmma_fence();
#pragma unroll
              for (int kk = 0; kk < 3; kk++) {
                wgmma_ss_n128(acc + mb * 80, dsc<128, 0>(d0, p * 12288 + kk * 2048 + mb * 6144), dsc<1024, 1>(db, p * 12288 + kk * 2048), p + kk > 0);
                if (kk == 0 && u > SPL) { wgmma_commit(); wgmma_wait<1>(); rel3(p - 1); }
              }
              wgmma_commit();
            }
          }
#pragma unroll 1
          for (int it = 0; it < 6 / NK; it++) {
#pragma unroll
            for (int p = 0; p < 6; p++) {
              if (p < SPL && lead && it == 0) continue;
              if (NK == 3) mbar_wait_c(af + p * 8, L);
              if (p == 0 && it == 0) bar_sync(6 + w, 256);
              mbar_wait_c(bars + B_F3 + p * 8, ph);
              TRC(tr && p == 0 && it == 0, w, tb + 6 + half * 4);
              if (lead) SCLK2(12 + it * 6 + p);
              if (NK == 2 ? !(p & 1) : p % 3 == 0) SCLK(half * 11 + (NK == 2 ? it * 3 + p / 2 : it * 2 + p / 3));
              wgmma_fence();
#pragma unroll
              for (int u = 0; u < 2 * NK; u++) {
                const int kk = u >> 1, mb = u & 1, e = p * NK + kk;
                const uint64_t da = dsc<128, 0>(d0, (e / 3) * 12288 + (e % 3) * 2048 + mb * 6144);
                if (NK == 3) wgmma_ss_n128(acc + mb * 80, da, dsc<1024, 1>(db, p * 12288 + kk * 2048), e > 0 || it > 0);
                else wgmma_ss_n160(acc + mb * 80, da, dsc<1024, 1>(db, p * 12288 + kk * 6144), e > 0 || it > 0);
                if (u == 0) { wgmma_commit(); wgmma_wait<1>(); if (p > 0 || it > 0) rel3((p + 5) % 6); }
                if (p * 8 + u == (NK == 2 ? HO3 : HO4) && it == 6 / NK - 1) bar_arrive(7 - w, 256);
              }
              wgmma_commit();
            }
            d0 += NK * 1536; af += 48;
            ph ^= 1;
          }
        };
        const int go = (j & 1) ? (big ? 0 : 20) : (big ? 16 : 0);
        const float* gbp = (const float*)(smem_raw + SM_OFF + 8);
        asm volatile("" : "+l"(gbp));
        uint8_t* zd = half ? z1_block(rb, 0, j) + go * 1024 + (q & 1) * 2048 + (q >> 1) * 512 + lane * 16 : z2_block(rb, j) + q * 9216 + go * 128 + ((g & 3) * 2 + (g >> 2)) * 16 + t * 4;
        asm volatile("" : "+l"(zd));
        if (big) pass(Int<2>{}); else pass(Int<3>{});
        if (w) { bar_sync(13, 256); zo = __uint_as_float(lds32(zp + half * 512)); }
        if (half) { zstat(1, true); if (XAL) mbar_wait_c(bars + B_S5, 1); }
        const uint32_t off2 = lds32(sb + SM_OFF);
        wgmma_wait<0>();
        SCLK(half * 11 + 9);
        rel3(5);
        TRC(tr, w, tb + 7 + half * 4);
        auto gelu = [&](auto z2) {
          constexpr int NC = z2.value ? NC2 : NC1;
          float gate[NC], gb = GB, gn = GB;
          uint32_t qa[2][3] = {{0, 0, 0}, {0, 0, 0}};
#pragma unroll
          for (int e = 0; e < NC; e++) gate[e] = GB;
#pragma unroll
          for (int G = 0; G < 20; G++) {
            if (G == 16 && !big) break;
            if (G % (z2.value ? LD2 : LD1) == 0) { gb = gn; if (G < 20 - (z2.value ? LD2 : LD1)) asm volatile("ld.f32 %0, [%1];" : "=f"(gn) : "l"(gbp) : "memory"); }
#pragma unroll
            for (int r = 0; r < 2; r++) {
              float z[2];
              float& gt = gate[(G * 2 + r) % NC];
#pragma unroll
              for (int e = 0; e < 2; e++) {
                const float v = acc[4 * G + 2 * r + e];
                z[e] = fmaf(v, tanh_fast(v * fmaf(v, v, gt)), v);
                if (z2.value) { s[r] = fmaf(z[e], 0x1p-60f, s[r]); qq[r] = fmaf(z[e], z[e], qq[r]); }
              }
              const uint32_t pk = pack2(z[0], z[1]);
              if (z2.value) {
                stg32(zd + G * 128 + r * 4608, hsub2(pk, off2));
                gt = fmaf(qq[r], s[r], gb);
              } else {
                gt = fmaf(__uint_as_float(pk), 0x1p-60f, gb);
                if ((G & 3) == 3) stg128(zd + (G >> 2) * 4096 + r * 1024, qa[r][0], qa[r][1], qa[r][2], pk);
                else qa[r][G & 3] = pk;
              }
            }
          }
        };
#pragma unroll 1
        for (int mb = 0;; mb++) {
          if (half) gelu(Int<0>{}); else gelu(Int<1>{});
          if (mb) break;
          zstat(0, !half);
#pragma unroll
          for (int i = 0; i < 80; i++) acc[i] = acc[80 + i];
          zd += half ? 8 * ZB : 128 * ZB;
        }
        mbar_wait_c(bars + B_GATE3, L);
        signal(half ? EV_Z1 : EV_ZN);
        SCLK(half * 11 + 10);
        TRC(tr, w, tb + 8 + half * 4);
      }
      }
      PHASE;
      const uint32_t aoff = (pw * 64 + pq * 16 + (lane & 15)) * 128 + (((lane >> 4) ^ (lane & 7)) << 4);
      uint32_t hA[18][4];
      {
        float acc[144];
        {
          const uint32_t c16 = lds32(sb + SM_OFF + 12), a[4] = {c16, c16, c16, c16};
          wgmma_fence();
          wgmma_rs_n144(acc, a, dsc<0, 0>(dlo(sb + SM_CV + 512, 0), 0), 0);
          wgmma_rs_n144(acc + 72, a, dsc<0, 0>(dlo(sb + SM_CV + 512, 0), 128), 0);
          wgmma_commit();
        }
        uint32_t prev = 0;
        auto stage = [&](int kb, bool odd) {
          mbar_wait_c(bars + B_FULL + c.s * 8, c.ph);
          TRC(tr && kb == 0, w, tb + 13);
          SCLK(22 + kb);
          const uint32_t st = sb + c.s * ST_BYTES, db = dlo(st + ST_B, 4608), rt = sb + SM_RT + kb * 128 + t * 8;
          uint32_t a[4][4];
#pragma unroll
          for (int kk = 0; kk < 4; kk++) {
            uint32_t r[4];
            ldsm4(r, st + (aoff ^ (kk << 5)));
            const uint2 sc = lds64(rt + kk * 32);
            a[kk][0] = hmul2(__byte_perm(r[0], r[2], 0x5410), sc.x); a[kk][2] = hmul2(__byte_perm(r[0], r[2], 0x7632), sc.y);
            a[kk][1] = hmul2(__byte_perm(r[1], r[3], 0x5410), sc.x); a[kk][3] = hmul2(__byte_perm(r[1], r[3], 0x7632), sc.y);
          }
          if (!odd && kb + w == 0) bar_sync(6, 256);
          wgmma_fence();
#pragma unroll
          for (int i = 0; i < 8; i++) {
            const int kk = i & 3, hf = i >> 2;
            wgmma_rs_n144(acc + hf * 72, a[kk], dsc<128, 0>(db, kk * 9216 + hf * 2304), 1);
            if (i == 0) { wgmma_commit(); wgmma_wait<1>(); if (kb) release(prev); }
            if (i == 3) wgmma_commit();
          }
          wgmma_commit();
          prev = c.s; c.next();
        };
#pragma unroll 1
        for (int kb = 0; kb < 32; kb += 2) {
          if (!(kb & 7)) mbar_wait_c(bars + B_RT + kb, L);
          stage(kb, false);
          stage(kb + 1, true);
        }
        mbar_wait_c(bars + B_CV + pw * 8, L);
        const float gk = 0.5f / GA;
        const float c1 = __uint_as_float(lds32(sb + SM_OFF + 4));
        const float gb0 = -gk * (c1 + __uint_as_float(lds32(sb + SM_CV + pw * 256 + (16 * pq + g) * 4))), gb1 = -gk * (c1 + __uint_as_float(lds32(sb + SM_CV + pw * 256 + (16 * pq + g + 8) * 4)));
        if (w == 1) { mbar_wait_c(bars + B_FULL + c.s * 8, c.ph); release(c.s); c.next(); }
        mbar_wait_c(bars + B_FULL + c.s * 8, c.ph);
        const uint32_t zs = sb + c.s * ST_BYTES + ST_B + (tid & 127) * 16;
        uint4 zl, zh;
#pragma unroll
        for (int u = 0; u < 18; u++) {
          if (u == 0) wgmma_wait<1>();
          if (u == 9) {
            wgmma_wait<0>();
            release(prev);
            if (L == 0) signal(EV_PT);
            TRC(tr, w, tb + 14);
            SCLK(54);
          }
          if (!(u & 1)) { zl = lds128(zs + u * 2048); zh = lds128(zs + u * 2048 + 2048); }
          const uint4 z = (u & 1) ? make_uint4(zl.z, zh.z, zl.w, zh.w) : make_uint4(zl.x, zh.x, zl.y, zh.y);
          hA[u][0] = hmul2(z.x, pack2(fmaf(acc[8 * u], gk, gb0), fmaf(acc[8 * u + 1], gk, gb0)));
          hA[u][1] = hmul2(z.y, pack2(fmaf(acc[8 * u + 2], gk, gb1), fmaf(acc[8 * u + 3], gk, gb1)));
          hA[u][2] = hmul2(z.z, pack2(fmaf(acc[8 * u + 4], gk, gb0), fmaf(acc[8 * u + 5], gk, gb0)));
          hA[u][3] = hmul2(z.w, pack2(fmaf(acc[8 * u + 6], gk, gb1), fmaf(acc[8 * u + 7], gk, gb1)));
        }
        __syncwarp();
        release(c.s);
        c.next();
        if (w == 0) { mbar_wait_c(bars + B_FULL + c.s * 8, c.ph); release(c.s); c.next(); }
        TRC(tr, w, tb + 15);
      }
      {
        CLK_INIT;
        if (w == 1) bar_arrive(6, 256);
        uint4 v[4];
#pragma unroll
        for (int u = 0; u < 4; u++) v[u] = make_uint4(0u, 0u, 0u, 0u);
        uint32_t rl = sb + SM_STG + pw * 8192 + pq * 2048 + (lane >> 3) * 128 + (((lane & 7) ^ (lane >> 3)) << 4);
        uint8_t* rd = Q.out + (128 * rb + 32 * pq + 2 * (lane >> 3) + pw) * (DM * 2) + j * 128 + (lane & 7) * 16;
        asm volatile("" : "+r"(rl), "+l"(rd));
        auto send = [&](int u0, int u1) {
#pragma unroll
          for (int u = u0; u < u1; u++)
            asm volatile("red.relaxed.gpu.global.add.noftz.v4.bf16x2 [%0], {%1,%2,%3,%4};" ::"l"(rd + u * (8 * DM * 2)), "r"(v[u].x), "r"(v[u].y), "r"(v[u].z), "r"(v[u].w) : "memory");
        };
#pragma unroll 1
        for (int p = 0; p < 9; p++) {
          float acc[32];
          CLK(0);
          mbar_wait_c(bars + B_FULL + c.s * 8, c.ph);
          const uint32_t db = dlo(sb + c.s * ST_BYTES + ST_B, 0);
          CLK(1);
          bar_sync(6 + w, 256);
          CLK(2);
          wgmma_fence();
#pragma unroll
          for (int kk = 0; kk < 18; kk++) {
            wgmma_rs_n64(acc, hA[kk], dsc<1024, 1>(db, kk * 2048), kk != 0);
            if (kk == PPK && (w == 0 || p < 8)) bar_arrive(7 - w, 256);
          }
          wgmma_commit();
          CLK(3);
          if (p > 0) { send(NOW, 4); rd += p + j == 9 ? -1024 : 128; }
          CLK(5);
          wgmma_wait<0>();
          CLK(4);
          if (L == 0 || p < 5) release(c.s);
          c.next();
          TRC(tr && p == 8, w, tb + 16);
#pragma unroll
          for (int u = 0; u < 4; u++)
            stsm4(sb + SM_STG + (aoff ^ (u << 5)), pack2(acc[8 * u], acc[8 * u + 1]), pack2(acc[8 * u + 2], acc[8 * u + 3]), pack2(acc[8 * u + 4], acc[8 * u + 5]), pack2(acc[8 * u + 6], acc[8 * u + 7]));
          __syncwarp();
#pragma unroll
          for (int u = 0; u < 4; u++) v[u] = lds128(rl + u * 512 ^ (u & 1) << 6);
          send(0, NOW);
        }
        send(NOW, 4);
        TRC(tr, w, tb + 17);
        if (L == 0) signal(EV_PT);
        CLK_OUT;
        TRC(tr, w, tb + 18);
      }
    }
    if ((tid & 127) == 0) Q.flags[(rb * 2 + w) * 32 + FR_EP + j] = epoch + 1;
    if (tid == 0) Q.flags[FJ + j * 32 + FJ_EP + rb] = epoch + 1;
  }
}

typedef CUresult (*EncodeFn)(CUtensorMap*, CUtensorMapDataType, cuuint32_t, void*, const cuuint64_t*, const cuuint64_t*, const cuuint32_t*,
                             const cuuint32_t*, CUtensorMapInterleave, CUtensorMapSwizzle, CUtensorMapL2promotion, CUtensorMapFloatOOBfill);

static void make_map(EncodeFn fn, CUtensorMap* m, const void* ptr, int rank, uint64_t d0, uint64_t d1, uint64_t d2, uint64_t s1, uint64_t s2,
                     uint32_t b0, uint32_t b1, uint32_t b2, CUtensorMapSwizzle swz) {
  cuuint64_t dims[3] = {d0, d1, d2}, strides[2] = {s1, s2};
  cuuint32_t box[3] = {b0, b1, b2}, es[3] = {1, 1, 1};
  fn(m, CU_TENSOR_MAP_DATA_TYPE_BFLOAT16, rank, const_cast<void*>(ptr), dims, strides, box, es, CU_TENSOR_MAP_INTERLEAVE_NONE, swz,
     CU_TENSOR_MAP_L2_PROMOTION_L2_128B, CU_TENSOR_MAP_FLOAT_OOB_FILL_NONE);
}

}

extern "C" void kernel_launch(void* const* d_in, const int* in_sizes, int n_in, void* d_out, int out_size) {
  using namespace mk;
  (void)in_sizes; (void)n_in; (void)out_size;
  static EncodeFn fn = nullptr;
  static Scratch* sc = nullptr;
  if (!fn) {
    cudaDriverEntryPointQueryResult qr;
    cudaGetDriverEntryPoint("cuTensorMapEncodeTiled", (void**)&fn, cudaEnableDefault, &qr);
    cudaGetSymbolAddress((void**)&sc, g_scratch);
    cudaFuncSetAttribute(mega_kernel, cudaFuncAttributeMaxDynamicSharedMemorySize, SM_TOTAL);
  }
  Params p;
  Ptrs a;
  a.x = (const uint8_t*)d_in[0];
  a.wqkv = (const __nv_bfloat16*)d_in[1];
  a.wo = (const __nv_bfloat16*)d_in[2];
  a.w_in = (const __nv_bfloat16*)d_in[4];
  a.w_sp = (const __nv_bfloat16*)d_in[5];
  a.b_sp = (const __nv_bfloat16*)d_in[6];
  a.out = (uint8_t*)d_out;
  a.zero = 0;
  a.WQ = sc->WQ; a.flags = sc->flags; a.CSP = sc->CSP; a.XST = sc->XST; a.HALO = sc->HALO; a.ST1 = sc->ST1; a.ZST = sc->ZST; a.RT = sc->RT; a.Z = sc->Z; a.WO = sc->WO;
  make_map(fn, &p.wsp, a.w_sp, 3, 2048, 1024, 2, 8192, 4096, 64, 64, 2, CU_TENSOR_MAP_SWIZZLE_128B);
  for (int i = 0; i < 2; i++) {
    make_map(fn, &p.act[i], i ? a.out : a.x, 3, DM, 1024, 2, 2304, 1152, 64, 32, 2, CU_TENSOR_MAP_SWIZZLE_128B);
    make_map(fn, &p.res[i], i ? a.out : a.x, 3, DM, 1024, 2, 2304, 1152, 72, 32, 2, CU_TENSOR_MAP_SWIZZLE_NONE);
  }
  for (int i = 0; i < 2; i++) make_map(fn, &p.winb[i], a.w_in + 32 * i, 3, 64, 576, 72 - i, 9216, 128, 64, 16, 3, CU_TENSOR_MAP_SWIZZLE_128B);
  make_map(fn, &p.wins, a.w_in, 3, 64, 576, 72, 9216, 128, 64, 48, 1, CU_TENSOR_MAP_SWIZZLE_128B);
  make_map(fn, &p.wout, d_in[7], 2, 576, 2304, 1, 1152, 0, 64, 144, 1, CU_TENSOR_MAP_SWIZZLE_128B);
  mega_kernel<<<NGRID, 384, SM_TOTAL, cudaStreamPerThread>>>(a, p);
}
```

```cpp
#include <cuda_runtime.h>
#include <cuda.h>
#include <cuda_bf16.h>
#include <stdint.h>

#define MK_TRACE 0
#define MK_DBG 0
#define P5TRACE 0

#define C0S 32.f
#define OFM 0x10u
#define NC2 2
#define LD2 2
#define PDEL 8
#define SDEL 10
#define ZD1 8
#define ZD2 20
#define FD3 14
#define YPACE 2
#define SPL 4
#define XP0 10
#define APACE 7
#define AEP 2
#define PZI 4
#define RFI 3
#define KS 1
#define XK1 1
#define XK2 2
#define HO3 41
#define HO4 41
#define PPK 17
#define NOW 3
#define WTI 12
#define EFM 0x22333022
#define EF(i) ((((EFM >> (4 * (i))) & 3) == 3) || (((EFM >> (4 * (i))) >> L) & 1))

namespace mk {

constexpr int SEQ = 2048, DM = 576, FH = 2304;
constexpr int NCTA = 128;
constexpr int NGRID = 132;
constexpr uint32_t ZB = 36864;
constexpr uint32_t WQ_SL = 72 * 3456;
constexpr uint32_t WO_SL = 72 * 1152;
constexpr float LN_EPS = 1e-5f;
constexpr float GA = 0.3292034911525734f, GB = 2.423681954311584f;

constexpr uint32_t ST_BYTES = 53248, ST_B = 16384, NST = 4;
constexpr uint32_t SM_STG = NST * ST_BYTES;
constexpr uint32_t SM_BAR = SM_STG + 2 * 9216, B_OFF = 896;
constexpr uint32_t SM_OFF = SM_BAR + B_OFF;
constexpr uint32_t SM_TOTAL = SM_BAR + 1024;
constexpr uint32_t SM_RT = SM_STG + 9216, SM_CV = SM_STG + 17408, SM_WT = SM_STG;
constexpr uint32_t SM_WOI = 44032, SM_CSQ = 49280, SM_XST = 50176;
enum { EV_PT = 0, EV_O = 1, EV_X1 = 2, EV_ZN = 3, EV_Z1 = 4, EV_XS = 5, EV_N = 6 };
constexpr uint32_t B_FULL = 0, B_FULLA = 32, B_RES = 96, B_WT = 112, B_GATE3 = 128, B_Z1 = 136, B_ZOK = 144, B_CV = 152, B_XRW = 168, B_F3 = 184, B_WF = 232, B_OF = 240,
                   B_RT = 320, B_AF3 = 352, B_RB = 544,
                   B_AD = 576, B_S5 = 608, B_AV = 616, B_CSQ = 760,
                   B_HOLD = 768, B_X3 = 776, B_ZS = 784, B_EVT = 800,
                   B_IMG = 912, B_WOI = 920, B_E3 = 928, B_XD = 976,
                   B_EMPTY = 992;
constexpr uint32_t SM_B3 = 9 * 16384, SM_ZP3 = SM_STG + 8192;

enum { FR_X2 = 0, FR_O = 1, FR_XR = 5, FR_OL = 7, FR_PZ = 9, FR_EP = 16, FJ = 32 * 32, FJ_WQ = 0, FJ_WO = 1, FJ_ZN = 3, FJ_P4 = 5, FJ_EP = 16, F_N = FJ + 8 * 32 };

struct Scratch {
  alignas(1024) uint32_t flags[F_N];
  alignas(1024) float CSP[2 * NCTA * 216];
  alignas(1024) uint2 RT[SEQ];
  alignas(1024) uint4 XST[2 * SEQ];
  alignas(1024) uint4 ST1[SEQ * 4];
  alignas(1024) uint4 ZST[SEQ * 4];
  alignas(1024) uint4 HALO[32 * 8 * 6 * 32];
  alignas(1024) uint8_t WO[8 * WO_SL];
  alignas(1024) uint8_t WQ[8 * WQ_SL];
  alignas(1024) uint8_t Z[512 * ZB];
};
__device__ Scratch g_scratch;

struct Ptrs {
  const __nv_bfloat16* wqkv;
  uint8_t* WQ;
  uint32_t* flags;
  float* CSP;
  const uint8_t* x;
  uint32_t zero;
  uint4 *XST, *HALO, *ST1, *ZST;
  uint2* RT;
  uint8_t *Z, *WO, *out;
  const __nv_bfloat16 *wo, *w_in, *w_sp, *b_sp;
};
struct Params {
  CUtensorMap wsp, winb[2], wins, wout;
  CUtensorMap act[2];
  CUtensorMap res[2];
};

__device__ __forceinline__ uint32_t smem_u32(const void* p) { return (uint32_t)__cvta_generic_to_shared(p); }
__device__ __forceinline__ void mbar_init(uint32_t bar, uint32_t cnt) { asm volatile("mbarrier.init.shared::cta.b64 [%0], %1;" ::"r"(bar), "r"(cnt)); }
__device__ __forceinline__ void mbar_arrive(uint32_t bar) { asm volatile("mbarrier.arrive.shared::cta.b64 _, [%0];" ::"r"(bar) : "memory"); }
__device__ __forceinline__ void mbar_wait(uint32_t bar, uint32_t parity) {
  asm volatile(
      "{\n.reg .pred p;\n.reg .u32 c;\nmov.u32 c, 0;\nLAB_WAIT:\n"
      "mbarrier.try_wait.parity.shared::cta.b64 p, [%0], %1;\n@p bra LAB_DONE;\n"
      "add.u32 c, c, 1;\nsetp.lt.u32 p, c, 0x100000;\n@p bra LAB_WAIT;\ntrap;\nLAB_DONE:\n}" ::"r"(bar), "r"(parity)
      : "memory");
}
__device__ __forceinline__ void mbar_wait_c(uint32_t bar, uint32_t parity) {
  asm volatile("{\n.reg .pred p;\nLAB_WAIT:\nmbarrier.try_wait.parity.shared::cta.b64 p, [%0], %1;\n@!p bra LAB_WAIT;\n}" ::"r"(bar), "r"(parity) : "memory");
}
__device__ __forceinline__ void flag_wait(const uint32_t* f, uint32_t target) {
  asm volatile(
      "{\n.reg .pred p;\n.reg .u32 c, v;\nmov.u32 c, 0;\nLAB_WAIT:\n"
      "ld.relaxed.gpu.global.u32 v, [%0];\nsub.u32 v, v, %1;\nsetp.ge.s32 p, v, 0;\n@p bra LAB_DONE;\n"
      "add.u32 c, c, 1;\nsetp.lt.u32 p, c, 0x400000;\n@p bra LAB_WAIT;\ntrap;\nLAB_DONE:\nfence.acquire.gpu;\n}" ::"l"(f), "r"(target)
      : "memory");
}
__device__ __forceinline__ void fence_gpu() { asm volatile("fence.acq_rel.gpu;" ::: "memory"); }
__device__ __forceinline__ void fence_async_g() { asm volatile("fence.proxy.async.global;" ::: "memory"); }
__device__ __forceinline__ void fence_async_s() { asm volatile("fence.proxy.async.shared::cta;" ::: "memory"); }
__device__ __forceinline__ uint32_t elect_one() {
  uint32_t p; asm volatile("{\n.reg .pred P;\nelect.sync _|P, 0xffffffff;\nselp.u32 %0, 1, 0, P;\n}" : "=r"(p)); return p;
}
__device__ __forceinline__ void expect_tx_p(uint32_t el, uint32_t bar, uint32_t bytes) {
  asm volatile("{\n.reg .pred P;\nsetp.ne.u32 P, %2, 0;\n@P mbarrier.arrive.expect_tx.shared::cta.b64 _, [%0], %1;\n}" ::"r"(bar), "r"(bytes), "r"(el) : "memory");
}
__device__ __forceinline__ void bulk_load_p(uint32_t el, uint32_t dst, const void* src, uint32_t bytes, uint32_t bar) {
  asm volatile("{\n.reg .pred P;\nsetp.ne.u32 P, %4, 0;\n@P cp.async.bulk.shared::cluster.global.mbarrier::complete_tx::bytes [%0], [%1], %2, [%3];\n}" ::"r"(dst), "l"(src), "r"(bytes), "r"(bar), "r"(el) : "memory");
}
__device__ __forceinline__ uint64_t policy_evict_first() { uint64_t p; asm("createpolicy.fractional.L2::evict_first.b64 %0, 1.0;" : "=l"(p)); return p; }
__device__ __forceinline__ void bulk_load_h(uint32_t el, uint32_t dst, const void* src, uint32_t bytes, uint32_t bar, bool ef, uint64_t pol) {
  if (ef) {
    asm volatile("{\n.reg .pred P;\nsetp.ne.u32 P, %4, 0;\n@P cp.async.bulk.shared::cluster.global.mbarrier::complete_tx::bytes.L2::cache_hint [%0], [%1], %2, [%3], %5;\n}" ::"r"(dst), "l"(src), "r"(bytes), "r"(bar), "r"(el), "l"(pol) : "memory");
  } else {
    asm volatile("{\n.reg .pred P;\nsetp.ne.u32 P, %4, 0;\n@P cp.async.bulk.shared::cluster.global.mbarrier::complete_tx::bytes [%0], [%1], %2, [%3];\n}" ::"r"(dst), "l"(src), "r"(bytes), "r"(bar), "r"(el) : "memory");
  }
}
__device__ __forceinline__ void bulk_mc_h(uint32_t el, uint32_t dst, const void* src, uint32_t bytes, uint32_t bar, bool ef, uint64_t pol) {
  if (ef) {
    asm volatile("{\n.reg .pred P;\nsetp.ne.u32 P, %4, 0;\n@P cp.async.bulk.shared::cluster.global.mbarrier::complete_tx::bytes.multicast::cluster.L2::cache_hint [%0], [%1], %2, [%3], %5, %6;\n}" ::"r"(dst), "l"(src), "r"(bytes), "r"(bar), "r"(el), "h"((uint16_t)3), "l"(pol) : "memory");
  } else {
    asm volatile("{\n.reg .pred P;\nsetp.ne.u32 P, %4, 0;\n@P cp.async.bulk.shared::cluster.global.mbarrier::complete_tx::bytes.multicast::cluster [%0], [%1], %2, [%3], %5;\n}" ::"r"(dst), "l"(src), "r"(bytes), "r"(bar), "r"(el), "h"((uint16_t)3) : "memory");
  }
}
__device__ __forceinline__ void tma3d_h(uint32_t el, uint32_t dst, const CUtensorMap* m, int c0, int c1, int c2, uint32_t bar, bool ef, uint64_t pol) {
  if (ef) {
    asm volatile("{\n.reg .pred P;\nsetp.ne.u32 P, %6, 0;\n@P cp.async.bulk.tensor.3d.shared::cluster.global.mbarrier::complete_tx::bytes.L2::cache_hint [%0], [%1, {%3, %4, %5}], [%2], %7;\n}" ::"r"(dst), "l"(m), "r"(bar), "r"(c0), "r"(c1), "r"(c2), "r"(el), "l"(pol) : "memory");
  } else {
    asm volatile("{\n.reg .pred P;\nsetp.ne.u32 P, %6, 0;\n@P cp.async.bulk.tensor.3d.shared::cluster.global.mbarrier::complete_tx::bytes [%0], [%1, {%3, %4, %5}], [%2];\n}" ::"r"(dst), "l"(m), "r"(bar), "r"(c0), "r"(c1), "r"(c2), "r"(el) : "memory");
  }
}
__device__ __forceinline__ void tma2d_mc_h(uint32_t el, uint32_t dst, const CUtensorMap* m, int c0, int c1, uint32_t bar, bool ef, uint64_t pol) {
  if (ef) {
    asm volatile("{\n.reg .pred P;\nsetp.ne.u32 P, %5, 0;\n@P cp.async.bulk.tensor.2d.shared::cluster.global.mbarrier::complete_tx::bytes.multicast::cluster.L2::cache_hint [%0], [%1, {%3, %4}], [%2], %6, %7;\n}" ::"r"(dst), "l"(m), "r"(bar), "r"(c0), "r"(c1), "r"(el), "h"((uint16_t)3), "l"(pol) : "memory");
  } else {
    asm volatile("{\n.reg .pred P;\nsetp.ne.u32 P, %5, 0;\n@P cp.async.bulk.tensor.2d.shared::cluster.global.mbarrier::complete_tx::bytes.multicast::cluster [%0], [%1, {%3, %4}], [%2], %6;\n}" ::"r"(dst), "l"(m), "r"(bar), "r"(c0), "r"(c1), "r"(el), "h"((uint16_t)3) : "memory");
  }
}
__device__ __forceinline__ void tma3d_mc_h(uint32_t el, uint32_t dst, const CUtensorMap* m, int c0, int c1, int c2, uint32_t bar, bool ef, uint64_t pol) {
  if (ef) {
    asm volatile("{\n.reg .pred P;\nsetp.ne.u32 P, %6, 0;\n@P cp.async.bulk.tensor.3d.shared::cluster.global.mbarrier::complete_tx::bytes.multicast::cluster.L2::cache_hint [%0], [%1, {%3, %4, %5}], [%2], %7, %8;\n}" ::"r"(dst), "l"(m), "r"(bar), "r"(c0), "r"(c1), "r"(c2), "r"(el), "h"((uint16_t)3), "l"(pol) : "memory");
  } else {
    asm volatile("{\n.reg .pred P;\nsetp.ne.u32 P, %6, 0;\n@P cp.async.bulk.tensor.3d.shared::cluster.global.mbarrier::complete_tx::bytes.multicast::cluster [%0], [%1, {%3, %4, %5}], [%2], %7;\n}" ::"r"(dst), "l"(m), "r"(bar), "r"(c0), "r"(c1), "r"(c2), "r"(el), "h"((uint16_t)3) : "memory");
  }
}
__device__ __forceinline__ void mbar_arrive_cluster(uint32_t addr) { asm volatile("mbarrier.arrive.shared::cluster.b64 _, [%0];" ::"r"(addr) : "memory"); }
__device__ __forceinline__ uint32_t mapa(uint32_t addr, uint32_t rank) { uint32_t r; asm("mapa.shared::cluster.u32 %0, %1, %2;" : "=r"(r) : "r"(addr), "r"(rank)); return r; }
__device__ __forceinline__ void bulk_store_p(uint32_t el, void* dst, uint32_t src, uint32_t bytes) {
  asm volatile("{\n.reg .pred P;\nsetp.ne.u32 P, %3, 0;\n@P cp.async.bulk.global.shared::cta.bulk_group [%0], [%1], %2;\n}" ::"l"(dst), "r"(src), "r"(bytes), "r"(el) : "memory");
}
__device__ __forceinline__ void flag_release_p(uint32_t el, uint32_t* f) {
  asm volatile("{\n.reg .pred P;\nsetp.ne.u32 P, %1, 0;\nfence.proxy.async;\n@P red.relaxed.gpu.global.add.u32 [%0], 1;\n}" ::"l"(f), "r"(el) : "memory");
}
__device__ __forceinline__ void flag_add_p(uint32_t el, uint32_t* f) {
  asm volatile("{\n.reg .pred P;\nsetp.ne.u32 P, %1, 0;\n@P red.relaxed.gpu.global.add.u32 [%0], 1;\n}" ::"l"(f), "r"(el) : "memory");
}
__device__ __forceinline__ void prefetch_l2(const void* src, uint32_t bytes) { asm volatile("cp.async.bulk.prefetch.L2.global [%0], %1;" ::"l"(src), "r"(bytes) : "memory"); }
__device__ __forceinline__ void prefetch_map(const CUtensorMap* m) { asm volatile("prefetch.tensormap [%0];" ::"l"(m) : "memory"); }
__device__ __forceinline__ void wgmma_fence() { asm volatile("wgmma.fence.sync.aligned;" ::: "memory"); }
__device__ __forceinline__ void wgmma_commit() { asm volatile("wgmma.commit_group.sync.aligned;" ::: "memory"); }
template <int N> __device__ __forceinline__ void wgmma_wait() { asm volatile("wgmma.wait_group.sync.aligned %0;" ::"n"(N) : "memory"); }
__device__ __forceinline__ uint32_t dlo(uint32_t addr, uint32_t lbo) { return ((addr & 0x3FFFF) >> 4) + ((lbo >> 4) << 16); }
template <uint32_t SBO, uint32_t SWZ> __device__ __forceinline__ uint64_t dsc(uint32_t lo, uint32_t off) {
  uint64_t d; asm("mov.b64 %0, {%1, %2};" : "=l"(d) : "r"(lo + (off >> 4)), "n"((SBO >> 4) | (SWZ << 30))); return d;
}
template <int R> __device__ __forceinline__ void reg_alloc() { asm volatile("setmaxnreg.inc.sync.aligned.u32 %0;" ::"n"(R)); }
template <int R> __device__ __forceinline__ void reg_dealloc() { asm volatile("setmaxnreg.dec.sync.aligned.u32 %0;" ::"n"(R)); }
__device__ __forceinline__ void bar_sync(int id, int n) { asm volatile("bar.sync %0, %1;" ::"r"(id), "r"(n) : "memory"); }
__device__ __forceinline__ void bar_arrive(int id, int n) { asm volatile("bar.arrive %0, %1;" ::"r"(id), "r"(n) : "memory"); }
__device__ __forceinline__ void ldsm4(uint32_t* r, uint32_t addr) {
  asm volatile("ldmatrix.sync.aligned.m8n8.x4.shared.b16 {%0,%1,%2,%3}, [%4];" : "=r"(r[0]), "=r"(r[1]), "=r"(r[2]), "=r"(r[3]) : "r"(addr) : "memory");
}
__device__ __forceinline__ uint32_t movm(uint32_t a) { uint32_t d; asm volatile("movmatrix.sync.aligned.m8n8.trans.b16 %0, %1;" : "=r"(d) : "r"(a)); return d; }
__device__ __forceinline__ void mma16(float* c, uint32_t a0, uint32_t a1, uint32_t a2, uint32_t a3, uint32_t b0, uint32_t b1) {
  asm volatile("mma.sync.aligned.m16n8k16.row.col.f32.bf16.bf16.f32 {%0,%1,%2,%3}, {%4,%5,%6,%7}, {%8,%9}, {%0,%1,%2,%3};"
               : "+f"(c[0]), "+f"(c[1]), "+f"(c[2]), "+f"(c[3]) : "r"(a0), "r"(a1), "r"(a2), "r"(a3), "r"(b0), "r"(b1));
}
__device__ __forceinline__ void mma8(float* c, uint32_t a0, uint32_t a1, uint32_t b0) {
  asm volatile("mma.sync.aligned.m16n8k8.row.col.f32.bf16.bf16.f32 {%0,%1,%2,%3}, {%4,%5}, {%6}, {%0,%1,%2,%3};"
               : "+f"(c[0]), "+f"(c[1]), "+f"(c[2]), "+f"(c[3]) : "r"(a0), "r"(a1), "r"(b0));
}
__device__ __forceinline__ uint32_t pack2(float lo, float hi) { uint32_t r; asm("cvt.rn.bf16x2.f32 %0, %1, %2;" : "=r"(r) : "f"(hi), "f"(lo)); return r; }
__device__ __forceinline__ float blo(uint32_t v) { return __uint_as_float(v << 16); }
__device__ __forceinline__ float bhi(uint32_t v) { return __uint_as_float(v & 0xffff0000u); }
__device__ __forceinline__ float tanh_fast(float x) { float y; asm("tanh.approx.f32 %0, %1;" : "=f"(y) : "f"(x)); return y; }
__device__ __forceinline__ float rcp_fast(float x) { float y; asm("rcp.approx.ftz.f32 %0, %1;" : "=f"(y) : "f"(x)); return y; }
__device__ __forceinline__ float rsq_fast(float x) { float y; asm("rsqrt.approx.ftz.f32 %0, %1;" : "=f"(y) : "f"(x)); return y; }
__device__ __forceinline__ float ex2(float x) { float y; asm("ex2.approx.ftz.f32 %0, %1;" : "=f"(y) : "f"(x)); return y; }
__device__ __forceinline__ float qsum(float v) { v += __shfl_xor_sync(~0u, v, 1); v += __shfl_xor_sync(~0u, v, 2); return v; }
__device__ __forceinline__ float qmax(float v) { v = fmaxf(v, __shfl_xor_sync(~0u, v, 1)); v = fmaxf(v, __shfl_xor_sync(~0u, v, 2)); return v; }
__device__ __forceinline__ void stg32(void* p, uint32_t v) { asm volatile("st.global.u32 [%0], %1;" ::"l"(p), "r"(v) : "memory"); }
__device__ __forceinline__ void stg128(void* p, uint32_t a, uint32_t b, uint32_t c, uint32_t d) { asm volatile("st.global.v4.u32 [%0], {%1,%2,%3,%4};" ::"l"(p), "r"(a), "r"(b), "r"(c), "r"(d) : "memory"); }
__device__ __forceinline__ uint32_t ldcg32(const void* p) { uint32_t v; asm volatile("ld.global.L1::no_allocate.u32 %0, [%1];" : "=r"(v) : "l"(p) : "memory"); return v; }
__device__ __forceinline__ void stg128_if(bool c, void* p, uint32_t a, uint32_t b, uint32_t cc, uint32_t d) {
  asm volatile("{\n.reg .pred P;\nsetp.ne.u32 P, %5, 0;\n@P st.global.v4.u32 [%0], {%1,%2,%3,%4};\n}" ::"l"(p), "r"(a), "r"(b), "r"(cc), "r"(d), "r"((uint32_t)c) : "memory");
}
__device__ __forceinline__ uint2 lds64(uint32_t a) { uint2 v; asm volatile("ld.shared.v2.u32 {%0,%1}, [%2];" : "=r"(v.x), "=r"(v.y) : "r"(a) : "memory"); return v; }
__device__ __forceinline__ uint32_t ldnc16(const void* p) { uint16_t v; asm volatile("ld.global.nc.u16 %0, [%1];" : "=h"(v) : "l"(p)); return v; }
__device__ __forceinline__ uint4 ldnc128(const void* p) { uint4 v; asm volatile("ld.global.nc.v4.u32 {%0,%1,%2,%3}, [%4];" : "=r"(v.x), "=r"(v.y), "=r"(v.z), "=r"(v.w) : "l"(p)); return v; }
__device__ __forceinline__ void cp_async16(uint32_t dst, const void* src) { asm volatile("cp.async.cg.shared.global [%0], [%1], 16;" ::"r"(dst), "l"(src) : "memory"); }
__device__ __forceinline__ uint32_t hsub2(uint32_t a, uint32_t b) { uint32_t d; asm("sub.rn.bf16x2 %0, %1, %2;" : "=r"(d) : "r"(a), "r"(b)); return d; }
__device__ __forceinline__ void stg32_if(bool c, void* p, uint32_t v) {
  asm volatile("{\n.reg .pred P;\nsetp.ne.u32 P, %2, 0;\n@P st.global.u32 [%0], %1;\n}" ::"l"(p), "r"(v), "r"((uint32_t)c) : "memory");
}
__device__ __forceinline__ float wsum(float v) { for (int o = 16; o; o >>= 1) v += __shfl_xor_sync(~0u, v, o); return v; }
__device__ __forceinline__ uint32_t hmul2(uint32_t a, uint32_t b) { uint32_t d; asm("mul.rn.bf16x2 %0, %1, %2;" : "=r"(d) : "r"(a), "r"(b)); return d; }
__device__ __forceinline__ void sts32(uint32_t a, uint32_t v) { asm volatile("st.shared.u32 [%0], %1;" ::"r"(a), "r"(v) : "memory"); }
__device__ __forceinline__ uint32_t lds32(uint32_t a) { uint32_t v; asm volatile("ld.shared.u32 %0, [%1];" : "=r"(v) : "r"(a) : "memory"); return v; }
__device__ __forceinline__ void sts128(uint32_t a, uint32_t x, uint32_t y, uint32_t z, uint32_t w) { asm volatile("st.shared.v4.u32 [%0], {%1,%2,%3,%4};" ::"r"(a), "r"(x), "r"(y), "r"(z), "r"(w) : "memory"); }
__device__ __forceinline__ uint4 lds128(uint32_t a) { uint4 v; asm volatile("ld.shared.v4.u32 {%0,%1,%2,%3}, [%4];" : "=r"(v.x), "=r"(v.y), "=r"(v.z), "=r"(v.w) : "r"(a) : "memory"); return v; }
__device__ __forceinline__ void ll_st64(uint2* p, uint32_t v, uint32_t tag) {
  asm volatile("{\n.reg .b64 r;\nmov.b64 r, {%1,%2};\nst.relaxed.gpu.global.b64 [%0], r;\n}" ::"l"(p), "r"(v), "r"(tag) : "memory");
}
__device__ __forceinline__ uint2 ll_ld64(const uint2* p) {
  uint2 v; asm volatile("{\n.reg .b64 r;\nld.relaxed.gpu.global.b64 r, [%2];\nmov.b64 {%0,%1}, r;\n}" : "=r"(v.x), "=r"(v.y) : "l"(p) : "memory"); return v;
}
__device__ __forceinline__ void ll_st128(uint4* p, float a, float b, uint32_t tag, float c = 0.f) {
  asm volatile("{\n.reg .b128 r;\n.reg .b64 lo, hi;\nmov.b64 lo, {%1,%2};\nmov.b64 hi, {%3,%4};\nmov.b128 r, {lo, hi};\nst.relaxed.gpu.global.b128 [%0], r;\n}" ::"l"(p), "r"(__float_as_uint(a)), "r"(__float_as_uint(b)), "r"(tag), "r"(__float_as_uint(c)) : "memory");
}
__device__ __forceinline__ uint4 ll_ld128g(const void* p) {
  uint4 v; asm volatile("{\n.reg .b128 r;\n.reg .b64 lo, hi;\nld.relaxed.gpu.b128 r, [%4];\nmov.b128 {lo, hi}, r;\nmov.b64 {%0,%1}, lo;\nmov.b64 {%2,%3}, hi;\n}" : "=r"(v.x), "=r"(v.y), "=r"(v.z), "=r"(v.w) : "l"(p) : "memory"); return v;
}
__device__ __forceinline__ uint4 ll_ld128(const uint4* p) {
  uint4 v; asm volatile("{\n.reg .b128 r;\n.reg .b64 lo, hi;\nld.relaxed.gpu.global.b128 r, [%4];\nmov.b128 {lo, hi}, r;\nmov.b64 {%0,%1}, lo;\nmov.b64 {%2,%3}, hi;\n}" : "=r"(v.x), "=r"(v.y), "=r"(v.z), "=r"(v.w) : "l"(p) : "memory"); return v;
}
__device__ __forceinline__ void publish_p(uint32_t el, uint32_t* f) {
  asm volatile("{\n.reg .pred P;\nsetp.ne.u32 P, %1, 0;\n@P cp.async.bulk.commit_group;\n@P cp.async.bulk.wait_group 0;\n@P red.release.gpu.global.add.u32 [%0], 1;\n}" ::"l"(f), "r"(el) : "memory");
}
__device__ __forceinline__ void stsm4(uint32_t addr, uint32_t a, uint32_t b, uint32_t c, uint32_t d) {
  asm volatile("stmatrix.sync.aligned.m8n8.x4.shared.b16 [%0], {%1,%2,%3,%4};" ::"r"(addr), "r"(a), "r"(b), "r"(c), "r"(d) : "memory");
}
__device__ __forceinline__ void sts64(uint32_t a, uint32_t x, uint32_t y) { asm volatile("st.shared.v2.u32 [%0], {%1,%2};" ::"r"(a), "r"(x), "r"(y) : "memory"); }
__device__ __forceinline__ void ll_st128_if(bool on, uint4* p, float a, float b, uint32_t tag) {
  asm volatile("{\n.reg .pred P;\n.reg .b128 r;\n.reg .b64 lo, hi;\nsetp.ne.u32 P, %4, 0;\nmov.b64 lo, {%1,%2};\nmov.b64 hi, {%3,%3};\nmov.b128 r, {lo, hi};\n@P st.relaxed.gpu.global.b128 [%0], r;\n}" ::"l"(p), "r"(__float_as_uint(a)), "r"(__float_as_uint(b)), "r"(tag), "r"((uint32_t)on) : "memory");
}
__device__ __forceinline__ uint4 ldnc128_if(bool c, const void* p) {
  uint4 v = make_uint4(0u, 0u, 0u, 0u);
  asm volatile("{\n.reg .pred P;\nsetp.ne.u32 P, %5, 0;\n@P ld.global.nc.v4.u32 {%0,%1,%2,%3}, [%4];\n}" : "+r"(v.x), "+r"(v.y), "+r"(v.z), "+r"(v.w) : "l"(p), "r"((uint32_t)c));
  return v;
}
__device__ __forceinline__ float2 lds64f(uint32_t a) { float2 v; asm volatile("ld.shared.v2.f32 {%0,%1}, [%2];" : "=f"(v.x), "=f"(v.y) : "r"(a) : "memory"); return v; }
#define TRC(cond, role, idx) do {} while (0)
#define TRV(role, idx, v) do {} while (0)
#define TRVI(c, role, idx, v) do {} while (0)

#define ACLK_INIT do {} while (0)
#define ACLK(i) do {} while (0)
#define ACLK_OUT do {} while (0)
#define RCLK(i) do {} while (0)
#define RCLK_INIT do {} while (0)
#define RCLK_OUT do {} while (0)
#define SCLK(i) do {} while (0)
#define SCLK2(i) do {} while (0)
#define SCLK3(i) do {} while (0)
#define PL 1
#define PCLK(i) do {} while (0)
#define PQ 1
#define CLK_INIT do {} while (0)
#define CLK(i) do {} while (0)
#define CLK_OUT do {} while (0)

__device__ __forceinline__ void wgmma_ss_n216(float* d, uint64_t da, uint64_t db, int scaleD) {
  asm volatile("{\n.reg .pred p;\nsetp.ne.b32 p, %110, 0;\nwgmma.mma_async.sync.aligned.m64n216k16.f32.bf16.bf16 "
    "{%0,%1,%2,%3,%4,%5,%6,%7,%8,%9,%10,%11,%12,%13,%14,%15,%16,%17,%18,%19,%20,%21,%22,%23,%24,%25,%26,%27,%28,%29,%30,%31,%32,%33,%34,%35,%36,%37,%38,%39,%40,%41,%42,%43,%44,%45,%46,%47,%48,%49,%50,%51,%52,%53,%54,%55,%56,%57,%58,%59,%60,%61,%62,%63,%64,%65,%66,%67,%68,%69,%70,%71,%72,%73,%74,%75,%76,%77,%78,%79,%80,%81,%82,%83,%84,%85,%86,%87,%88,%89,%90,%91,%92,%93,%94,%95,%96,%97,%98,%99,%100,%101,%102,%103,%104,%105,%106,%107}, "
    "%108, %109, p, 1, 1, 0, 1;\n}\n"
    : "+f"(d[0]), "+f"(d[1]), "+f"(d[2]), "+f"(d[3]), "+f"(d[4]), "+f"(d[5]), "+f"(d[6]), "+f"(d[7]), "+f"(d[8]), "+f"(d[9]), "+f"(d[10]), "+f"(d[11]), "+f"(d[12]), "+f"(d[13]), "+f"(d[14]), "+f"(d[15]), "+f"(d[16]), "+f"(d[17]), "+f"(d[18]), "+f"(d[19]), "+f"(d[20]), "+f"(d[21]), "+f"(d[22]), "+f"(d[23]), "+f"(d[24]), "+f"(d[25]), "+f"(d[26]), "+f"(d[27]), "+f"(d[28]), "+f"(d[29]), "+f"(d[30]), "+f"(d[31]), "+f"(d[32]), "+f"(d[33]), "+f"(d[34]), "+f"(d[35]), "+f"(d[36]), "+f"(d[37]), "+f"(d[38]), "+f"(d[39]), "+f"(d[40]), "+f"(d[41]), "+f"(d[42]), "+f"(d[43]), "+f"(d[44]), "+f"(d[45]), "+f"(d[46]), "+f"(d[47]), "+f"(d[48]), "+f"(d[49]), "+f"(d[50]), "+f"(d[51]), "+f"(d[52]), "+f"(d[53]), "+f"(d[54]), "+f"(d[55]), "+f"(d[56]), "+f"(d[57]), "+f"(d[58]), "+f"(d[59]), "+f"(d[60]), "+f"(d[61]), "+f"(d[62]), "+f"(d[63]), "+f"(d[64]), "+f"(d[65]), "+f"(d[66]), "+f"(d[67]), "+f"(d[68]), "+f"(d[69]), "+f"(d[70]), "+f"(d[71]), "+f"(d[72]), "+f"(d[73]), "+f"(d[74]), "+f"(d[75]), "+f"(d[76]), "+f"(d[77]), "+f"(d[78]), "+f"(d[79]), "+f"(d[80]), "+f"(d[81]), "+f"(d[82]), "+f"(d[83]), "+f"(d[84]), "+f"(d[85]), "+f"(d[86]), "+f"(d[87]), "+f"(d[88]), "+f"(d[89]), "+f"(d[90]), "+f"(d[91]), "+f"(d[92]), "+f"(d[93]), "+f"(d[94]), "+f"(d[95]), "+f"(d[96]), "+f"(d[97]), "+f"(d[98]), "+f"(d[99]), "+f"(d[100]), "+f"(d[101]), "+f"(d[102]), "+f"(d[103]), "+f"(d[104]), "+f"(d[105]), "+f"(d[106]), "+f"(d[107])
    : "l"(da), "l"(db), "r"(scaleD));
}
__device__ __forceinline__ void wgmma_ss_n72(float* d, uint64_t da, uint64_t db, int scaleD) {
  asm volatile("{\n.reg .pred p;\nsetp.ne.b32 p, %38, 0;\nwgmma.mma_async.sync.aligned.m64n72k16.f32.bf16.bf16 "
    "{%0,%1,%2,%3,%4,%5,%6,%7,%8,%9,%10,%11,%12,%13,%14,%15,%16,%17,%18,%19,%20,%21,%22,%23,%24,%25,%26,%27,%28,%29,%30,%31,%32,%33,%34,%35}, "
    "%36, %37, p, 1, 1, 0, 1;\n}\n"
    : "+f"(d[0]), "+f"(d[1]), "+f"(d[2]), "+f"(d[3]), "+f"(d[4]), "+f"(d[5]), "+f"(d[6]), "+f"(d[7]), "+f"(d[8]), "+f"(d[9]), "+f"(d[10]), "+f"(d[11]), "+f"(d[12]), "+f"(d[13]), "+f"(d[14]), "+f"(d[15]), "+f"(d[16]), "+f"(d[17]), "+f"(d[18]), "+f"(d[19]), "+f"(d[20]), "+f"(d[21]), "+f"(d[22]), "+f"(d[23]), "+f"(d[24]), "+f"(d[25]), "+f"(d[26]), "+f"(d[27]), "+f"(d[28]), "+f"(d[29]), "+f"(d[30]), "+f"(d[31]), "+f"(d[32]), "+f"(d[33]), "+f"(d[34]), "+f"(d[35])
    : "l"(da), "l"(db), "r"(scaleD));
}
__device__ __forceinline__ void wgmma_ss_n128(float* d, uint64_t da, uint64_t db, int scaleD) {
  asm volatile("{\n.reg .pred p;\nsetp.ne.b32 p, %66, 0;\nwgmma.mma_async.sync.aligned.m64n128k16.f32.bf16.bf16 "
    "{%0,%1,%2,%3,%4,%5,%6,%7,%8,%9,%10,%11,%12,%13,%14,%15,%16,%17,%18,%19,%20,%21,%22,%23,%24,%25,%26,%27,%28,%29,%30,%31,%32,%33,%34,%35,%36,%37,%38,%39,%40,%41,%42,%43,%44,%45,%46,%47,%48,%49,%50,%51,%52,%53,%54,%55,%56,%57,%58,%59,%60,%61,%62,%63}, "
    "%64, %65, p, 1, 1, 0, 1;\n}\n"
    : "+f"(d[0]), "+f"(d[1]), "+f"(d[2]), "+f"(d[3]), "+f"(d[4]), "+f"(d[5]), "+f"(d[6]), "+f"(d[7]), "+f"(d[8]), "+f"(d[9]), "+f"(d[10]), "+f"(d[11]), "+f"(d[12]), "+f"(d[13]), "+f"(d[14]), "+f"(d[15]), "+f"(d[16]), "+f"(d[17]), "+f"(d[18]), "+f"(d[19]), "+f"(d[20]), "+f"(d[21]), "+f"(d[22]), "+f"(d[23]), "+f"(d[24]), "+f"(d[25]), "+f"(d[26]), "+f"(d[27]), "+f"(d[28]), "+f"(d[29]), "+f"(d[30]), "+f"(d[31]), "+f"(d[32]), "+f"(d[33]), "+f"(d[34]), "+f"(d[35]), "+f"(d[36]), "+f"(d[37]), "+f"(d[38]), "+f"(d[39]), "+f"(d[40]), "+f"(d[41]), "+f"(d[42]), "+f"(d[43]), "+f"(d[44]), "+f"(d[45]), "+f"(d[46]), "+f"(d[47]), "+f"(d[48]), "+f"(d[49]), "+f"(d[50]), "+f"(d[51]), "+f"(d[52]), "+f"(d[53]), "+f"(d[54]), "+f"(d[55]), "+f"(d[56]), "+f"(d[57]), "+f"(d[58]), "+f"(d[59]), "+f"(d[60]), "+f"(d[61]), "+f"(d[62]), "+f"(d[63])
    : "l"(da), "l"(db), "r"(scaleD));
}
__device__ __forceinline__ void wgmma_ss_n160(float* d, uint64_t da, uint64_t db, int scaleD) {
  asm volatile("{\n.reg .pred p;\nsetp.ne.b32 p, %82, 0;\nwgmma.mma_async.sync.aligned.m64n160k16.f32.bf16.bf16 "
    "{%0,%1,%2,%3,%4,%5,%6,%7,%8,%9,%10,%11,%12,%13,%14,%15,%16,%17,%18,%19,%20,%21,%22,%23,%24,%25,%26,%27,%28,%29,%30,%31,%32,%33,%34,%35,%36,%37,%38,%39,%40,%41,%42,%43,%44,%45,%46,%47,%48,%49,%50,%51,%52,%53,%54,%55,%56,%57,%58,%59,%60,%61,%62,%63,%64,%65,%66,%67,%68,%69,%70,%71,%72,%73,%74,%75,%76,%77,%78,%79}, "
    "%80, %81, p, 1, 1, 0, 1;\n}\n"
    : "+f"(d[0]), "+f"(d[1]), "+f"(d[2]), "+f"(d[3]), "+f"(d[4]), "+f"(d[5]), "+f"(d[6]), "+f"(d[7]), "+f"(d[8]), "+f"(d[9]), "+f"(d[10]), "+f"(d[11]), "+f"(d[12]), "+f"(d[13]), "+f"(d[14]), "+f"(d[15]), "+f"(d[16]), "+f"(d[17]), "+f"(d[18]), "+f"(d[19]), "+f"(d[20]), "+f"(d[21]), "+f"(d[22]), "+f"(d[23]), "+f"(d[24]), "+f"(d[25]), "+f"(d[26]), "+f"(d[27]), "+f"(d[28]), "+f"(d[29]), "+f"(d[30]), "+f"(d[31]), "+f"(d[32]), "+f"(d[33]), "+f"(d[34]), "+f"(d[35]), "+f"(d[36]), "+f"(d[37]), "+f"(d[38]), "+f"(d[39]), "+f"(d[40]), "+f"(d[41]), "+f"(d[42]), "+f"(d[43]), "+f"(d[44]), "+f"(d[45]), "+f"(d[46]), "+f"(d[47]), "+f"(d[48]), "+f"(d[49]), "+f"(d[50]), "+f"(d[51]), "+f"(d[52]), "+f"(d[53]), "+f"(d[54]), "+f"(d[55]), "+f"(d[56]), "+f"(d[57]), "+f"(d[58]), "+f"(d[59]), "+f"(d[60]), "+f"(d[61]), "+f"(d[62]), "+f"(d[63]), "+f"(d[64]), "+f"(d[65]), "+f"(d[66]), "+f"(d[67]), "+f"(d[68]), "+f"(d[69]), "+f"(d[70]), "+f"(d[71]), "+f"(d[72]), "+f"(d[73]), "+f"(d[74]), "+f"(d[75]), "+f"(d[76]), "+f"(d[77]), "+f"(d[78]), "+f"(d[79])
    : "l"(da), "l"(db), "r"(scaleD));
}
__device__ __forceinline__ void wgmma_rs_n144(float* d, const uint32_t* a, uint64_t db, int scaleD) {
  asm volatile("{\n.reg .pred p;\nsetp.ne.b32 p, %77, 0;\nwgmma.mma_async.sync.aligned.m64n144k16.f32.bf16.bf16 "
    "{%0,%1,%2,%3,%4,%5,%6,%7,%8,%9,%10,%11,%12,%13,%14,%15,%16,%17,%18,%19,%20,%21,%22,%23,%24,%25,%26,%27,%28,%29,%30,%31,%32,%33,%34,%35,%36,%37,%38,%39,%40,%41,%42,%43,%44,%45,%46,%47,%48,%49,%50,%51,%52,%53,%54,%55,%56,%57,%58,%59,%60,%61,%62,%63,%64,%65,%66,%67,%68,%69,%70,%71}, "
    "{%72,%73,%74,%75}, %76, p, 1, 1, 1;\n}\n"
    : "+f"(d[0]), "+f"(d[1]), "+f"(d[2]), "+f"(d[3]), "+f"(d[4]), "+f"(d[5]), "+f"(d[6]), "+f"(d[7]), "+f"(d[8]), "+f"(d[9]), "+f"(d[10]), "+f"(d[11]), "+f"(d[12]), "+f"(d[13]), "+f"(d[14]), "+f"(d[15]), "+f"(d[16]), "+f"(d[17]), "+f"(d[18]), "+f"(d[19]), "+f"(d[20]), "+f"(d[21]), "+f"(d[22]), "+f"(d[23]), "+f"(d[24]), "+f"(d[25]), "+f"(d[26]), "+f"(d[27]), "+f"(d[28]), "+f"(d[29]), "+f"(d[30]), "+f"(d[31]), "+f"(d[32]), "+f"(d[33]), "+f"(d[34]), "+f"(d[35]), "+f"(d[36]), "+f"(d[37]), "+f"(d[38]), "+f"(d[39]), "+f"(d[40]), "+f"(d[41]), "+f"(d[42]), "+f"(d[43]), "+f"(d[44]), "+f"(d[45]), "+f"(d[46]), "+f"(d[47]), "+f"(d[48]), "+f"(d[49]), "+f"(d[50]), "+f"(d[51]), "+f"(d[52]), "+f"(d[53]), "+f"(d[54]), "+f"(d[55]), "+f"(d[56]), "+f"(d[57]), "+f"(d[58]), "+f"(d[59]), "+f"(d[60]), "+f"(d[61]), "+f"(d[62]), "+f"(d[63]), "+f"(d[64]), "+f"(d[65]), "+f"(d[66]), "+f"(d[67]), "+f"(d[68]), "+f"(d[69]), "+f"(d[70]), "+f"(d[71])
    : "r"(a[0]), "r"(a[1]), "r"(a[2]), "r"(a[3]), "l"(db), "r"(scaleD));
}
__device__ __forceinline__ void wgmma_rs_n64(float* d, const uint32_t* a, uint64_t db, int scaleD) {
  asm volatile("{\n.reg .pred p;\nsetp.ne.b32 p, %37, 0;\nwgmma.mma_async.sync.aligned.m64n64k16.f32.bf16.bf16 "
    "{%0,%1,%2,%3,%4,%5,%6,%7,%8,%9,%10,%11,%12,%13,%14,%15,%16,%17,%18,%19,%20,%21,%22,%23,%24,%25,%26,%27,%28,%29,%30,%31}, "
    "{%32,%33,%34,%35}, %36, p, 1, 1, 1;\n}\n"
    : "+f"(d[0]), "+f"(d[1]), "+f"(d[2]), "+f"(d[3]), "+f"(d[4]), "+f"(d[5]), "+f"(d[6]), "+f"(d[7]), "+f"(d[8]), "+f"(d[9]), "+f"(d[10]), "+f"(d[11]), "+f"(d[12]), "+f"(d[13]), "+f"(d[14]), "+f"(d[15]), "+f"(d[16]), "+f"(d[17]), "+f"(d[18]), "+f"(d[19]), "+f"(d[20]), "+f"(d[21]), "+f"(d[22]), "+f"(d[23]), "+f"(d[24]), "+f"(d[25]), "+f"(d[26]), "+f"(d[27]), "+f"(d[28]), "+f"(d[29]), "+f"(d[30]), "+f"(d[31])
    : "r"(a[0]), "r"(a[1]), "r"(a[2]), "r"(a[3]), "l"(db), "r"(scaleD));
}

template <int V> struct Int { static constexpr int value = V; };
struct Cur {
  uint32_t s, ph;
  __device__ __forceinline__ void next() { if (++s == NST) { s = 0; ph ^= 1; } }
};

__device__ __forceinline__ uint32_t o_place(uint32_t w, uint32_t e) { return (((w ? 0xd5310u : 0xa8d57u) >> (4 * e)) & 15) * 8192 + 90112; }
#define z1_block(rb, w, j) (Q.Z + ((rb) * 16 + (w) * 8 + (j)) * ZB)
#define xn_block(hw) (Q.Z + ((hw) * 8 + 2) * ZB)
#define z2_block(kb, j) (Q.Z + (256 + (kb) * 8 + (j)) * ZB)
template <int N> __device__ __forceinline__ void pause(uint32_t zero) {
  if (N <= 0) return;
  uint32_t z = clock() + threadIdx.x;
  do {
#pragma unroll (N > 8 ? 1 : 8)
    for (int i = 0; i < N; i++) asm volatile("shfl.sync.bfly.b32 %0, %0, 1, 0x1f, 0xffffffff;" : "+r"(z)::"memory");
  } while (__any_sync(~0u, z & zero));
}

__global__ void __cluster_dims__(2, 1, 1) __launch_bounds__(384, 1) mega_kernel(const Ptrs Q, const __grid_constant__ Params P) {
  extern __shared__ __align__(1024) uint8_t smem_raw[];
  const uint32_t sb = smem_u32(smem_raw);
  const uint32_t bars = sb + SM_BAR;
  const int tid = threadIdx.x;
  int lane = tid & 31;
  const int wid = __shfl_sync(~0u, tid >> 5, 0);
  const int cl = blockIdx.x >> 1;
  const int bid = (cl < 4 ? cl * 8 + 32 : cl - 4 + (max(cl - 29, 0) * 37 >> 8)) * 2 + (blockIdx.x & 1);
  const int rb = bid & 15, j = bid >> 4;
  uint4 wv[5];
  {
    const int n8 = min(tid >> 3, 26), part = n8 / 9;
    const uint8_t* src = (const uint8_t*)Q.wqkv + (8 * rb + (tid & 7)) * (3 * DM * 2) + (part * (DM - 72) + 72 * j + 8 * n8) * 2;
#pragma unroll
    for (int u = 0; u < 5; u++) wv[u] = ldnc128_if(tid < 216 && cl < 64 && (u < 4 || rb < 8), src + u * (128 * 3 * DM * 2));
  }
  if (cl >= 64) return;
  if (wid >= 7 && lane == 0) {
    if (wid < 10) {
#pragma unroll
      for (uint32_t b = 0; b < B_AD / 3; b += 8) mbar_init(bars + (wid - 7) * (B_AD / 3) + b, 1);
    } else if (wid == 10) {
#pragma unroll
      for (uint32_t b = B_AD; b < B_EVT; b += 8) mbar_init(bars + b, b < B_HOLD ? 2 : 4);
    } else {
#pragma unroll
      for (uint32_t b = B_EVT; b < 1024; b += 8) if (b < B_OFF || b >= B_IMG) mbar_init(bars + b, b < B_IMG ? 4 : b < B_EMPTY ? 8 : 16);
    }
    asm volatile("fence.mbarrier_init.release.cluster;" ::: "memory");
  }
  __syncthreads();

  if (wid >= 8) {
    reg_dealloc<56>();
    const uint32_t el = elect_one();
    const uint64_t pol = policy_evict_first();
    uint32_t* const fj = Q.flags + FJ + j * 32;
    if (wid == 8) {
      if (el) { prefetch_map(&P.wsp); prefetch_map(&P.winb[j & 1]); prefetch_map(&P.wins); prefetch_map(&P.wout); prefetch_map(&P.act[1]); prefetch_map(&P.res[0]); prefetch_map(&P.res[1]); }
      const uint32_t epoch = ldcg32(fj + FJ_EP + rb);
      Cur c{0, 1};
      const uint32_t rk = bid & 1;
      uint32_t st, full;
      auto slot = [&](uint32_t bytes) {
        st = sb + c.s * ST_BYTES; full = bars + B_FULL + c.s * 8;
        mbar_wait(full, c.ph);
        expect_tx_p(el, full, bytes);
        mbar_wait(full - B_FULL + B_EMPTY, c.ph);
      };
#pragma unroll 1
      for (int L = 0; L < 2; L++) {
#pragma unroll 1
        for (int i = 0; i < 9; i++) {
          if (L == 0 && i == 0) {
            flag_wait(fj + FJ_WQ, (epoch + 1) * 16);
            fence_async_g();
            TRC(el, 2, 45);
          }
          slot(27648);
          bulk_mc_h(el, st + ST_B + rk * 13824, Q.WQ + j * WQ_SL + i * 27648 + rk * 13824, 13824, full, EF(0), pol);
          c.next();
        }
        if (L == 0) {
          flag_wait(fj + FJ_WO, (epoch + 1) * 16);
          fence_async_g();
          TRC(el, 2, 46);
        }
#pragma unroll 1
        while (c.s) {
          mbar_wait(bars + B_EMPTY + c.s * 8, c.ph);
          if (el) { mbar_arrive(bars + B_FULL + c.s * 8); asm volatile("mbarrier.arrive.shared::cta.b64 _, [%0], 16;" ::"r"(bars + B_EMPTY + c.s * 8) : "memory"); }
          c.next();
        }
        expect_tx_p(el, bars + B_WF, WO_SL);
        mbar_wait(bars + B_EMPTY, c.ph);
        mbar_wait(bars + B_EMPTY + 8, c.ph);
        bulk_mc_h(el, sb + rk * (WO_SL / 2), Q.WO + j * WO_SL + rk * (WO_SL / 2), WO_SL / 2, bars + B_WF, EF(1), pol);
#pragma unroll 1
        for (int r = 0; r < 10; r++) {
          const bool big = r >= 2 && r < 8;
          const int a0 = (r < 5 ? 36 : 0) + ((9 * j) >> 1) + (big ? 2 - 2 * (j & 1) : 3 * (j & 1) + rk), ks = big ? 32 : 48;
          int k = big ? (r < 5 ? r - 2 : r - 5) * 192 + rk * 16 : (r & 1) * 288;
          const CUtensorMap* m = big ? &P.winb[j & 1] : &P.wins;
          const uint32_t dst = sb + SM_B3 + rk * 6144;
#pragma unroll
          for (int p = 0; p < 6; p++, k += ks) {
            if (!(p & 3) && r == 0) mbar_wait(bars + B_XD + p * 2, L);
            if (p) mbar_wait_c(bars + B_E3 + p * 8, ~r & 1); else mbar_wait(bars + B_E3, ~r & 1);
            expect_tx_p(el, bars + B_F3 + p * 8, 12288);
            tma3d_mc_h(el, dst + p * 12288, m, 0, k, a0, bars + B_F3 + p * 8, EF(2), pol);
          }
        }
        TRC(el, 2, L * 16 + 6);
        mbar_wait(bars + B_ZOK, L);
        fence_async_g();
        TRC(el, 2, L * 16 + 7);
        const uint8_t* src = z2_block(0, j) + rk * 18432;
#pragma unroll 1
        for (int r = 0; r < 8; r++) {
          const int k = (r & 3) * 512 + ((r >> 2) ^ 1) * 64;
#pragma unroll
          for (int p = 0; p < 4; p++, src += 8 * ZB) {
            if ((p == 1 || p == 2) && r == 0) mbar_wait(bars + B_E3 - 8 + p * 24, 1);
            mbar_wait_c(bars + B_AD + p * 8, ~r & 1);
            if (p) mbar_wait_c(bars + B_EMPTY + p * 8, c.ph); else mbar_wait(bars + B_EMPTY, c.ph);
            expect_tx_p(el, bars + B_FULL + p * 8, ST_BYTES);
            bulk_mc_h(el, sb + p * ST_BYTES + ST_B + rk * 18432, src, 18432, bars + B_FULL + p * 8, EF(4), pol);
            tma3d_h(el, sb + p * ST_BYTES, &P.wsp, k + p * 128, rb * 64, 0, bars + B_FULL + p * 8, EF(3), pol);
          }
          c.ph ^= 1;
        }
        mbar_wait(bars + B_Z1, L);
        fence_async_g();
#pragma unroll 1
        for (int i = 0; i < 11; i++) {
          const int cb = i - 2 + j;
          if (i < 4) mbar_wait(bars + B_AD + c.s * 8, 1);
          slot(ZB);
          if (i < 2) bulk_load_h(el, st + ST_B, z1_block(rb, i, j), ZB, full, true, pol);
          else tma2d_mc_h(el, st + ST_B + rk * 18432, &P.wout, (cb >= 9 ? cb - 9 : cb) * 64, 288 * j + rk * 144, full, EF(5), pol);
          c.next();
        }
      }
    } else if (wid < 11) {
      uint32_t id = bid * 2 + wid - 9;
#define AGENT_IDS asm volatile("" : "+r"(lane), "+r"(id)); const uint32_t w = id & 1, hw = id & 31, rb = hw >> 1, j = id >> 5, ev = bars + B_EVT + w * EV_N * 8; \
      uint32_t* const fr = Q.flags + hw * 32; uint32_t* const fj = Q.flags + FJ + j * 32; (void)fr; (void)fj; (void)ev; (void)rb
      uint32_t t8 = 0;
      Cur c{0, 1};
#pragma unroll 1
      for (int L = 0; L < 2; L++) {
        if (L) {
          AGENT_IDS;
          const uint32_t full = bars + B_FULLA + w * 32 + c.s * 8, dst = sb + c.s * ST_BYTES + w * 8192;
          expect_tx_p(el, full, 8192);
          mbar_wait_c(ev + EV_PT * 8, 1);
          TRC(el, 3, w * 32 + 16);
          flag_release_p(el, fr + FR_X2);
          TRC(el, 3, w * 32 + 17);
          mbar_wait_c(bars + B_EMPTY + c.s * 8, c.ph);
          flag_wait(fr + FR_X2, t8);
          fence_async_g();
          tma3d_h(el, dst, &P.act[1], 0, (hw ^ 1) * 32, 0, full, false, pol);
          c.next();
          TRC(el, 3, w * 32 + 18);
        }
#pragma unroll 1
        for (int i = L; i < 9; i++) {
          AGENT_IDS;
          const uint32_t full = bars + B_FULLA + w * 32 + c.s * 8, dst = sb + c.s * ST_BYTES + w * 8192;
          if (L == 0 && i == AEP) t8 = (ldcg32(fr + FR_EP + j) + 1) * 8;
          mbar_wait_c(bars + B_EMPTY + c.s * 8, c.ph);
          expect_tx_p(el, full, 8192);
          tma3d_h(el, dst, &P.act[L], i * 64, (hw ^ 1) * 32, 0, full, false, pol);
          c.next();
          if (i == PZI || i == PZI + 1) {
            uint8_t* d = (i == PZI ? xn_block(hw) : z1_block(rb, 0, 0) + w * 4608) + j * 9216 + lane * 16;
#pragma unroll 1
            for (int u = i == PZI ? 0 : 3; u < 6; u++, d += 1536) { stg128(d, ~0u, ~0u, ~0u, ~0u); stg128(d + 512, ~0u, ~0u, ~0u, ~0u); stg128(d + 1024, ~0u, ~0u, ~0u, ~0u); }
          }
          if (i == PZI) { stg128(Q.ST1 + (hw * 8 + j) * 32 + lane, ~0u, ~0u, ~0u, ~0u); stg128(Q.ZST + (hw * 8 + j) * 32 + lane, ~0u, ~0u, ~0u, ~0u); }
          if (i == RFI) {
            if (L) mbar_wait_c(bars + B_EVT + (EV_N * (1 - w) + EV_PT) * 8, 1);
            expect_tx_p(el, bars + B_WT + w * 8, 9216);
            bulk_load_p(el, sb + SM_STG + w * 9216, (L ? Q.out : Q.x) + ((hw ^ 1) * 64 + 8 * j) * (DM * 2), 9216, bars + B_WT + w * 8);
          }
          if (i == 4 && L > w) {
            expect_tx_p(el, bars + B_XRW + 8, 864);
            bulk_load_p(el, sb + 3 * ST_BYTES + SM_CSQ, Q.CSP + (NCTA + (id >> 1)) * 216, 864, bars + B_XRW + 8);
          }
        }
        if (c.s) { c.s = 0; c.ph ^= 1; }
        {
          AGENT_IDS;
          const uint32_t tag = (t8 >> 2) - 1 + L;
          uint4* const xs = Q.XST + hw * 128;
          const uint32_t tab = sb + L * (3 * ST_BYTES) + SM_XST + w * 768 + lane * 8;
          TRC(el, 3, w * 32 + L * 16 + 13);
#pragma unroll 1
          for (int it = 0; it < (1 << 22); it++) {
            const uint4 a = ll_ld128(xs + 2 * lane), b = ll_ld128(xs + 64 + 2 * lane), h = ll_ld128(xs - (rb ? 192 : 0) + 2 * (lane | 24));
            if (__all_sync(~0u, a.z == tag && b.z == tag && h.z == tag)) { sts64(tab, h.x, h.y); sts64(tab + 256, a.x, a.y); sts64(tab + 512, b.x, b.y); break; }
          }
          __syncwarp();
          if (el) mbar_arrive(bars + B_CSQ);
          TRC(el, 3, w * 32 + L * 16 + 14);
          uint32_t* f = Q.flags + rb * 64 + FR_PZ + L;
          flag_release_p(el, f);
          expect_tx_p(el, bars + B_RES + w * 8, 9216);
          tma3d_h(el, sb + SM_STG + w * 9216, &P.res[L], j * 72, (hw ^ 1) * 32, 0, bars + B_RES + w * 8, !L, pol);
          pause<FD3>(Q.zero);
          flag_wait(f, t8 * 2);
          fence_async_g();
          TRC(el, 3, w * 32 + L * 16 + 15);
        }
        {
          AGENT_IDS;
          uint32_t* f = Q.flags + rb * 64 + FR_O + L;
#pragma unroll 1
          for (int e = 0; e < 5; e++) {
            const uint32_t nb = e ? 16384 : 8192, full = bars + B_OF + w * 40 + e * 8, dst = sb + o_place(w, e);
            const uint8_t* src = z1_block(rb, w, 0) + (e ? e * 16384 - 8192 : 0);
            expect_tx_p(el, full, nb);
            if (e == 0) {
              mbar_wait_c(ev + EV_O * 8, L);
              TRC(el, 3, w * 32 + L * 16 + 3);
              if (!w) flag_add_p(el, f);
              flag_wait(f + w * (FR_OL - FR_O), t8);
              if (w) fence_async_g();
            }
            if (w && (e == 0 || e == 3)) mbar_wait_c(bars + (e ? B_X3 : B_OF + YPACE * 8), L);
            bulk_load_h(el, dst, src, nb, full, EF(6), pol);
            TRC(el && e == 0, 3, w * 32 + L * 16 + 5);
          }
        }
        {
          AGENT_IDS;
          const uint8_t* src = xn_block(hw);
          uint32_t full = bars + B_AF3 + w * 96, dst = sb + w * 6144;
          if (L) flag_wait(fj + FJ_P4, t8 * 4);
          mbar_wait_c(bars + B_XD + 8, L);
          mbar_wait_c(ev + EV_X1 * 8, L);
          TRC(el, 3, w * 32 + L * 16 + 6);
          pause<SDEL>(Q.zero);
#pragma unroll 1
          for (int k = 0; k < 12; k++, src += 6144, dst += 12288, full += 8) {
            expect_tx_p(el, full, 6144);
            if (k >= APACE) mbar_wait_c(full - APACE * 8, L);
            bulk_load_h(el, dst, src, 6144, full, EF(7), pol);
            TRC(el && k == 0, 3, w * 32 + L * 16 + 8);
          }
        }
        if (wid == 10) {
          AGENT_IDS;
          mbar_wait_c(ev - (EV_N - EV_ZN) * 8, L);
          mbar_wait_c(ev + EV_ZN * 8, L);
          asm volatile("fence.release.gpu;" ::: "memory");
          flag_add_p(el, fj + FJ_ZN + L);
          flag_add_p(el, fr - 32 + FR_XR + L);
          flag_wait(fj + FJ_ZN + L, t8 * 2);
          flag_wait(fr - 32 + FR_XR + L, t8);
          if (el) mbar_arrive(bars + B_ZOK);
        } else {
          AGENT_IDS;
          mbar_wait_c(ev + EV_ZN * 8, L);
          if (el) asm volatile("cp.async.bulk.prefetch.tensor.3d.L2.global [%0, {%1, %2, %3}];" ::"l"(&P.wsp), "r"(j * 128 + 64), "r"(rb * 64), "r"(0) : "memory");

        }
        float cv;
        {
        AGENT_IDS;
        cv = (lane & 3) ? 0.f : -blo(ldnc16(Q.b_sp + 128 * rb + 16 * j + 2 * (lane >> 2) + w));
        const uint32_t ro = (w * 64 + 8 * j + (lane >> 2)) * 128, x0 = ((lane & 3) * 2) ^ (lane >> 2);
#pragma unroll 1
        for (int i = 0; i < 32; i++) {
          const bool tail = (i >> 1) == 12;
          const int kb = tail ? i + 6 : i < 24 ? i : i - 2;
          if (!(i & 7)) mbar_wait_c(bars + B_RT + i, L);
          if (i == 24) mbar_wait_c(bars + B_WT + w * 8, 1);
          if (!tail) mbar_wait(bars + B_FULL + c.s * 8, c.ph ^ 1);
          uint4 x[2];
#pragma unroll
          for (int e = 0; e < 2; e++) x[e] = lds128(!tail ? sb + c.s * ST_BYTES + ro + ((x0 ^ e) << 4) : sb + SM_WT + w * 3200 + (lane >> 2) * 400 + (i - 24) * 256 + (lane & 3) * 32 + e * 16);
          if (!tail) {
            __syncwarp();
            if (el) mbar_arrive(bars + B_AD + c.s * 8);
            c.next();
          }
#pragma unroll
          for (int e = 0; e < 2; e++) {
            const uint4 a = x[e], m = lds128(sb + SM_RT + 4096 + kb * 128 + (lane & 3) * 32 + e * 16);
            cv = fmaf(blo(a.x), blo(m.x), fmaf(bhi(a.x), bhi(m.x), fmaf(blo(a.y), blo(m.y), fmaf(bhi(a.y), bhi(m.y), cv))));
            cv = fmaf(blo(a.z), blo(m.z), fmaf(bhi(a.z), bhi(m.z), fmaf(blo(a.w), blo(m.w), fmaf(bhi(a.w), bhi(m.w), cv))));
          }
          if (i == WTI) {
            uint32_t id2 = id;
            asm volatile("" : "+r"(id2));
            expect_tx_p(el, bars + B_WT + w * 8, 3072);
#pragma unroll 1
            for (int r = 0; r < 8; r++)
              bulk_load_p(el, sb + SM_WT + w * 3200 + r * 400, (const uint8_t*)Q.w_sp + (64 * (id2 & 30) + 16 * (id2 >> 5) + 2 * r + w) * (SEQ * 2) + 28 * 128, 384, bars + B_WT + w * 8);
          }
        }
        }
        AGENT_IDS;
        TRC(el, 3, w * 32 + L * 16 + 11);
        asm volatile("" : "+r"(t8));
        const uint32_t tag = (t8 >> 2) - 1 + L;
        cv = qsum(cv);
        uint2* const cs = (uint2*)(Q.XST + hw * 128 + 1);
        if ((lane & 3) == 0) ll_st64(cs + 32 * j + (lane >> 2) * 4, __float_as_uint(cv), tag);
#pragma unroll 1
        for (int it = 0; it < (1 << 22); it++) {
          const uint2 a = ll_ld64(cs + 4 * lane), b = ll_ld64(cs + 128 + 4 * lane);
          if (__all_sync(~0u, a.y == tag && b.y == tag)) { sts32(sb + SM_CV + w * 256 + lane * 4, a.x); sts32(sb + SM_CV + w * 256 + 128 + lane * 4, b.x); break; }
        }
        __syncwarp();
        if (el) mbar_arrive(bars + B_CV + w * 8);
        TRC(el, 3, w * 32 + L * 16 + 12);
#pragma unroll 1
        for (int kb = 30; kb < 32; kb++) {
          mbar_wait_c(bars + B_FULL + c.s * 8, c.ph ^ 1);
          if (el) mbar_arrive(bars + B_AD + c.s * 8);
          c.next();
        }
        c.ph ^= ((c.s + 11) >> 2) & 1; c.s = (c.s + 11) & 3;
        if (L == 0) {
          mbar_wait_c(ev + EV_PT * 8, 0);
          flag_add_p(el, fj + FJ_P4);
        }
      }
    } else {
      const uint32_t epoch = ldcg32(fj + FJ_EP + rb);
      mbar_wait(bars + B_IMG, 0);
      TRC(el, 2, 41);
      flag_release_p(el, fj + FJ_WQ);
      TRC(el, 2, 42);
#pragma unroll 1
      for (int L = 0; L < 2; L++) {
        float* const csf = Q.CSP + (NCTA + bid) * 216;
        if (L == 0) {
          flag_wait(fj + FJ_WQ, (epoch + 1) * 16);
          fence_async_g();
          expect_tx_p(el, bars + B_XRW, 13824);
          bulk_load_p(el, sb + ST_BYTES + SM_WOI, Q.CSP + j * 16 * 216, 6912, bars + B_XRW);
          bulk_load_p(el, sb + 2 * ST_BYTES + SM_WOI, Q.CSP + (j * 16 + 8) * 216, 6912, bars + B_XRW);
          mbar_wait(bars + B_XRW, 0);
#pragma unroll 1
          for (int f = lane; f < 54; f += 32) {
            float s[4] = {0.f, 0.f, 0.f, 0.f};
#pragma unroll 2
            for (int r = 0; r < 16; r++) {
              const uint4 v = lds128(sb + ST_BYTES + SM_WOI + (r >> 3) * ST_BYTES + (r & 7) * 864 + f * 16);
              s[0] += __uint_as_float(v.x); s[1] += __uint_as_float(v.y); s[2] += __uint_as_float(v.z); s[3] += __uint_as_float(v.w);
            }
            sts128(sb + SM_CSQ + f * 16, __float_as_uint(s[0]), __float_as_uint(s[1]), __float_as_uint(s[2]), __float_as_uint(s[3]));
            stg128(csf + f * 4, __float_as_uint(s[0]), __float_as_uint(s[1]), __float_as_uint(s[2]), __float_as_uint(s[3]));
          }
          __syncwarp();
          if (el) mbar_arrive(bars + B_XRW + 8);
          TRC(el, 2, 43);
          mbar_wait(bars + B_WOI, 0);
          bulk_store_p(el, Q.WO + j * WO_SL + rb * (41 * 128), sb + SM_WOI, (rb < 15 ? 41 : 33) * 128);
          publish_p(el, fj + FJ_WO);
          TRC(el, 2, 44);
          if (el) prefetch_l2((const uint8_t*)Q.w_in + bid * 41472, 41472);
          float o0 = 0.f, o1 = 0.f;
#pragma unroll 1
          for (int u = 0; u < 2; u++) {
            const uint8_t* src = (u ? (const uint8_t*)Q.w_sp + 500 * (SEQ * 2) + 2048 : (const uint8_t*)Q.w_in + 100 * (2 * FH * 2) + FH * 2) + lane * 16;
            const uint4 a = ldnc128(src), b = ldnc128(src + 300 * (2 * FH * 2) + 2048);
            const uint32_t x[8] = {a.x, a.y, a.z, a.w, b.x, b.y, b.z, b.w};
            float sq = 0.f;
#pragma unroll
            for (int e = 0; e < 8; e++) sq = fmaf(blo(x[e]), blo(x[e]), fmaf(bhi(x[e]), bhi(x[e]), sq));
            o0 = o1;
            asm("sqrt.approx.f32 %0, %1;" : "=f"(o1) : "f"(wsum(sq) * (u ? C0S * C0S * SEQ / 512.f : 2.f * GA * GA * DM / 512.f)));
          }
          const uint32_t off = (__float_as_uint(o0) & 0x7f800000u) >> 16 | 0x8000u | OFM;
          const uint32_t c0 = min(max(__float_as_uint(o1) & 0x7f800000u, 0x04000000u), 0x7e000000u) | 0x00400000u;
          if (el) sts128(sb + SM_OFF, off * 0x10001u, c0, __float_as_uint(GB), ((c0 >> 16) - 0x200u) * 0x10001u);
        }
        mbar_wait(bars + B_EVT + EV_O * 8, L);
        mbar_wait(bars + B_EVT + (EV_N + EV_O) * 8, L);
        flag_release_p(el, Q.flags + rb * 64 + FR_OL + L);
#pragma unroll 1
        for (int w = 0; w < 2; w++) {
          mbar_wait(bars + B_EVT + (w * EV_N + EV_XS) * 8, L);
          if (!w) mbar_wait(bars + B_AF3 + 96 + XP0 * 8, L);
          if (el) asm volatile("cp.async.bulk.tensor.3d.global.shared::cta.tile.bulk_group [%0, {%2, %3, %4}], [%1];\ncp.async.bulk.commit_group;\ncp.async.bulk.wait_group.read 0;" ::"l"(&P.res[1]), "r"(sb + SM_STG + 9216), "r"(j * 72), "r"(rb * 64 + (w ^ 1) * 32), "r"(0) : "memory");
          __syncwarp();
          if (lane < 2 && !w) mbar_arrive(bars + B_S5);
        }
        sts64(sb + SM_CV + 512 + lane * 8, 0x3f803f80u, 0x3f803f80u);
        fence_async_s();
        __syncwarp();
        if (el) { asm volatile("cp.async.bulk.wait_group 0;" ::: "memory"); mbar_arrive(bars + B_GATE3); }
        const uint32_t tag = epoch * 2 + L + 1;
        asm volatile("" : "+r"(lane));
#pragma unroll 1
        for (int b = 0; b < 8; b++) {
          if (!(b & 3)) {
            const int mb = b >> 2;
            mbar_wait(bars + B_ZS + mb * 8, L);
            pause<ZD1>(Q.zero);
            TRC(el && !mb, 2, L * 16 + 8);
            uint4 v;
#pragma unroll 1
            for (int it = 0; it < (1 << 22); it++) {
              v = ll_ld128(Q.ZST + ((rb * 2 + mb) * 8 + (lane >> 2)) * 32 + 4 * j + (lane & 3));
              if (__all_sync(~0u, max(max(v.x, v.y), max(v.z, v.w)) != ~0u)) break;
            }
            if (lane < 2 && !mb) mbar_arrive(bars + B_S5);
            const bool o = lane & 16;
            float ss = __uint_as_float(o ? v.y : v.x) + __shfl_xor_sync(~0u, __uint_as_float(o ? v.x : v.y), 16), sq = __uint_as_float(o ? v.w : v.z) + __shfl_xor_sync(~0u, __uint_as_float(o ? v.z : v.w), 16);
            ss += __shfl_xor_sync(~0u, ss, 4); sq += __shfl_xor_sync(~0u, sq, 4); ss += __shfl_xor_sync(~0u, ss, 8); sq += __shfl_xor_sync(~0u, sq, 8);
            const float mean = ss * (1.f / FH), rs = blo(pack2(rsq_fast(fmaxf(fmaf(sq, 1.f / FH, -mean * mean), 0.f) + 4.f * GA * GA * LN_EPS), 0.f));
            if (!(lane & 12)) ll_st64(Q.RT + (mb * 16 + rb) * 64 + 8 * j + 2 * (lane & 3) + (lane >> 4), pack2(rs, rs * (mean - blo(lds32(sb + SM_OFF)))), tag);
            TRC(el && !mb, 2, L * 16 + 10);
            pause<ZD2>(Q.zero);
          }
          uint4 v[4];
#pragma unroll 1
          for (int it = 0; it < (1 << 22); it++) {
            bool ok = true;
#pragma unroll
            for (int u = 0; u < 4; u++) { v[u] = ll_ld128((const uint4*)Q.RT + b * 128 + u * 32 + lane); ok = ok && v[u].y == tag && v[u].w == tag; }
            if (__all_sync(~0u, ok)) break;
          }
#pragma unroll
          for (int u = 0; u < 4; u++) {
            const uint32_t rt = sb + SM_RT + b * 512 + u * 128, ro = (lane >> 3) * 32 + (lane & 3) * 8 + ((lane >> 2) & 1) * 2;
            sts32(rt + 4096 + lane * 4, __byte_perm(v[u].x, v[u].z, 0x7632));
            asm volatile("st.shared.u16 [%0], %1;\nst.shared.u16 [%0 + 4], %2;" ::"r"(rt + ro), "h"((uint16_t)v[u].x), "h"((uint16_t)v[u].z) : "memory");
          }
          __syncwarp();
          if (el && (b & 1)) mbar_arrive(bars + B_RT + (b - 1) * 4);
          TRC(el && b < 2, 2, L * 16 + 11 + b);
        }
        TRC(el, 2, L * 16 + 9);
        mbar_wait(bars + B_EVT + EV_Z1 * 8, L);
        mbar_wait(bars + B_EVT + (EV_N + EV_Z1) * 8, L);
        fence_gpu();
        if (el) mbar_arrive(bars + B_Z1);
      }
    }
  } else {
    int w = wid >> 2, q = wid & 3, rb = bid & 15, j = bid >> 4;
    int g = lane >> 2, t = lane & 3;
#define PHASE asm volatile("" : "+r"(w), "+r"(q), "+r"(rb), "+r"(j))
#define stg (sb + SM_STG + w * 9216)
#define pw (q >> 1)
#define pq (2 - 2 * w + (q & 1))
    const bool tr = (tid & 127) == 0;
    (void)tr;
    Cur c{0, 0};
    const uint32_t ebar = mapa(bars + B_EMPTY, (bid & 1) ^ (lane & 1));
    auto release = [&](uint32_t s) { if (lane < 2) mbar_arrive_cluster(ebar + s * 8); };
    uint32_t ia = 0;
    auto wait_ab = [&]() { mbar_wait_c(bars + B_FULL + c.s * 8, c.ph); mbar_wait_c(bars + B_FULLA + w * 32 + c.s * 8, (ia >> c.s) & 1); ia ^= 1u << c.s; };
    uint32_t rp = 0;
    auto check = [&](auto n, uint32_t dst, const uint8_t* src) {
      const uint32_t a = dst + lane * 32 + (lane >> 2) * 4;
#pragma unroll 1
      for (int it = 0; it < (1 << 16); it++) {
        uint32_t x = lds32(a);
#pragma unroll
        for (int e = 1; e < n.value; e++) x = max(x, lds32(a + e * 1024));
        if (!__any_sync(~0u, x == ~0u)) break;
        fence_async_s();
        __syncwarp();
        const uint32_t el = elect_one();
        expect_tx_p(el, bars + B_RB + q * 8, n.value * 1024);
        bulk_load_p(el, dst, src, n.value * 1024, bars + B_RB + q * 8);
        mbar_wait_c(bars + B_RB + q * 8, rp & 1);
        rp++;
      }
    };
    auto signal = [&](int e) { __syncwarp(); if (lane == 0) mbar_arrive(bars + B_EVT + w * EV_N * 8 + e * 8); };
    TRC(tr, w, 0);

    {
      uint8_t* dst = Q.WQ + j * WQ_SL + rb * 3456 + tid * 16;
#pragma unroll
      for (int u = 0; u < 5; u++) {
        stg128_if((u < 4 || rb < 8) && tid < 216, dst + u * (16 * 3456), wv[u].x, wv[u].y, wv[u].z, wv[u].w);
        if (u == 0) TRC(tr, w, 60);
      }
      if (Q.zero == 0) {
        float s[8];
#pragma unroll
        for (int u = 0; u < 5; u++) {
          const uint32_t x[4] = {wv[u].x, wv[u].y, wv[u].z, wv[u].w};
#pragma unroll
          for (int e = 0; e < 4; e++) { s[2 * e] = u ? s[2 * e] + blo(x[e]) : blo(x[e]); s[2 * e + 1] = u ? s[2 * e + 1] + bhi(x[e]) : bhi(x[e]); }
        }
#pragma unroll
        for (int m = 4; m; m >>= 1) {
#pragma unroll
          for (int e = 0; e < m; e++) s[e] = ((tid & m) ? s[e + m] : s[e]) + __shfl_xor_sync(~0u, (tid & m) ? s[e] : s[e + m], m);
        }
        stg32_if(tid < 216, Q.CSP + bid * 216 + tid, __float_as_uint(s[0]));
      }
      __syncwarp();
      if (lane == 0) mbar_arrive(bars + B_IMG);
    }
    reg_alloc<224>();
    auto fetch_wo = [&]() {
#pragma unroll 1
      for (int u = tid; u < 328; u += 256) {
        const int m = min(41 * rb + (u >> 3), 647), k8 = m / 9;
        cp_async16(sb + SM_WOI + u * 16, (const uint8_t*)Q.wo + (8 * k8 + (u & 7)) * (DM * 2) + (72 * j + 8 * (m - k8 * 9)) * 2);
      }
    };
    const uint32_t epoch = ldcg32(Q.flags + (rb * 2 + w) * 32 + FR_EP + j);
    TRC(tr, w, 1);

#pragma unroll 1
    for (int L = 0; L < 2; L++) {
      const int tb = 2 + L * 24;
      asm volatile("" : "+r"(lane), "+r"(g), "+r"(t));
      PHASE;
      (void)tb;
      const uint32_t tag = epoch * 2 + L + 1;
      {
        uint32_t Pk[27][2];
        float rk[2][2], sc[2][2];
        const bool up0 = 2 * t > g, up1 = 2 * t + 1 > g;
        constexpr int HA_[6] = {0, 2, 4, 7, 12, 15}, HC_[6] = {6, 9, 10, 11, 14, 17};
        const bool remote = pq == 0 && rb > 0;
        uint4* hp = Q.HALO + ((((rb - (pq == 0)) * 2 + pw) * 8 + j) * 6) * 32 + lane;
        const uint32_t att = 2 * ST_BYTES + pw * 3072 + lane * 16;
        const uint8_t* hs = remote ? (const uint8_t*)hp : smem_raw + att + (pq == 3 ? 0 : pq == 2 ? ST_BYTES + 8192 : 8192);
        uint8_t* od = z1_block(rb, w, 0) + (9 * j) * 1024 + (4 * (q & 1) + pw) * 128 + lane * 4;
        ACLK_INIT;
        {
          float acc[108];
#pragma unroll
          for (int i = 0; i < 108; i++) acc[i] = 0.f;
          float sx[2] = {0.f, 0.f}, sq[2] = {0.f, 0.f};
          uint32_t prev = 0;
#pragma unroll 1
          for (int kb = 0; kb < 7; kb++) {
            wait_ab();
            TRC(tr && kb == 0, w, tb + 0);
            PCLK(kb * 4);
            const uint32_t st = sb + c.s * ST_BYTES, da = dlo(st + w * 8192, 16), db = dlo(st + ST_B, 3456);
            wgmma_fence();
#pragma unroll
            for (int kk = 0; kk < 4; kk++) {
              wgmma_ss_n216(acc, dsc<1024, 1>(da, kk * 32), dsc<128, 0>(db, kk * 6912), 1);
              if (kk == 0) { wgmma_commit(); wgmma_wait<1>(); if (kb > 0) release(prev); }
              if (kk == 3) wgmma_commit();
              if (kk == XK1) {
            if (kb >= KS && kb < KS + 3) {
              mbar_wait_c(bars + B_WT + w * 8, 0);
#pragma unroll
              for (int u = 0; u < 3; u++) {
                const uint2 x = lds64(stg + (2 * q + (lane >> 4)) * 1152 + (lane & 15) * 8 + (kb - KS) * 384 + u * 128);
                sx[0] += blo(x.x) + bhi(x.x); sx[1] += blo(x.y) + bhi(x.y);
                sq[0] = fmaf(blo(x.x), blo(x.x), fmaf(bhi(x.x), bhi(x.x), sq[0])); sq[1] = fmaf(blo(x.y), blo(x.y), fmaf(bhi(x.y), bhi(x.y), sq[1]));
              }
            }
            if (kb == KS + 3) {
              const bool o = lane & 1;
              float v = (o ? sq[0] + sq[1] : sx[0] + sx[1]) + __shfl_xor_sync(~0u, o ? sx[0] + sx[1] : sq[0] + sq[1], 1);
              v += __shfl_xor_sync(~0u, v, 2); v += __shfl_xor_sync(~0u, v, 4); v += __shfl_xor_sync(~0u, v, 8);
              const float m = v * (-1.f / DM), r = rsq_fast(fmaxf(fmaf(__shfl_xor_sync(~0u, v, 1), 1.f / DM, -m * m), 0.f) + LN_EPS);
              ll_st128_if(!(lane & 15), Q.XST + rb * 256 + (lane >> 4) * 128 + (1 - w) * 64 + 8 * j + 2 * q, m, r, tag);
            }
              }
              if (kk == XK2 && L == 0) {
            if (kb == 0) fetch_wo();
            if (kb == 3) {
              asm volatile("cp.async.wait_all;" ::: "memory");
              fence_async_s();
              __syncwarp();
              if (lane == 0) mbar_arrive(bars + B_WOI);
            }
              }
            }
            prev = c.s; c.next();
          }
          const uint32_t ls = sb + L * (3 * ST_BYTES), cs = ls + SM_CSQ + t * 8;
          float2 cv[27];
          mbar_wait_c(bars + B_XRW + 8, L);
#pragma unroll
          for (int kb = 7; kb < 9; kb++) {
            wait_ab();
            PCLK(kb * 4);
            const uint32_t st = sb + c.s * ST_BYTES, da = dlo(st + w * 8192, 16), db = dlo(st + ST_B, 3456);
            wgmma_fence();
#pragma unroll
            for (int kk = 0; kk < 4; kk++) {
              wgmma_ss_n216(acc, dsc<1024, 1>(da, kk * 32), dsc<128, 0>(db, kk * 6912), 1);
              if (kk == 0) { wgmma_commit(); wgmma_wait<1>(); release(prev); }
              if (kb == 7 && kk < 3) {
#pragma unroll
                for (int G = 9 * kk; G < 9 * kk + 9; G++) cv[G] = lds64f(cs + G * 32);
                wgmma_fence();
              }
            }
            wgmma_commit();
            prev = c.s; c.next();
          }
          mbar_wait_c(bars + B_CSQ, L);
          const uint32_t xs = ls + SM_XST + pw * 768 + 256 + pq * 128;
          const float2 n0 = lds64f(xs + g * 8), n1 = lds64f(xs + g * 8 + 64);
          const float m0 = n0.x, m1 = n1.x;
#pragma unroll
          for (int u = 0; u < 4; u++) {
            rk[u >> 1][u & 1] = __uint_as_float(lds32(xs + t * 16 + ((u & 1 ? up1 : up0) ? -64 : 0) + (u & 1) * 8 + (u >> 1) * 64 + 4));
            sc[u >> 1][u & 1] = rk[u >> 1][u & 1] * ((u >> 1 ? n1.y : n0.y) * (0.23570226039551584f * 1.4426950408889634f));
          }
          PCLK(36);
          wgmma_wait<0>();
          PCLK(37);
          release(prev);
          TRC(tr, w, tb + 1);
          ACLK(0);
#pragma unroll
          for (int G = 9; G < 27; G++) Pk[G][1] = pack2(fmaf(m1, cv[G].x, acc[4 * G + 2]), fmaf(m1, cv[G].y, acc[4 * G + 3]));
          if (pq < 3) {
#pragma unroll
            for (int i = 0; i < 6; i++) sts128(sb + att + (pq & 1) * ST_BYTES + w * 8192 + i * 512, Pk[9 + HA_[i]][1], Pk[10 + HA_[i]][1], tag, Pk[9 + HC_[i]][1]);
          } else if (rb < 15) {
#pragma unroll
            for (int i = 0; i < 6; i++) ll_st128(hp + i * 32, __uint_as_float(Pk[9 + HA_[i]][1]), __uint_as_float(Pk[10 + HA_[i]][1]), tag, __uint_as_float(Pk[9 + HC_[i]][1]));
          }
          if (w) bar_arrive(1, 256);
#pragma unroll
          for (int G = 0; G < 27; G++) {
            Pk[G][0] = pack2(fmaf(m0, cv[G].x, acc[4 * G]), fmaf(m0, cv[G].y, acc[4 * G + 1]));
            if (G < 9) Pk[G][1] = pack2(fmaf(m1, cv[G].x, acc[4 * G + 2]), fmaf(m1, cv[G].y, acc[4 * G + 3]));
          }
        }
        ACLK(1);
        constexpr int GA_[4] = {0, 2, 4, 7}, GB_[4] = {1, 3, 5, 8}, GC_[4] = {2, 4, 6, 6};
        float S1[4][4], S2[4][4];
        uint32_t qa[4][2], qc[4][2];
#pragma unroll
        for (int h = 0; h < 4; h++) {
#pragma unroll
          for (int r = 0; r < 2; r++) {
            qa[h][r] = (h == 0 || h == 3 || t >= h) ? Pk[GA_[h]][r] : 0u;
            qc[h][r] = (h == 3 ? t == 3 : t <= h) ? Pk[GC_[h]][r] : 0u;
          }
#pragma unroll
          for (int i = 0; i < 4; i++) S1[h][i] = S2[h][i] = 0.f;
          mma16(S1[h], qa[h][0], qa[h][1], Pk[GB_[h]][0], Pk[GB_[h]][1], Pk[9 + GA_[h]][0], Pk[9 + GB_[h]][0]);
          mma16(S2[h], qa[h][0], qa[h][1], Pk[GB_[h]][0], Pk[GB_[h]][1], Pk[9 + GA_[h]][1], Pk[9 + GB_[h]][1]);
        }
#pragma unroll
        for (int h = 0; h < 4; h++) {
          mma8(S1[h], qc[h][0], qc[h][1], Pk[9 + GC_[h]][0]);
          mma8(S2[h], qc[h][0], qc[h][1], Pk[9 + GC_[h]][1]);
        }
        uint32_t V1[9], V2[9];
#pragma unroll
        for (int i = 0; i < 9; i++) { V1[i] = movm(Pk[18 + i][0]); V2[i] = movm(Pk[18 + i][1]); }
        uint4 hv[6];
        auto look = [&]() {
          if (w) mbar_wait_c(bars + B_HOLD, L);
#pragma unroll
          for (int i = 0; i < 6; i++) hv[i] = ll_ld128g(hs + i * 512);
        };
        const uint32_t mup = (up0 ? 0xffffu : 0u) | (up1 ? 0xffff0000u : 0u);
        auto finish = [&](const float (&x0)[4], const float (&x1)[4], const uint32_t (&Vb)[9], uint32_t ma, int hi) {
          uint32_t p[4], n[4];
          float rs[4];
#pragma unroll
          for (int h = 0; h < 4; h++) {
            const float m = qmax(fmaxf(x0[h], x1[h])), e0 = ex2(x0[h] - m), e1 = ex2(x1[h] - m);
            n[h] = pack2(e0, e1);
            p[h] = pack2(e0 * rk[hi][0], e1 * rk[hi][1]);
          }
          if (hi) look();
#pragma unroll
          for (int h = 0; h < 4; h += 2) {
            float D[4] = {0.f, 0.f, 0.f, 0.f};
            mma8(D, n[h], n[h + 1], 0x3f803f80u);
            rs[h] = rcp_fast(D[0]); rs[h + 1] = rcp_fast(D[2]);
          }
#pragma unroll
          for (int i = 0; i < 9; i++) {
            const int h = i < 4 ? 0 : i == 4 ? 1 : 2;
            const bool nx = (i == 2 || i == 4 || i == 6) ? 2 * t >= i : i == 3 || i > 6;
            float O[4] = {0.f, 0.f, 0.f, 0.f};
            mma16(O, p[h] & ma, p[h + 1] & ma, p[h] & ~ma, p[h + 1] & ~ma, V1[i], Vb[i]);
            const float r = nx ? rs[h + 1] : rs[h];
            stg32(od + i * 1024 + hi * 256, pack2((nx ? O[2] : O[0]) * r, (nx ? O[3] : O[1]) * r));
          }
        };
        {
          float x0[4], x1[4];
#pragma unroll
          for (int h = 0; h < 4; h++) { x0[h] = (up0 ? S1[h][2] : S2[h][2]) * sc[1][0]; x1[h] = (up1 ? S1[h][3] : S2[h][3]) * sc[1][1]; }
          finish(x0, x1, V2, mup, 1);
        }
        ACLK(2);
        if (lane + w == 0) mbar_arrive(bars + B_HOLD);
        bar_sync(1 + w, 256 - 128 * w);
#pragma unroll 1
        for (int it = 0; it < (1 << 20); it++) {
          if (remote) {
            bool ok = true;
#pragma unroll
            for (int i = 0; i < 6; i++) ok = ok && hv[i].z == tag;
            if (__all_sync(~0u, ok)) break;
          }
#pragma unroll
          for (int i = 0; i < 6; i++) hv[i] = ll_ld128g(hs + i * 512);
          if (!remote) break;
        }
        uint32_t H[18];
#pragma unroll
        for (int i = 0; i < 6; i++) { H[HA_[i]] = hv[i].x; H[HA_[i] + 1] = hv[i].y; H[HC_[i]] = hv[i].w; }
        float S0[4][4];
#pragma unroll
        for (int h = 0; h < 4; h++) {
#pragma unroll
          for (int i = 0; i < 4; i++) S0[h][i] = 0.f;
          mma16(S0[h], qa[h][0], qa[h][1], Pk[GB_[h]][0], Pk[GB_[h]][1], H[GA_[h]], H[GB_[h]]);
        }
#pragma unroll
        for (int h = 0; h < 4; h++) mma8(S0[h], qc[h][0], qc[h][1], H[GC_[h]]);
        uint32_t V0[9];
#pragma unroll
        for (int i = 0; i < 9; i++) V0[i] = movm(H[9 + i]);
        ACLK(3);
        {
          const bool nohalo = (rb | pq) == 0;
          const float b0 = up0 && nohalo ? -INFINITY : 0.f, b1 = up1 && nohalo ? -INFINITY : 0.f;
          float x0[4], x1[4];
#pragma unroll
          for (int h = 0; h < 4; h++) { x0[h] = fmaf(up0 ? S0[h][0] : S1[h][0], sc[0][0], b0); x1[h] = fmaf(up1 ? S0[h][1] : S1[h][1], sc[0][1], b1); }
          finish(x0, x1, V0, ~mup, 0);
        }
        ACLK(4);
        signal(EV_O);
        ACLK_OUT;
        TRC(tr, w, tb + 2);
      }
      if (c.s) { c.s = 0; c.ph ^= 1; }
      PHASE;
      {
        float acc[36];
        const int hw = rb * 2 + w;
        const uint32_t xt = stg + (8 * q + g) * 144 + t * 4;
        uint32_t xm = sb + SM_STG + 9216 + (8 * q + (lane & 7)) * 144 + (lane & 8) * 576 + (lane & 16);
        uint8_t* xn = xn_block(hw) + j * 9216 + q * 256 + lane * 4;
        uint32_t* sp = (uint32_t*)(Q.ST1 + (hw * 8 + j) * 32 + 8 * q) + lane;
        const uint4* sg = Q.ST1 + (hw * 8 + t) * 32 + 8 * q + g;
        asm volatile("" : "+r"(xm), "+l"(xn), "+l"(sp), "+l"(sg));
        mbar_wait_c(bars + B_RES + w * 8, L);
        TRC(tr, w, tb + 21);
#pragma unroll
        for (int i = 0; i < 18; i++) { const uint32_t x = lds32(xt + (i >> 1) * 16 + (i & 1) * 4608); acc[2 * i] = blo(x); acc[2 * i + 1] = bhi(x); asm volatile("" : "+f"(acc[2 * i]), "+f"(acc[2 * i + 1])); }
        mbar_wait_c(bars + B_WF, L);
        const uint32_t db = dlo(sb, 1152), of = bars + (w ? B_OF + 40 : B_AV + 96);
        uint32_t da[5];
#pragma unroll
        for (int e = 0; e < 5; e++) da[e] = __shfl_sync(~0u, dlo(sb + o_place(w, e), 1024), 0);
        if (w) {
#pragma unroll 1
          for (int kb = q; kb < 9; kb += 4) {
            const uint32_t e = (kb + 1) >> 1;
            mbar_wait_c(bars + B_OF + e * 8, L);
            check(Int<8>{}, sb + o_place(0, e) + (kb && !(kb & 1)) * 8192, z1_block(rb, 0, 0) + kb * 8192);
            if (lane <= !kb) mbar_arrive(bars + B_AV + (12 + e) * 8);
          }
          bar_sync(7, 256);
        }
        mbar_wait_c(of, L & w);
        TRC(tr, w, tb + 3);
        wgmma_fence();
#pragma unroll
        for (int kk = 0; kk < 4; kk++) wgmma_ss_n72(acc, dsc<128, 0>(da[0], kk * 2048), dsc<128, 0>(db, kk * 2304), 1);
        wgmma_commit();
#pragma unroll 1
        for (int h = 0; h < 2; h++) {
#pragma unroll
          for (int u = 0; u < 4; u++) {
            if (!(u & 1)) { mbar_wait_c(of + 8 + h * 16 + u * 4, 1 + 2 * h + (u >> 1) < SPL ? L & w : L); wgmma_fence(); }
            if (u == 3 && h && !w) bar_arrive(7, 256);
#pragma unroll
            for (int kk = 0; kk < 4; kk++) wgmma_ss_n72(acc, dsc<128, 0>(da[1 + (u >> 1)], (u & 1) * 8192 + kk * 2048), dsc<128, 0>(db + h * 2304, (1 + u) * 9216 + kk * 2304), 1);
            if (u != 2) wgmma_commit();
            if (u == 0) { wgmma_wait<1>(); if (lane + w == 0 && h) mbar_arrive(bars + B_X3); }
          }
          da[1] = da[3]; da[2] = da[4];
        }
        RCLK_INIT;
        wgmma_wait<0>();
        RCLK(0);
        if (lane < 2) mbar_arrive_cluster(ebar + B_XD - B_EMPTY + w * 8);
        TRC(tr && P5TRACE != 5, w, tb + 4);
        {
          float s0 = 0.f, s1 = 0.f, q0 = 0.f, q1 = 0.f;
#pragma unroll
          for (int i = 0; i < 36; i++) {
            if (i & 2) { s1 += acc[i]; q1 = fmaf(acc[i], acc[i], q1); } else { s0 += acc[i]; q0 = fmaf(acc[i], acc[i], q0); }
          }
          const bool o1 = t & 1, o2 = t & 2;
          const float ss = (o1 ? s1 : s0) + __shfl_xor_sync(~0u, o1 ? s0 : s1, 1), sq = (o1 ? q1 : q0) + __shfl_xor_sync(~0u, o1 ? q0 : q1, 1);
          const float v = (o2 ? sq : ss) + __shfl_xor_sync(~0u, o2 ? ss : sq, 2);
          asm volatile("st.relaxed.gpu.global.u32 [%0], %1;" ::"l"(sp), "r"(__float_as_uint(v)) : "memory");
        }
        RCLK(1);
        RCLK(2);
        pause<PDEL>(Q.zero);
        uint4 pa, pb;
        auto there = [&](const uint4& a, const uint4& b) { return __all_sync(~0u, max(max(max(a.x, a.y), max(a.z, a.w)), max(max(b.x, b.y), max(b.z, b.w))) != ~0u); };
#pragma unroll 1
        for (int it = 0; it < (1 << 20); it++) {
          pa = ll_ld128(sg); pb = ll_ld128(sg + 128);
          if (there(pa, pb)) break;
        }
        RCLK(3);
        float mean0 = qsum(__uint_as_float(pa.x) + __uint_as_float(pb.x)) * (-1.f / DM), mean1 = qsum(__uint_as_float(pa.y) + __uint_as_float(pb.y)) * (-1.f / DM);
        const float rs0 = GA * rsq_fast(fmaxf(fmaf(qsum(__uint_as_float(pa.z) + __uint_as_float(pb.z)), 1.f / DM, -mean0 * mean0), 0.f) + LN_EPS);
        const float rs1 = GA * rsq_fast(fmaxf(fmaf(qsum(__uint_as_float(pa.w) + __uint_as_float(pb.w)), 1.f / DM, -mean1 * mean1), 0.f) + LN_EPS);
        mean0 *= rs0; mean1 *= rs1;
#pragma unroll
        for (int i = 0; i < 18; i++) {
          const float a = (i & 1) ? rs1 : rs0, b = (i & 1) ? mean1 : mean0;
          stg32(xn + (i >> 1) * 1024 + (i & 1) * 128, pack2(fmaf(acc[2 * i], a, b), fmaf(acc[2 * i + 1], a, b)));
        }
        signal(EV_X1);
        RCLK(4);
        if (w) {
#pragma unroll 1
          for (int u = q; u < 24; u += 4) {
            const uint32_t mb = u < 2 * SPL ? u >= SPL : u & 1, k = u < 2 * SPL ? u - mb * SPL : u >> 1;
            mbar_wait_c(bars + B_AF3 + mb * 96 + k * 8, L);
            SCLK3(u);
            check(Int<6>{}, sb + k * 12288 + mb * 6144, xn_block(rb * 2 + mb) + k * 6144);
            SCLK3(24 + u);
            if (lane <= (u < 2 * SPL)) mbar_arrive(bars + B_AV + (u < SPL ? 12 + k : k) * 8);
          }
          TRVI(lane == 0 && P5TRACE != 5, 5, 56 + L * 4 + q, rp);
          mbar_wait_c(bars + B_S5, 0);
        }
#pragma unroll
        for (int u = 0; u < 4; u++)
          stsm4(xm + u * 32, pack2(acc[8 * u], acc[8 * u + 1]), pack2(acc[8 * u + 2], acc[8 * u + 3]), pack2(acc[8 * u + 4], acc[8 * u + 5]), pack2(acc[8 * u + 6], acc[8 * u + 7]));
        asm volatile("stmatrix.sync.aligned.m8n8.x2.shared.b16 [%0], {%1,%2};" ::"r"(xm + 128), "r"(pack2(acc[32], acc[33])), "r"(pack2(acc[34], acc[35])) : "memory");
        fence_async_s();
        signal(EV_XS);
        RCLK(5);
        TRC(tr, w, tb + 5);
        RCLK(6);
        RCLK_OUT;
      }
      PHASE;
      {
      float acc[160];
#pragma unroll
      for (int i = 0; i < 160; i++) acc[i] = 0.f;
      float s[2] = {0.f, 0.f}, qq[2] = {0.f, 0.f}, zo = 0.f;
      const uint32_t zp = sb + SM_ZP3 + (tid & 127) * 4;
      auto zstat = [&](int mb, bool on) {
        const bool o1 = t & 1, o2 = t & 2;
        const float ss = ((o1 ? s[1] : s[0]) + __shfl_xor_sync(~0u, o1 ? s[0] : s[1], 1)) * 0x1p60f, sq = (o1 ? qq[1] : qq[0]) + __shfl_xor_sync(~0u, o1 ? qq[0] : qq[1], 1);
        const uint32_t v = __float_as_uint((o2 ? sq : ss) + zo + __shfl_xor_sync(~0u, o2 ? ss : sq, 2));
        asm volatile("{\n.reg .pred p, q, r;\nsetp.eq.u32 p, %4, 1;\nsetp.eq.u32 q, %4, 2;\nsetp.eq.and.u32 r, %5, 0, q;\n@p st.shared.u32 [%0], %2;\n@p bar.arrive 13, 256;\n"
                     "@q st.relaxed.gpu.global.u32 [%1], %2;\n@r mbarrier.arrive.shared::cta.b64 _, [%3];\n}" ::"r"(zp + mb * 512), "l"((uint32_t*)(Q.ZST + ((rb * 2 + mb) * 8 + j) * 32) + (tid & 127)),
                     "r"(v), "r"(bars + B_ZS + mb * 8), "r"(on ? 1 + w : 0), "r"(lane) : "memory");
        s[0] = s[1] = qq[0] = qq[1] = 0.f;
      };
      const uint32_t ebar3 = ebar + (B_E3 - B_EMPTY);
#pragma unroll 1
      for (int half = 0; half < 2; half++) {
        const bool big = half != w;
        auto rel3 = [&](int p) { if (lane < 2) mbar_arrive_cluster(ebar3 + p * 8); };
        auto pass = [&](auto nk) {
          constexpr int NK = nk.value;
          uint32_t d0 = dlo(sb, 1024), ph = half & ~w, af = bars + B_AV;
          const uint32_t db = dlo(sb + SM_B3, NK == 3 ? 6144 : 2048);
          const bool lead = NK == 3 && !half;
          if (lead) {
#pragma unroll
            for (int u = 0; u < 2 * SPL; u++) {
              const int mb = u / SPL, p = u % SPL;
              if (!mb) mbar_wait_c(bars + B_F3 + p * 8, 0);
              mbar_wait_c(af + (mb ? p : 12 + p) * 8, mb || p > 4 ? L : 1);
              TRC(tr && u == 0, w, tb + 6);
              SCLK2(u);
              if (p == 0) SCLK(mb * 4);
              wgmma_fence();
#pragma unroll
              for (int kk = 0; kk < 3; kk++) {
                wgmma_ss_n128(acc + mb * 80, dsc<128, 0>(d0, p * 12288 + kk * 2048 + mb * 6144), dsc<1024, 1>(db, p * 12288 + kk * 2048), p + kk > 0);
                if (kk == 0 && u > SPL) { wgmma_commit(); wgmma_wait<1>(); rel3(p - 1); }
              }
              wgmma_commit();
            }
          }
#pragma unroll 1
          for (int it = 0; it < 6 / NK; it++) {
#pragma unroll
            for (int p = 0; p < 6; p++) {
              if (p < SPL && lead && it == 0) continue;
              if (NK == 3) mbar_wait_c(af + p * 8, L);
              if (p == 0 && it == 0) bar_sync(6 + w, 256);
              mbar_wait_c(bars + B_F3 + p * 8, ph);
              TRC(tr && p == 0 && it == 0, w, tb + 6 + half * 4);
              if (lead) SCLK2(12 + it * 6 + p);
              if (NK == 2 ? !(p & 1) : p % 3 == 0) SCLK(half * 11 + (NK == 2 ? it * 3 + p / 2 : it * 2 + p / 3));
              wgmma_fence();
#pragma unroll
              for (int u = 0; u < 2 * NK; u++) {
                const int kk = u >> 1, mb = u & 1, e = p * NK + kk;
                const uint64_t da = dsc<128, 0>(d0, (e / 3) * 12288 + (e % 3) * 2048 + mb * 6144);
                if (NK == 3) wgmma_ss_n128(acc + mb * 80, da, dsc<1024, 1>(db, p * 12288 + kk * 2048), e > 0 || it > 0);
                else wgmma_ss_n160(acc + mb * 80, da, dsc<1024, 1>(db, p * 12288 + kk * 6144), e > 0 || it > 0);
                if (u == 0) { wgmma_commit(); wgmma_wait<1>(); if (p > 0 || it > 0) rel3((p + 5) % 6); }
                if (p * 8 + u == (NK == 2 ? HO3 : HO4) && it == 6 / NK - 1) bar_arrive(7 - w, 256);
              }
              wgmma_commit();
            }
            d0 += NK * 1536; af += 48;
            ph ^= 1;
          }
        };
        const int go = (j & 1) ? (big ? 0 : 20) : (big ? 16 : 0);
        const float* gbp = (const float*)(smem_raw + SM_OFF + 8);
        asm volatile("" : "+l"(gbp));
        uint8_t* zd = half ? z1_block(rb, 0, j) + go * 1024 + (q & 1) * 2048 + (q >> 1) * 512 + lane * 16 : z2_block(rb, j) + q * 9216 + go * 128 + ((g & 3) * 2 + (g >> 2)) * 16 + t * 4;
        asm volatile("" : "+l"(zd));
        if (big) pass(Int<2>{}); else pass(Int<3>{});
        if (w) { bar_sync(13, 256); zo = __uint_as_float(lds32(zp + half * 512)); }
        if (half) { zstat(1, true); mbar_wait_c(bars + B_S5, 1); }
        const uint32_t off2 = lds32(sb + SM_OFF);
        wgmma_wait<0>();
        SCLK(half * 11 + 9);
        rel3(5);
        TRC(tr, w, tb + 7 + half * 4);
        auto gelu = [&](auto z2) {
          float gate[NC2], gb = GB, gn = GB;
          uint32_t qa[2][3] = {{0, 0, 0}, {0, 0, 0}};
#pragma unroll
          for (int e = 0; e < NC2; e++) gate[e] = GB;
#pragma unroll
          for (int G = 0; G < 20; G++) {
            if (G == 16 && !big) break;
            if (z2.value && G % LD2 == 0) { gb = gn; if (G < 20 - LD2) asm volatile("ld.f32 %0, [%1];" : "=f"(gn) : "l"(gbp) : "memory"); }
#pragma unroll
            for (int r = 0; r < 2; r++) {
              float z[2];
              float& gt = gate[(G * 2 + r) % NC2];
#pragma unroll
              for (int e = 0; e < 2; e++) {
                const float v = acc[4 * G + 2 * r + e];
                z[e] = fmaf(v, tanh_fast(v * fmaf(v, v, gt)), v);
                if (z2.value) { s[r] = fmaf(z[e], 0x1p-60f, s[r]); qq[r] = fmaf(z[e], z[e], qq[r]); }
              }
              const uint32_t pk = pack2(z[0], z[1]);
              if (z2.value) {
                stg32(zd + G * 128 + r * 4608, hsub2(pk, off2));
                gt = fmaf(qq[r], s[r], gb);
              } else {
                if ((G & 3) == 3) stg128(zd + (G >> 2) * 4096 + r * 1024, qa[r][0], qa[r][1], qa[r][2], pk);
                else qa[r][G & 3] = pk;
              }
            }
          }
        };
#pragma unroll 1
        for (int mb = 0;; mb++) {
          if (half) gelu(Int<0>{}); else gelu(Int<1>{});
          if (mb) break;
          zstat(0, !half);
#pragma unroll
          for (int i = 0; i < 80; i++) acc[i] = acc[80 + i];
          zd += half ? 8 * ZB : 128 * ZB;
        }
        mbar_wait_c(bars + B_GATE3, L);
        signal(half ? EV_Z1 : EV_ZN);
        SCLK(half * 11 + 10);
        TRC(tr, w, tb + 8 + half * 4);
      }
      }
      PHASE;
      const uint32_t aoff = (pw * 64 + pq * 16 + (lane & 15)) * 128 + (((lane >> 4) ^ (lane & 7)) << 4);
      uint32_t hA[18][4];
      {
        float acc[144];
        {
          const uint32_t c16 = lds32(sb + SM_OFF + 12), a[4] = {c16, c16, c16, c16};
          wgmma_fence();
          wgmma_rs_n144(acc, a, dsc<0, 0>(dlo(sb + SM_CV + 512, 0), 0), 0);
          wgmma_rs_n144(acc + 72, a, dsc<0, 0>(dlo(sb + SM_CV + 512, 0), 128), 0);
          wgmma_commit();
        }
        uint32_t prev = 0;
        auto stage = [&](int kb, bool odd) {
          mbar_wait_c(bars + B_FULL + c.s * 8, c.ph);
          TRC(tr && kb == 0, w, tb + 13);
          SCLK(22 + kb);
          const uint32_t st = sb + c.s * ST_BYTES, db = dlo(st + ST_B, 4608), rt = sb + SM_RT + kb * 128 + t * 8;
          uint32_t a[4][4];
#pragma unroll
          for (int kk = 0; kk < 4; kk++) {
            uint32_t r[4];
            ldsm4(r, st + (aoff ^ (kk << 5)));
            const uint2 sc = lds64(rt + kk * 32);
            a[kk][0] = hmul2(__byte_perm(r[0], r[2], 0x5410), sc.x); a[kk][2] = hmul2(__byte_perm(r[0], r[2], 0x7632), sc.y);
            a[kk][1] = hmul2(__byte_perm(r[1], r[3], 0x5410), sc.x); a[kk][3] = hmul2(__byte_perm(r[1], r[3], 0x7632), sc.y);
          }
          if (!odd && kb + w == 0) bar_sync(6, 256);
          wgmma_fence();
#pragma unroll
          for (int i = 0; i < 8; i++) {
            const int kk = i & 3, hf = i >> 2;
            wgmma_rs_n144(acc + hf * 72, a[kk], dsc<128, 0>(db, kk * 9216 + hf * 2304), 1);
            if (i == 0) { wgmma_commit(); wgmma_wait<1>(); if (kb) release(prev); }
            if (i == 3) wgmma_commit();
          }
          wgmma_commit();
          prev = c.s; c.next();
        };
#pragma unroll 1
        for (int kb = 0; kb < 32; kb += 2) {
          if (!(kb & 7)) mbar_wait_c(bars + B_RT + kb, L);
          stage(kb, false);
          stage(kb + 1, true);
        }
        mbar_wait_c(bars + B_CV + pw * 8, L);
        const float gk = 0.5f / GA;
        const float c1 = __uint_as_float(lds32(sb + SM_OFF + 4));
        const float gb0 = -gk * (c1 + __uint_as_float(lds32(sb + SM_CV + pw * 256 + (16 * pq + g) * 4))), gb1 = -gk * (c1 + __uint_as_float(lds32(sb + SM_CV + pw * 256 + (16 * pq + g + 8) * 4)));
        if (w == 1) { mbar_wait_c(bars + B_FULL + c.s * 8, c.ph); release(c.s); c.next(); }
        mbar_wait_c(bars + B_FULL + c.s * 8, c.ph);
        const uint32_t zs = sb + c.s * ST_BYTES + ST_B + (tid & 127) * 16;
        uint4 zl, zh;
#pragma unroll
        for (int u = 0; u < 18; u++) {
          if (u == 0) wgmma_wait<1>();
          if (u == 9) {
            wgmma_wait<0>();
            release(prev);
            if (L == 0) signal(EV_PT);
            TRC(tr, w, tb + 14);
            SCLK(54);
          }
          if (!(u & 1)) { zl = lds128(zs + u * 2048); zh = lds128(zs + u * 2048 + 2048); }
          const uint4 z = (u & 1) ? make_uint4(zl.z, zh.z, zl.w, zh.w) : make_uint4(zl.x, zh.x, zl.y, zh.y);
          hA[u][0] = hmul2(z.x, pack2(fmaf(acc[8 * u], gk, gb0), fmaf(acc[8 * u + 1], gk, gb0)));
          hA[u][1] = hmul2(z.y, pack2(fmaf(acc[8 * u + 2], gk, gb1), fmaf(acc[8 * u + 3], gk, gb1)));
          hA[u][2] = hmul2(z.z, pack2(fmaf(acc[8 * u + 4], gk, gb0), fmaf(acc[8 * u + 5], gk, gb0)));
          hA[u][3] = hmul2(z.w, pack2(fmaf(acc[8 * u + 6], gk, gb1), fmaf(acc[8 * u + 7], gk, gb1)));
        }
        __syncwarp();
        release(c.s);
        c.next();
        if (w == 0) { mbar_wait_c(bars + B_FULL + c.s * 8, c.ph); release(c.s); c.next(); }
        TRC(tr, w, tb + 15);
      }
      {
        CLK_INIT;
        if (w == 1) bar_arrive(6, 256);
        uint4 v[4];
#pragma unroll
        for (int u = 0; u < 4; u++) v[u] = make_uint4(0u, 0u, 0u, 0u);
        uint32_t rl = sb + SM_STG + pw * 8192 + pq * 2048 + (lane >> 3) * 128 + (((lane & 7) ^ (lane >> 3)) << 4);
        uint8_t* rd = Q.out + (128 * rb + 32 * pq + 2 * (lane >> 3) + pw) * (DM * 2) + j * 128 + (lane & 7) * 16;
        asm volatile("" : "+r"(rl), "+l"(rd));
        auto send = [&](int u0, int u1) {
#pragma unroll
          for (int u = u0; u < u1; u++)
            asm volatile("red.relaxed.gpu.global.add.noftz.v4.bf16x2 [%0], {%1,%2,%3,%4};" ::"l"(rd + u * (8 * DM * 2)), "r"(v[u].x), "r"(v[u].y), "r"(v[u].z), "r"(v[u].w) : "memory");
        };
#pragma unroll 1
        for (int p = 0; p < 9; p++) {
          float acc[32];
          CLK(0);
          mbar_wait_c(bars + B_FULL + c.s * 8, c.ph);
          const uint32_t db = dlo(sb + c.s * ST_BYTES + ST_B, 0);
          CLK(1);
          bar_sync(6 + w, 256);
          CLK(2);
          wgmma_fence();
#pragma unroll
          for (int kk = 0; kk < 18; kk++) {
            wgmma_rs_n64(acc, hA[kk], dsc<1024, 1>(db, kk * 2048), kk != 0);
            if (kk == PPK && (w == 0 || p < 8)) bar_arrive(7 - w, 256);
          }
          wgmma_commit();
          CLK(3);
          if (p > 0) { send(NOW, 4); rd += p + j == 9 ? -1024 : 128; }
          CLK(5);
          wgmma_wait<0>();
          CLK(4);
          if (L == 0 || p < 5) release(c.s);
          c.next();
          TRC(tr && p == 8, w, tb + 16);
#pragma unroll
          for (int u = 0; u < 4; u++)
            stsm4(sb + SM_STG + (aoff ^ (u << 5)), pack2(acc[8 * u], acc[8 * u + 1]), pack2(acc[8 * u + 2], acc[8 * u + 3]), pack2(acc[8 * u + 4], acc[8 * u + 5]), pack2(acc[8 * u + 6], acc[8 * u + 7]));
          __syncwarp();
#pragma unroll
          for (int u = 0; u < 4; u++) v[u] = lds128(rl + u * 512 ^ (u & 1) << 6);
          send(0, NOW);
        }
        send(NOW, 4);
        TRC(tr, w, tb + 17);
        if (L == 0) signal(EV_PT);
        CLK_OUT;
        TRC(tr, w, tb + 18);
      }
    }
    if ((tid & 127) == 0) Q.flags[(rb * 2 + w) * 32 + FR_EP + j] = epoch + 1;
    if (tid == 0) Q.flags[FJ + j * 32 + FJ_EP + rb] = epoch + 1;
  }
}

typedef CUresult (*EncodeFn)(CUtensorMap*, CUtensorMapDataType, cuuint32_t, void*, const cuuint64_t*, const cuuint64_t*, const cuuint32_t*,
                             const cuuint32_t*, CUtensorMapInterleave, CUtensorMapSwizzle, CUtensorMapL2promotion, CUtensorMapFloatOOBfill);

static void make_map(EncodeFn fn, CUtensorMap* m, const void* ptr, int rank, uint64_t d0, uint64_t d1, uint64_t d2, uint64_t s1, uint64_t s2,
                     uint32_t b0, uint32_t b1, uint32_t b2, CUtensorMapSwizzle swz) {
  cuuint64_t dims[3] = {d0, d1, d2}, strides[2] = {s1, s2};
  cuuint32_t box[3] = {b0, b1, b2}, es[3] = {1, 1, 1};
  fn(m, CU_TENSOR_MAP_DATA_TYPE_BFLOAT16, rank, const_cast<void*>(ptr), dims, strides, box, es, CU_TENSOR_MAP_INTERLEAVE_NONE, swz,
     CU_TENSOR_MAP_L2_PROMOTION_L2_128B, CU_TENSOR_MAP_FLOAT_OOB_FILL_NONE);
}

}

extern "C" void kernel_launch(void* const* d_in, const int* in_sizes, int n_in, void* d_out, int out_size) {
  using namespace mk;
  (void)in_sizes; (void)n_in; (void)out_size;
  static EncodeFn fn = nullptr;
  static Scratch* sc = nullptr;
  if (!fn) {
    cudaDriverEntryPointQueryResult qr;
    cudaGetDriverEntryPoint("cuTensorMapEncodeTiled", (void**)&fn, cudaEnableDefault, &qr);
    cudaGetSymbolAddress((void**)&sc, g_scratch);
    cudaFuncSetAttribute(mega_kernel, cudaFuncAttributeMaxDynamicSharedMemorySize, SM_TOTAL);
  }
  Params p;
  Ptrs a;
  a.x = (const uint8_t*)d_in[0];
  a.wqkv = (const __nv_bfloat16*)d_in[1];
  a.wo = (const __nv_bfloat16*)d_in[2];
  a.w_in = (const __nv_bfloat16*)d_in[4];
  a.w_sp = (const __nv_bfloat16*)d_in[5];
  a.b_sp = (const __nv_bfloat16*)d_in[6];
  a.out = (uint8_t*)d_out;
  a.zero = 0;
  a.WQ = sc->WQ; a.flags = sc->flags; a.CSP = sc->CSP; a.XST = sc->XST; a.HALO = sc->HALO; a.ST1 = sc->ST1; a.ZST = sc->ZST; a.RT = sc->RT; a.Z = sc->Z; a.WO = sc->WO;
  make_map(fn, &p.wsp, a.w_sp, 3, 2048, 1024, 2, 8192, 4096, 64, 64, 2, CU_TENSOR_MAP_SWIZZLE_128B);
  for (int i = 0; i < 2; i++) {
    make_map(fn, &p.act[i], i ? a.out : a.x, 3, DM, 1024, 2, 2304, 1152, 64, 32, 2, CU_TENSOR_MAP_SWIZZLE_128B);
    make_map(fn, &p.res[i], i ? a.out : a.x, 3, DM, 1024, 2, 2304, 1152, 72, 32, 2, CU_TENSOR_MAP_SWIZZLE_NONE);
  }
  for (int i = 0; i < 2; i++) make_map(fn, &p.winb[i], a.w_in + 32 * i, 3, 64, 576, 72 - i, 9216, 128, 64, 16, 3, CU_TENSOR_MAP_SWIZZLE_128B);
  make_map(fn, &p.wins, a.w_in, 3, 64, 576, 72, 9216, 128, 64, 48, 1, CU_TENSOR_MAP_SWIZZLE_128B);
  make_map(fn, &p.wout, d_in[7], 2, 576, 2304, 1, 1152, 0, 64, 144, 1, CU_TENSOR_MAP_SWIZZLE_128B);
  mega_kernel<<<NGRID, 384, SM_TOTAL, cudaStreamPerThread>>>(a, p);
}
```

```cpp
#include <cuda_runtime.h>
#include <cuda.h>
#include <cuda_bf16.h>
#include <stdint.h>

#define MK_TRACE 0
#define MK_DBG 0
#define P5TRACE 0

#define C0S 32.f
#define OFM 0x10u
#define NC2 2
#define LD2 2
#define PDEL 8
#define SDEL 10
#define ZD1 8
#define ZD2 20
#define FD3 14
#define YPACE 2
#define SPL 4
#define XP0 8
#define APACE 7
#define AEP 2
#define PZI 4
#define RFI 3
#define KS 1
#define XK1 1
#define XK2 2
#define HO3 41
#define HO4 41
#define PPK 17
#define NOW 3
#define WTI 12
#define EFM 0x22333022
#define EF(i) ((((EFM >> (4 * (i))) & 3) == 3) || (((EFM >> (4 * (i))) >> L) & 1))

namespace mk {

constexpr int SEQ = 2048, DM = 576, FH = 2304;
constexpr int NCTA = 128;
constexpr int NGRID = 132;
constexpr uint32_t ZB = 36864;
constexpr uint32_t WQ_SL = 72 * 3456;
constexpr uint32_t WO_SL = 72 * 1152;
constexpr float LN_EPS = 1e-5f;
constexpr float GA = 0.3292034911525734f, GB = 2.423681954311584f;

constexpr uint32_t ST_BYTES = 53248, ST_B = 16384, NST = 4;
constexpr uint32_t SM_STG = NST * ST_BYTES;
constexpr uint32_t SM_BAR = SM_STG + 2 * 9216, B_OFF = 896;
constexpr uint32_t SM_OFF = SM_BAR + B_OFF;
constexpr uint32_t SM_TOTAL = SM_BAR + 1024;
constexpr uint32_t SM_RT = SM_STG + 9216, SM_CV = SM_STG + 17408, SM_WT = SM_STG;
constexpr uint32_t SM_WOI = 44032, SM_CSQ = 49280, SM_XST = 50176;
enum { EV_PT = 0, EV_O = 1, EV_X1 = 2, EV_ZN = 3, EV_Z1 = 4, EV_XS = 5, EV_N = 6 };
constexpr uint32_t B_FULL = 0, B_FULLA = 32, B_RES = 96, B_WT = 112, B_GATE3 = 128, B_Z1 = 136, B_ZOK = 144, B_CV = 152, B_XRW = 168, B_F3 = 184, B_WF = 232, B_OF = 240,
                   B_RT = 320, B_AF3 = 352, B_RB = 544,
                   B_AD = 576, B_S5 = 608, B_AV = 616, B_CSQ = 760,
                   B_HOLD = 768, B_X3 = 776, B_ZS = 784, B_EVT = 800,
                   B_IMG = 912, B_WOI = 920, B_E3 = 928, B_XD = 976,
                   B_EMPTY = 992;
constexpr uint32_t SM_B3 = 9 * 16384, SM_ZP3 = SM_STG + 8192;

enum { FR_X2 = 0, FR_O = 1, FR_XR = 5, FR_OL = 7, FR_PZ = 9, FR_EP = 16, FJ = 32 * 32, FJ_WQ = 0, FJ_WO = 1, FJ_ZN = 3, FJ_P4 = 5, FJ_EP = 16, F_N = FJ + 8 * 32 };

struct Scratch {
  alignas(1024) uint32_t flags[F_N];
  alignas(1024) float CSP[2 * NCTA * 216];
  alignas(1024) uint2 RT[SEQ];
  alignas(1024) uint4 XST[2 * SEQ];
  alignas(1024) uint4 ST1[SEQ * 4];
  alignas(1024) uint4 ZST[SEQ * 4];
  alignas(1024) uint4 HALO[32 * 8 * 6 * 32];
  alignas(1024) uint8_t WO[8 * WO_SL];
  alignas(1024) uint8_t WQ[8 * WQ_SL];
  alignas(1024) uint8_t Z[512 * ZB];
};
__device__ Scratch g_scratch;

struct Ptrs {
  const __nv_bfloat16* wqkv;
  uint8_t* WQ;
  uint32_t* flags;
  float* CSP;
  const uint8_t* x;
  uint32_t zero;
  uint4 *XST, *HALO, *ST1, *ZST;
  uint2* RT;
  uint8_t *Z, *WO, *out;
  const __nv_bfloat16 *wo, *w_in, *w_sp, *b_sp;
};
struct Params {
  CUtensorMap wsp, winb[2], wins, wout;
  CUtensorMap act[2];
  CUtensorMap res[2];
};

__device__ __forceinline__ uint32_t smem_u32(const void* p) { return (uint32_t)__cvta_generic_to_shared(p); }
__device__ __forceinline__ void mbar_init(uint32_t bar, uint32_t cnt) { asm volatile("mbarrier.init.shared::cta.b64 [%0], %1;" ::"r"(bar), "r"(cnt)); }
__device__ __forceinline__ void mbar_arrive(uint32_t bar) { asm volatile("mbarrier.arrive.shared::cta.b64 _, [%0];" ::"r"(bar) : "memory"); }
__device__ __forceinline__ void mbar_wait(uint32_t bar, uint32_t parity) {
  asm volatile(
      "{\n.reg .pred p;\n.reg .u32 c;\nmov.u32 c, 0;\nLAB_WAIT:\n"
      "mbarrier.try_wait.parity.shared::cta.b64 p, [%0], %1;\n@p bra LAB_DONE;\n"
      "add.u32 c, c, 1;\nsetp.lt.u32 p, c, 0x100000;\n@p bra LAB_WAIT;\ntrap;\nLAB_DONE:\n}" ::"r"(bar), "r"(parity)
      : "memory");
}
__device__ __forceinline__ void mbar_wait_c(uint32_t bar, uint32_t parity) {
  asm volatile("{\n.reg .pred p;\nLAB_WAIT:\nmbarrier.try_wait.parity.shared::cta.b64 p, [%0], %1;\n@!p bra LAB_WAIT;\n}" ::"r"(bar), "r"(parity) : "memory");
}
__device__ __forceinline__ void flag_wait(const uint32_t* f, uint32_t target) {
  asm volatile(
      "{\n.reg .pred p;\n.reg .u32 c, v;\nmov.u32 c, 0;\nLAB_WAIT:\n"
      "ld.relaxed.gpu.global.u32 v, [%0];\nsub.u32 v, v, %1;\nsetp.ge.s32 p, v, 0;\n@p bra LAB_DONE;\n"
      "add.u32 c, c, 1;\nsetp.lt.u32 p, c, 0x400000;\n@p bra LAB_WAIT;\ntrap;\nLAB_DONE:\nfence.acquire.gpu;\n}" ::"l"(f), "r"(target)
      : "memory");
}
__device__ __forceinline__ void fence_gpu() { asm volatile("fence.acq_rel.gpu;" ::: "memory"); }
__device__ __forceinline__ void fence_async_g() { asm volatile("fence.proxy.async.global;" ::: "memory"); }
__device__ __forceinline__ void fence_async_s() { asm volatile("fence.proxy.async.shared::cta;" ::: "memory"); }
__device__ __forceinline__ uint32_t elect_one() {
  uint32_t p; asm volatile("{\n.reg .pred P;\nelect.sync _|P, 0xffffffff;\nselp.u32 %0, 1, 0, P;\n}" : "=r"(p)); return p;
}
__device__ __forceinline__ void expect_tx_p(uint32_t el, uint32_t bar, uint32_t bytes) {
  asm volatile("{\n.reg .pred P;\nsetp.ne.u32 P, %2, 0;\n@P mbarrier.arrive.expect_tx.shared::cta.b64 _, [%0], %1;\n}" ::"r"(bar), "r"(bytes), "r"(el) : "memory");
}
__device__ __forceinline__ void bulk_load_p(uint32_t el, uint32_t dst, const void* src, uint32_t bytes, uint32_t bar) {
  asm volatile("{\n.reg .pred P;\nsetp.ne.u32 P, %4, 0;\n@P cp.async.bulk.shared::cluster.global.mbarrier::complete_tx::bytes [%0], [%1], %2, [%3];\n}" ::"r"(dst), "l"(src), "r"(bytes), "r"(bar), "r"(el) : "memory");
}
__device__ __forceinline__ uint64_t policy_evict_first() { uint64_t p; asm("createpolicy.fractional.L2::evict_first.b64 %0, 1.0;" : "=l"(p)); return p; }
__device__ __forceinline__ void bulk_load_h(uint32_t el, uint32_t dst, const void* src, uint32_t bytes, uint32_t bar, bool ef, uint64_t pol) {
  if (ef) {
    asm volatile("{\n.reg .pred P;\nsetp.ne.u32 P, %4, 0;\n@P cp.async.bulk.shared::cluster.global.mbarrier::complete_tx::bytes.L2::cache_hint [%0], [%1], %2, [%3], %5;\n}" ::"r"(dst), "l"(src), "r"(bytes), "r"(bar), "r"(el), "l"(pol) : "memory");
  } else {
    asm volatile("{\n.reg .pred P;\nsetp.ne.u32 P, %4, 0;\n@P cp.async.bulk.shared::cluster.global.mbarrier::complete_tx::bytes [%0], [%1], %2, [%3];\n}" ::"r"(dst), "l"(src), "r"(bytes), "r"(bar), "r"(el) : "memory");
  }
}
__device__ __forceinline__ void bulk_mc_h(uint32_t el, uint32_t dst, const void* src, uint32_t bytes, uint32_t bar, bool ef, uint64_t pol) {
  if (ef) {
    asm volatile("{\n.reg .pred P;\nsetp.ne.u32 P, %4, 0;\n@P cp.async.bulk.shared::cluster.global.mbarrier::complete_tx::bytes.multicast::cluster.L2::cache_hint [%0], [%1], %2, [%3], %5, %6;\n}" ::"r"(dst), "l"(src), "r"(bytes), "r"(bar), "r"(el), "h"((uint16_t)3), "l"(pol) : "memory");
  } else {
    asm volatile("{\n.reg .pred P;\nsetp.ne.u32 P, %4, 0;\n@P cp.async.bulk.shared::cluster.global.mbarrier::complete_tx::bytes.multicast::cluster [%0], [%1], %2, [%3], %5;\n}" ::"r"(dst), "l"(src), "r"(bytes), "r"(bar), "r"(el), "h"((uint16_t)3) : "memory");
  }
}
__device__ __forceinline__ void tma3d_h(uint32_t el, uint32_t dst, const CUtensorMap* m, int c0, int c1, int c2, uint32_t bar, bool ef, uint64_t pol) {
  if (ef) {
    asm volatile("{\n.reg .pred P;\nsetp.ne.u32 P, %6, 0;\n@P cp.async.bulk.tensor.3d.shared::cluster.global.mbarrier::complete_tx::bytes.L2::cache_hint [%0], [%1, {%3, %4, %5}], [%2], %7;\n}" ::"r"(dst), "l"(m), "r"(bar), "r"(c0), "r"(c1), "r"(c2), "r"(el), "l"(pol) : "memory");
  } else {
    asm volatile("{\n.reg .pred P;\nsetp.ne.u32 P, %6, 0;\n@P cp.async.bulk.tensor.3d.shared::cluster.global.mbarrier::complete_tx::bytes [%0], [%1, {%3, %4, %5}], [%2];\n}" ::"r"(dst), "l"(m), "r"(bar), "r"(c0), "r"(c1), "r"(c2), "r"(el) : "memory");
  }
}
__device__ __forceinline__ void tma2d_mc_h(uint32_t el, uint32_t dst, const CUtensorMap* m, int c0, int c1, uint32_t bar, bool ef, uint64_t pol) {
  if (ef) {
    asm volatile("{\n.reg .pred P;\nsetp.ne.u32 P, %5, 0;\n@P cp.async.bulk.tensor.2d.shared::cluster.global.mbarrier::complete_tx::bytes.multicast::cluster.L2::cache_hint [%0], [%1, {%3, %4}], [%2], %6, %7;\n}" ::"r"(dst), "l"(m), "r"(bar), "r"(c0), "r"(c1), "r"(el), "h"((uint16_t)3), "l"(pol) : "memory");
  } else {
    asm volatile("{\n.reg .pred P;\nsetp.ne.u32 P, %5, 0;\n@P cp.async.bulk.tensor.2d.shared::cluster.global.mbarrier::complete_tx::bytes.multicast::cluster [%0], [%1, {%3, %4}], [%2], %6;\n}" ::"r"(dst), "l"(m), "r"(bar), "r"(c0), "r"(c1), "r"(el), "h"((uint16_t)3) : "memory");
  }
}
__device__ __forceinline__ void tma3d_mc_h(uint32_t el, uint32_t dst, const CUtensorMap* m, int c0, int c1, int c2, uint32_t bar, bool ef, uint64_t pol) {
  if (ef) {
    asm volatile("{\n.reg .pred P;\nsetp.ne.u32 P, %6, 0;\n@P cp.async.bulk.tensor.3d.shared::cluster.global.mbarrier::complete_tx::bytes.multicast::cluster.L2::cache_hint [%0], [%1, {%3, %4, %5}], [%2], %7, %8;\n}" ::"r"(dst), "l"(m), "r"(bar), "r"(c0), "r"(c1), "r"(c2), "r"(el), "h"((uint16_t)3), "l"(pol) : "memory");
  } else {
    asm volatile("{\n.reg .pred P;\nsetp.ne.u32 P, %6, 0;\n@P cp.async.bulk.tensor.3d.shared::cluster.global.mbarrier::complete_tx::bytes.multicast::cluster [%0], [%1, {%3, %4, %5}], [%2], %7;\n}" ::"r"(dst), "l"(m), "r"(bar), "r"(c0), "r"(c1), "r"(c2), "r"(el), "h"((uint16_t)3) : "memory");
  }
}
__device__ __forceinline__ void mbar_arrive_cluster(uint32_t addr) { asm volatile("mbarrier.arrive.shared::cluster.b64 _, [%0];" ::"r"(addr) : "memory"); }
__device__ __forceinline__ uint32_t mapa(uint32_t addr, uint32_t rank) { uint32_t r; asm("mapa.shared::cluster.u32 %0, %1, %2;" : "=r"(r) : "r"(addr), "r"(rank)); return r; }
__device__ __forceinline__ void bulk_store_p(uint32_t el, void* dst, uint32_t src, uint32_t bytes) {
  asm volatile("{\n.reg .pred P;\nsetp.ne.u32 P, %3, 0;\n@P cp.async.bulk.global.shared::cta.bulk_group [%0], [%1], %2;\n}" ::"l"(dst), "r"(src), "r"(bytes), "r"(el) : "memory");
}
__device__ __forceinline__ void flag_release_p(uint32_t el, uint32_t* f) {
  asm volatile("{\n.reg .pred P;\nsetp.ne.u32 P, %1, 0;\nfence.proxy.async;\n@P red.relaxed.gpu.global.add.u32 [%0], 1;\n}" ::"l"(f), "r"(el) : "memory");
}
__device__ __forceinline__ void flag_add_p(uint32_t el, uint32_t* f) {
  asm volatile("{\n.reg .pred P;\nsetp.ne.u32 P, %1, 0;\n@P red.relaxed.gpu.global.add.u32 [%0], 1;\n}" ::"l"(f), "r"(el) : "memory");
}
__device__ __forceinline__ void prefetch_l2(const void* src, uint32_t bytes) { asm volatile("cp.async.bulk.prefetch.L2.global [%0], %1;" ::"l"(src), "r"(bytes) : "memory"); }
__device__ __forceinline__ void prefetch_map(const CUtensorMap* m) { asm volatile("prefetch.tensormap [%0];" ::"l"(m) : "memory"); }
__device__ __forceinline__ void wgmma_fence() { asm volatile("wgmma.fence.sync.aligned;" ::: "memory"); }
__device__ __forceinline__ void wgmma_commit() { asm volatile("wgmma.commit_group.sync.aligned;" ::: "memory"); }
template <int N> __device__ __forceinline__ void wgmma_wait() { asm volatile("wgmma.wait_group.sync.aligned %0;" ::"n"(N) : "memory"); }
__device__ __forceinline__ uint32_t dlo(uint32_t addr, uint32_t lbo) { return ((addr & 0x3FFFF) >> 4) + ((lbo >> 4) << 16); }
template <uint32_t SBO, uint32_t SWZ> __device__ __forceinline__ uint64_t dsc(uint32_t lo, uint32_t off) {
  uint64_t d; asm("mov.b64 %0, {%1, %2};" : "=l"(d) : "r"(lo + (off >> 4)), "n"((SBO >> 4) | (SWZ << 30))); return d;
}
template <int R> __device__ __forceinline__ void reg_alloc() { asm volatile("setmaxnreg.inc.sync.aligned.u32 %0;" ::"n"(R)); }
template <int R> __device__ __forceinline__ void reg_dealloc() { asm volatile("setmaxnreg.dec.sync.aligned.u32 %0;" ::"n"(R)); }
__device__ __forceinline__ void bar_sync(int id, int n) { asm volatile("bar.sync %0, %1;" ::"r"(id), "r"(n) : "memory"); }
__device__ __forceinline__ void bar_arrive(int id, int n) { asm volatile("bar.arrive %0, %1;" ::"r"(id), "r"(n) : "memory"); }
__device__ __forceinline__ void ldsm4(uint32_t* r, uint32_t addr) {
  asm volatile("ldmatrix.sync.aligned.m8n8.x4.shared.b16 {%0,%1,%2,%3}, [%4];" : "=r"(r[0]), "=r"(r[1]), "=r"(r[2]), "=r"(r[3]) : "r"(addr) : "memory");
}
__device__ __forceinline__ uint32_t movm(uint32_t a) { uint32_t d; asm volatile("movmatrix.sync.aligned.m8n8.trans.b16 %0, %1;" : "=r"(d) : "r"(a)); return d; }
__device__ __forceinline__ void mma16(float* c, uint32_t a0, uint32_t a1, uint32_t a2, uint32_t a3, uint32_t b0, uint32_t b1) {
  asm volatile("mma.sync.aligned.m16n8k16.row.col.f32.bf16.bf16.f32 {%0,%1,%2,%3}, {%4,%5,%6,%7}, {%8,%9}, {%0,%1,%2,%3};"
               : "+f"(c[0]), "+f"(c[1]), "+f"(c[2]), "+f"(c[3]) : "r"(a0), "r"(a1), "r"(a2), "r"(a3), "r"(b0), "r"(b1));
}
__device__ __forceinline__ void mma8(float* c, uint32_t a0, uint32_t a1, uint32_t b0) {
  asm volatile("mma.sync.aligned.m16n8k8.row.col.f32.bf16.bf16.f32 {%0,%1,%2,%3}, {%4,%5}, {%6}, {%0,%1,%2,%3};"
               : "+f"(c[0]), "+f"(c[1]), "+f"(c[2]), "+f"(c[3]) : "r"(a0), "r"(a1), "r"(b0));
}
__device__ __forceinline__ uint32_t pack2(float lo, float hi) { uint32_t r; asm("cvt.rn.bf16x2.f32 %0, %1, %2;" : "=r"(r) : "f"(hi), "f"(lo)); return r; }
__device__ __forceinline__ float blo(uint32_t v) { return __uint_as_float(v << 16); }
__device__ __forceinline__ float bhi(uint32_t v) { return __uint_as_float(v & 0xffff0000u); }
__device__ __forceinline__ float tanh_fast(float x) { float y; asm("tanh.approx.f32 %0, %1;" : "=f"(y) : "f"(x)); return y; }
__device__ __forceinline__ float rcp_fast(float x) { float y; asm("rcp.approx.ftz.f32 %0, %1;" : "=f"(y) : "f"(x)); return y; }
__device__ __forceinline__ float rsq_fast(float x) { float y; asm("rsqrt.approx.ftz.f32 %0, %1;" : "=f"(y) : "f"(x)); return y; }
__device__ __forceinline__ float ex2(float x) { float y; asm("ex2.approx.ftz.f32 %0, %1;" : "=f"(y) : "f"(x)); return y; }
__device__ __forceinline__ float qsum(float v) { v += __shfl_xor_sync(~0u, v, 1); v += __shfl_xor_sync(~0u, v, 2); return v; }
__device__ __forceinline__ float qmax(float v) { v = fmaxf(v, __shfl_xor_sync(~0u, v, 1)); v = fmaxf(v, __shfl_xor_sync(~0u, v, 2)); return v; }
__device__ __forceinline__ void stg32(void* p, uint32_t v) { asm volatile("st.global.u32 [%0], %1;" ::"l"(p), "r"(v) : "memory"); }
__device__ __forceinline__ void stg128(void* p, uint32_t a, uint32_t b, uint32_t c, uint32_t d) { asm volatile("st.global.v4.u32 [%0], {%1,%2,%3,%4};" ::"l"(p), "r"(a), "r"(b), "r"(c), "r"(d) : "memory"); }
__device__ __forceinline__ uint32_t ldcg32(const void* p) { uint32_t v; asm volatile("ld.global.L1::no_allocate.u32 %0, [%1];" : "=r"(v) : "l"(p) : "memory"); return v; }
__device__ __forceinline__ void stg128_if(bool c, void* p, uint32_t a, uint32_t b, uint32_t cc, uint32_t d) {
  asm volatile("{\n.reg .pred P;\nsetp.ne.u32 P, %5, 0;\n@P st.global.v4.u32 [%0], {%1,%2,%3,%4};\n}" ::"l"(p), "r"(a), "r"(b), "r"(cc), "r"(d), "r"((uint32_t)c) : "memory");
}
__device__ __forceinline__ uint2 lds64(uint32_t a) { uint2 v; asm volatile("ld.shared.v2.u32 {%0,%1}, [%2];" : "=r"(v.x), "=r"(v.y) : "r"(a) : "memory"); return v; }
__device__ __forceinline__ uint32_t ldnc16(const void* p) { uint16_t v; asm volatile("ld.global.nc.u16 %0, [%1];" : "=h"(v) : "l"(p)); return v; }
__device__ __forceinline__ uint4 ldnc128(const void* p) { uint4 v; asm volatile("ld.global.nc.v4.u32 {%0,%1,%2,%3}, [%4];" : "=r"(v.x), "=r"(v.y), "=r"(v.z), "=r"(v.w) : "l"(p)); return v; }
__device__ __forceinline__ void cp_async16(uint32_t dst, const void* src) { asm volatile("cp.async.cg.shared.global [%0], [%1], 16;" ::"r"(dst), "l"(src) : "memory"); }
__device__ __forceinline__ uint32_t hsub2(uint32_t a, uint32_t b) { uint32_t d; asm("sub.rn.bf16x2 %0, %1, %2;" : "=r"(d) : "r"(a), "r"(b)); return d; }
__device__ __forceinline__ void stg32_if(bool c, void* p, uint32_t v) {
  asm volatile("{\n.reg .pred P;\nsetp.ne.u32 P, %2, 0;\n@P st.global.u32 [%0], %1;\n}" ::"l"(p), "r"(v), "r"((uint32_t)c) : "memory");
}
__device__ __forceinline__ float wsum(float v) { for (int o = 16; o; o >>= 1) v += __shfl_xor_sync(~0u, v, o); return v; }
__device__ __forceinline__ uint32_t hmul2(uint32_t a, uint32_t b) { uint32_t d; asm("mul.rn.bf16x2 %0, %1, %2;" : "=r"(d) : "r"(a), "r"(b)); return d; }
__device__ __forceinline__ void sts32(uint32_t a, uint32_t v) { asm volatile("st.shared.u32 [%0], %1;" ::"r"(a), "r"(v) : "memory"); }
__device__ __forceinline__ uint32_t lds32(uint32_t a) { uint32_t v; asm volatile("ld.shared.u32 %0, [%1];" : "=r"(v) : "r"(a) : "memory"); return v; }
__device__ __forceinline__ void sts128(uint32_t a, uint32_t x, uint32_t y, uint32_t z, uint32_t w) { asm volatile("st.shared.v4.u32 [%0], {%1,%2,%3,%4};" ::"r"(a), "r"(x), "r"(y), "r"(z), "r"(w) : "memory"); }
__device__ __forceinline__ uint4 lds128(uint32_t a) { uint4 v; asm volatile("ld.shared.v4.u32 {%0,%1,%2,%3}, [%4];" : "=r"(v.x), "=r"(v.y), "=r"(v.z), "=r"(v.w) : "r"(a) : "memory"); return v; }
__device__ __forceinline__ void ll_st64(uint2* p, uint32_t v, uint32_t tag) {
  asm volatile("{\n.reg .b64 r;\nmov.b64 r, {%1,%2};\nst.relaxed.gpu.global.b64 [%0], r;\n}" ::"l"(p), "r"(v), "r"(tag) : "memory");
}
__device__ __forceinline__ uint2 ll_ld64(const uint2* p) {
  uint2 v; asm volatile("{\n.reg .b64 r;\nld.relaxed.gpu.global.b64 r, [%2];\nmov.b64 {%0,%1}, r;\n}" : "=r"(v.x), "=r"(v.y) : "l"(p) : "memory"); return v;
}
__device__ __forceinline__ void ll_st128(uint4* p, float a, float b, uint32_t tag, float c = 0.f) {
  asm volatile("{\n.reg .b128 r;\n.reg .b64 lo, hi;\nmov.b64 lo, {%1,%2};\nmov.b64 hi, {%3,%4};\nmov.b128 r, {lo, hi};\nst.relaxed.gpu.global.b128 [%0], r;\n}" ::"l"(p), "r"(__float_as_uint(a)), "r"(__float_as_uint(b)), "r"(tag), "r"(__float_as_uint(c)) : "memory");
}
__device__ __forceinline__ uint4 ll_ld128g(const void* p) {
  uint4 v; asm volatile("{\n.reg .b128 r;\n.reg .b64 lo, hi;\nld.relaxed.gpu.b128 r, [%4];\nmov.b128 {lo, hi}, r;\nmov.b64 {%0,%1}, lo;\nmov.b64 {%2,%3}, hi;\n}" : "=r"(v.x), "=r"(v.y), "=r"(v.z), "=r"(v.w) : "l"(p) : "memory"); return v;
}
__device__ __forceinline__ uint4 ll_ld128(const uint4* p) {
  uint4 v; asm volatile("{\n.reg .b128 r;\n.reg .b64 lo, hi;\nld.relaxed.gpu.global.b128 r, [%4];\nmov.b128 {lo, hi}, r;\nmov.b64 {%0,%1}, lo;\nmov.b64 {%2,%3}, hi;\n}" : "=r"(v.x), "=r"(v.y), "=r"(v.z), "=r"(v.w) : "l"(p) : "memory"); return v;
}
__device__ __forceinline__ void publish_p(uint32_t el, uint32_t* f) {
  asm volatile("{\n.reg .pred P;\nsetp.ne.u32 P, %1, 0;\n@P cp.async.bulk.commit_group;\n@P cp.async.bulk.wait_group 0;\n@P red.release.gpu.global.add.u32 [%0], 1;\n}" ::"l"(f), "r"(el) : "memory");
}
__device__ __forceinline__ void stsm4(uint32_t addr, uint32_t a, uint32_t b, uint32_t c, uint32_t d) {
  asm volatile("stmatrix.sync.aligned.m8n8.x4.shared.b16 [%0], {%1,%2,%3,%4};" ::"r"(addr), "r"(a), "r"(b), "r"(c), "r"(d) : "memory");
}
__device__ __forceinline__ void sts64(uint32_t a, uint32_t x, uint32_t y) { asm volatile("st.shared.v2.u32 [%0], {%1,%2};" ::"r"(a), "r"(x), "r"(y) : "memory"); }
__device__ __forceinline__ void ll_st128_if(bool on, uint4* p, float a, float b, uint32_t tag) {
  asm volatile("{\n.reg .pred P;\n.reg .b128 r;\n.reg .b64 lo, hi;\nsetp.ne.u32 P, %4, 0;\nmov.b64 lo, {%1,%2};\nmov.b64 hi, {%3,%3};\nmov.b128 r, {lo, hi};\n@P st.relaxed.gpu.global.b128 [%0], r;\n}" ::"l"(p), "r"(__float_as_uint(a)), "r"(__float_as_uint(b)), "r"(tag), "r"((uint32_t)on) : "memory");
}
__device__ __forceinline__ uint4 ldnc128_if(bool c, const void* p) {
  uint4 v = make_uint4(0u, 0u, 0u, 0u);
  asm volatile("{\n.reg .pred P;\nsetp.ne.u32 P, %5, 0;\n@P ld.global.nc.v4.u32 {%0,%1,%2,%3}, [%4];\n}" : "+r"(v.x), "+r"(v.y), "+r"(v.z), "+r"(v.w) : "l"(p), "r"((uint32_t)c));
  return v;
}
__device__ __forceinline__ float2 lds64f(uint32_t a) { float2 v; asm volatile("ld.shared.v2.f32 {%0,%1}, [%2];" : "=f"(v.x), "=f"(v.y) : "r"(a) : "memory"); return v; }
#define TRC(cond, role, idx) do {} while (0)
#define TRV(role, idx, v) do {} while (0)
#define TRVI(c, role, idx, v) do {} while (0)

#define ACLK_INIT do {} while (0)
#define ACLK(i) do {} while (0)
#define ACLK_OUT do {} while (0)
#define RCLK(i) do {} while (0)
#define RCLK_INIT do {} while (0)
#define RCLK_OUT do {} while (0)
#define SCLK(i) do {} while (0)
#define SCLK2(i) do {} while (0)
#define SCLK3(i) do {} while (0)
#define OCLK(c, r, i) do {} while (0)
#define PL 1
#define PCLK(i) do {} while (0)
#define PQ 1
#define CLK_INIT do {} while (0)
#define CLK(i) do {} while (0)
#define CLK_OUT do {} while (0)

__device__ __forceinline__ void wgmma_ss_n216(float* d, uint64_t da, uint64_t db, int scaleD) {
  asm volatile("{\n.reg .pred p;\nsetp.ne.b32 p, %110, 0;\nwgmma.mma_async.sync.aligned.m64n216k16.f32.bf16.bf16 "
    "{%0,%1,%2,%3,%4,%5,%6,%7,%8,%9,%10,%11,%12,%13,%14,%15,%16,%17,%18,%19,%20,%21,%22,%23,%24,%25,%26,%27,%28,%29,%30,%31,%32,%33,%34,%35,%36,%37,%38,%39,%40,%41,%42,%43,%44,%45,%46,%47,%48,%49,%50,%51,%52,%53,%54,%55,%56,%57,%58,%59,%60,%61,%62,%63,%64,%65,%66,%67,%68,%69,%70,%71,%72,%73,%74,%75,%76,%77,%78,%79,%80,%81,%82,%83,%84,%85,%86,%87,%88,%89,%90,%91,%92,%93,%94,%95,%96,%97,%98,%99,%100,%101,%102,%103,%104,%105,%106,%107}, "
    "%108, %109, p, 1, 1, 0, 1;\n}\n"
    : "+f"(d[0]), "+f"(d[1]), "+f"(d[2]), "+f"(d[3]), "+f"(d[4]), "+f"(d[5]), "+f"(d[6]), "+f"(d[7]), "+f"(d[8]), "+f"(d[9]), "+f"(d[10]), "+f"(d[11]), "+f"(d[12]), "+f"(d[13]), "+f"(d[14]), "+f"(d[15]), "+f"(d[16]), "+f"(d[17]), "+f"(d[18]), "+f"(d[19]), "+f"(d[20]), "+f"(d[21]), "+f"(d[22]), "+f"(d[23]), "+f"(d[24]), "+f"(d[25]), "+f"(d[26]), "+f"(d[27]), "+f"(d[28]), "+f"(d[29]), "+f"(d[30]), "+f"(d[31]), "+f"(d[32]), "+f"(d[33]), "+f"(d[34]), "+f"(d[35]), "+f"(d[36]), "+f"(d[37]), "+f"(d[38]), "+f"(d[39]), "+f"(d[40]), "+f"(d[41]), "+f"(d[42]), "+f"(d[43]), "+f"(d[44]), "+f"(d[45]), "+f"(d[46]), "+f"(d[47]), "+f"(d[48]), "+f"(d[49]), "+f"(d[50]), "+f"(d[51]), "+f"(d[52]), "+f"(d[53]), "+f"(d[54]), "+f"(d[55]), "+f"(d[56]), "+f"(d[57]), "+f"(d[58]), "+f"(d[59]), "+f"(d[60]), "+f"(d[61]), "+f"(d[62]), "+f"(d[63]), "+f"(d[64]), "+f"(d[65]), "+f"(d[66]), "+f"(d[67]), "+f"(d[68]), "+f"(d[69]), "+f"(d[70]), "+f"(d[71]), "+f"(d[72]), "+f"(d[73]), "+f"(d[74]), "+f"(d[75]), "+f"(d[76]), "+f"(d[77]), "+f"(d[78]), "+f"(d[79]), "+f"(d[80]), "+f"(d[81]), "+f"(d[82]), "+f"(d[83]), "+f"(d[84]), "+f"(d[85]), "+f"(d[86]), "+f"(d[87]), "+f"(d[88]), "+f"(d[89]), "+f"(d[90]), "+f"(d[91]), "+f"(d[92]), "+f"(d[93]), "+f"(d[94]), "+f"(d[95]), "+f"(d[96]), "+f"(d[97]), "+f"(d[98]), "+f"(d[99]), "+f"(d[100]), "+f"(d[101]), "+f"(d[102]), "+f"(d[103]), "+f"(d[104]), "+f"(d[105]), "+f"(d[106]), "+f"(d[107])
    : "l"(da), "l"(db), "r"(scaleD));
}
__device__ __forceinline__ void wgmma_ss_n72(float* d, uint64_t da, uint64_t db, int scaleD) {
  asm volatile("{\n.reg .pred p;\nsetp.ne.b32 p, %38, 0;\nwgmma.mma_async.sync.aligned.m64n72k16.f32.bf16.bf16 "
    "{%0,%1,%2,%3,%4,%5,%6,%7,%8,%9,%10,%11,%12,%13,%14,%15,%16,%17,%18,%19,%20,%21,%22,%23,%24,%25,%26,%27,%28,%29,%30,%31,%32,%33,%34,%35}, "
    "%36, %37, p, 1, 1, 0, 1;\n}\n"
    : "+f"(d[0]), "+f"(d[1]), "+f"(d[2]), "+f"(d[3]), "+f"(d[4]), "+f"(d[5]), "+f"(d[6]), "+f"(d[7]), "+f"(d[8]), "+f"(d[9]), "+f"(d[10]), "+f"(d[11]), "+f"(d[12]), "+f"(d[13]), "+f"(d[14]), "+f"(d[15]), "+f"(d[16]), "+f"(d[17]), "+f"(d[18]), "+f"(d[19]), "+f"(d[20]), "+f"(d[21]), "+f"(d[22]), "+f"(d[23]), "+f"(d[24]), "+f"(d[25]), "+f"(d[26]), "+f"(d[27]), "+f"(d[28]), "+f"(d[29]), "+f"(d[30]), "+f"(d[31]), "+f"(d[32]), "+f"(d[33]), "+f"(d[34]), "+f"(d[35])
    : "l"(da), "l"(db), "r"(scaleD));
}
__device__ __forceinline__ void wgmma_ss_n128(float* d, uint64_t da, uint64_t db, int scaleD) {
  asm volatile("{\n.reg .pred p;\nsetp.ne.b32 p, %66, 0;\nwgmma.mma_async.sync.aligned.m64n128k16.f32.bf16.bf16 "
    "{%0,%1,%2,%3,%4,%5,%6,%7,%8,%9,%10,%11,%12,%13,%14,%15,%16,%17,%18,%19,%20,%21,%22,%23,%24,%25,%26,%27,%28,%29,%30,%31,%32,%33,%34,%35,%36,%37,%38,%39,%40,%41,%42,%43,%44,%45,%46,%47,%48,%49,%50,%51,%52,%53,%54,%55,%56,%57,%58,%59,%60,%61,%62,%63}, "
    "%64, %65, p, 1, 1, 0, 1;\n}\n"
    : "+f"(d[0]), "+f"(d[1]), "+f"(d[2]), "+f"(d[3]), "+f"(d[4]), "+f"(d[5]), "+f"(d[6]), "+f"(d[7]), "+f"(d[8]), "+f"(d[9]), "+f"(d[10]), "+f"(d[11]), "+f"(d[12]), "+f"(d[13]), "+f"(d[14]), "+f"(d[15]), "+f"(d[16]), "+f"(d[17]), "+f"(d[18]), "+f"(d[19]), "+f"(d[20]), "+f"(d[21]), "+f"(d[22]), "+f"(d[23]), "+f"(d[24]), "+f"(d[25]), "+f"(d[26]), "+f"(d[27]), "+f"(d[28]), "+f"(d[29]), "+f"(d[30]), "+f"(d[31]), "+f"(d[32]), "+f"(d[33]), "+f"(d[34]), "+f"(d[35]), "+f"(d[36]), "+f"(d[37]), "+f"(d[38]), "+f"(d[39]), "+f"(d[40]), "+f"(d[41]), "+f"(d[42]), "+f"(d[43]), "+f"(d[44]), "+f"(d[45]), "+f"(d[46]), "+f"(d[47]), "+f"(d[48]), "+f"(d[49]), "+f"(d[50]), "+f"(d[51]), "+f"(d[52]), "+f"(d[53]), "+f"(d[54]), "+f"(d[55]), "+f"(d[56]), "+f"(d[57]), "+f"(d[58]), "+f"(d[59]), "+f"(d[60]), "+f"(d[61]), "+f"(d[62]), "+f"(d[63])
    : "l"(da), "l"(db), "r"(scaleD));
}
__device__ __forceinline__ void wgmma_ss_n160(float* d, uint64_t da, uint64_t db, int scaleD) {
  asm volatile("{\n.reg .pred p;\nsetp.ne.b32 p, %82, 0;\nwgmma.mma_async.sync.aligned.m64n160k16.f32.bf16.bf16 "
    "{%0,%1,%2,%3,%4,%5,%6,%7,%8,%9,%10,%11,%12,%13,%14,%15,%16,%17,%18,%19,%20,%21,%22,%23,%24,%25,%26,%27,%28,%29,%30,%31,%32,%33,%34,%35,%36,%37,%38,%39,%40,%41,%42,%43,%44,%45,%46,%47,%48,%49,%50,%51,%52,%53,%54,%55,%56,%57,%58,%59,%60,%61,%62,%63,%64,%65,%66,%67,%68,%69,%70,%71,%72,%73,%74,%75,%76,%77,%78,%79}, "
    "%80, %81, p, 1, 1, 0, 1;\n}\n"
    : "+f"(d[0]), "+f"(d[1]), "+f"(d[2]), "+f"(d[3]), "+f"(d[4]), "+f"(d[5]), "+f"(d[6]), "+f"(d[7]), "+f"(d[8]), "+f"(d[9]), "+f"(d[10]), "+f"(d[11]), "+f"(d[12]), "+f"(d[13]), "+f"(d[14]), "+f"(d[15]), "+f"(d[16]), "+f"(d[17]), "+f"(d[18]), "+f"(d[19]), "+f"(d[20]), "+f"(d[21]), "+f"(d[22]), "+f"(d[23]), "+f"(d[24]), "+f"(d[25]), "+f"(d[26]), "+f"(d[27]), "+f"(d[28]), "+f"(d[29]), "+f"(d[30]), "+f"(d[31]), "+f"(d[32]), "+f"(d[33]), "+f"(d[34]), "+f"(d[35]), "+f"(d[36]), "+f"(d[37]), "+f"(d[38]), "+f"(d[39]), "+f"(d[40]), "+f"(d[41]), "+f"(d[42]), "+f"(d[43]), "+f"(d[44]), "+f"(d[45]), "+f"(d[46]), "+f"(d[47]), "+f"(d[48]), "+f"(d[49]), "+f"(d[50]), "+f"(d[51]), "+f"(d[52]), "+f"(d[53]), "+f"(d[54]), "+f"(d[55]), "+f"(d[56]), "+f"(d[57]), "+f"(d[58]), "+f"(d[59]), "+f"(d[60]), "+f"(d[61]), "+f"(d[62]), "+f"(d[63]), "+f"(d[64]), "+f"(d[65]), "+f"(d[66]), "+f"(d[67]), "+f"(d[68]), "+f"(d[69]), "+f"(d[70]), "+f"(d[71]), "+f"(d[72]), "+f"(d[73]), "+f"(d[74]), "+f"(d[75]), "+f"(d[76]), "+f"(d[77]), "+f"(d[78]), "+f"(d[79])
    : "l"(da), "l"(db), "r"(scaleD));
}
__device__ __forceinline__ void wgmma_rs_n144(float* d, const uint32_t* a, uint64_t db, int scaleD) {
  asm volatile("{\n.reg .pred p;\nsetp.ne.b32 p, %77, 0;\nwgmma.mma_async.sync.aligned.m64n144k16.f32.bf16.bf16 "
    "{%0,%1,%2,%3,%4,%5,%6,%7,%8,%9,%10,%11,%12,%13,%14,%15,%16,%17,%18,%19,%20,%21,%22,%23,%24,%25,%26,%27,%28,%29,%30,%31,%32,%33,%34,%35,%36,%37,%38,%39,%40,%41,%42,%43,%44,%45,%46,%47,%48,%49,%50,%51,%52,%53,%54,%55,%56,%57,%58,%59,%60,%61,%62,%63,%64,%65,%66,%67,%68,%69,%70,%71}, "
    "{%72,%73,%74,%75}, %76, p, 1, 1, 1;\n}\n"
    : "+f"(d[0]), "+f"(d[1]), "+f"(d[2]), "+f"(d[3]), "+f"(d[4]), "+f"(d[5]), "+f"(d[6]), "+f"(d[7]), "+f"(d[8]), "+f"(d[9]), "+f"(d[10]), "+f"(d[11]), "+f"(d[12]), "+f"(d[13]), "+f"(d[14]), "+f"(d[15]), "+f"(d[16]), "+f"(d[17]), "+f"(d[18]), "+f"(d[19]), "+f"(d[20]), "+f"(d[21]), "+f"(d[22]), "+f"(d[23]), "+f"(d[24]), "+f"(d[25]), "+f"(d[26]), "+f"(d[27]), "+f"(d[28]), "+f"(d[29]), "+f"(d[30]), "+f"(d[31]), "+f"(d[32]), "+f"(d[33]), "+f"(d[34]), "+f"(d[35]), "+f"(d[36]), "+f"(d[37]), "+f"(d[38]), "+f"(d[39]), "+f"(d[40]), "+f"(d[41]), "+f"(d[42]), "+f"(d[43]), "+f"(d[44]), "+f"(d[45]), "+f"(d[46]), "+f"(d[47]), "+f"(d[48]), "+f"(d[49]), "+f"(d[50]), "+f"(d[51]), "+f"(d[52]), "+f"(d[53]), "+f"(d[54]), "+f"(d[55]), "+f"(d[56]), "+f"(d[57]), "+f"(d[58]), "+f"(d[59]), "+f"(d[60]), "+f"(d[61]), "+f"(d[62]), "+f"(d[63]), "+f"(d[64]), "+f"(d[65]), "+f"(d[66]), "+f"(d[67]), "+f"(d[68]), "+f"(d[69]), "+f"(d[70]), "+f"(d[71])
    : "r"(a[0]), "r"(a[1]), "r"(a[2]), "r"(a[3]), "l"(db), "r"(scaleD));
}
__device__ __forceinline__ void wgmma_rs_n64(float* d, const uint32_t* a, uint64_t db, int scaleD) {
  asm volatile("{\n.reg .pred p;\nsetp.ne.b32 p, %37, 0;\nwgmma.mma_async.sync.aligned.m64n64k16.f32.bf16.bf16 "
    "{%0,%1,%2,%3,%4,%5,%6,%7,%8,%9,%10,%11,%12,%13,%14,%15,%16,%17,%18,%19,%20,%21,%22,%23,%24,%25,%26,%27,%28,%29,%30,%31}, "
    "{%32,%33,%34,%35}, %36, p, 1, 1, 1;\n}\n"
    : "+f"(d[0]), "+f"(d[1]), "+f"(d[2]), "+f"(d[3]), "+f"(d[4]), "+f"(d[5]), "+f"(d[6]), "+f"(d[7]), "+f"(d[8]), "+f"(d[9]), "+f"(d[10]), "+f"(d[11]), "+f"(d[12]), "+f"(d[13]), "+f"(d[14]), "+f"(d[15]), "+f"(d[16]), "+f"(d[17]), "+f"(d[18]), "+f"(d[19]), "+f"(d[20]), "+f"(d[21]), "+f"(d[22]), "+f"(d[23]), "+f"(d[24]), "+f"(d[25]), "+f"(d[26]), "+f"(d[27]), "+f"(d[28]), "+f"(d[29]), "+f"(d[30]), "+f"(d[31])
    : "r"(a[0]), "r"(a[1]), "r"(a[2]), "r"(a[3]), "l"(db), "r"(scaleD));
}

template <int V> struct Int { static constexpr int value = V; };
struct Cur {
  uint32_t s, ph;
  __device__ __forceinline__ void next() { if (++s == NST) { s = 0; ph ^= 1; } }
};

__device__ __forceinline__ uint32_t o_place(uint32_t w, uint32_t e) { return (((w ? 0xd5310u : 0xa8d57u) >> (4 * e)) & 15) * 8192 + 90112; }
#define z1_block(rb, w, j) (Q.Z + ((rb) * 16 + (w) * 8 + (j)) * ZB)
#define xn_block(hw) (Q.Z + ((hw) * 8 + 2) * ZB)
#define z2_block(kb, j) (Q.Z + (256 + (kb) * 8 + (j)) * ZB)
template <int N> __device__ __forceinline__ void pause(uint32_t zero) {
  if (N <= 0) return;
  uint32_t z = clock() + threadIdx.x;
  do {
#pragma unroll (N > 8 ? 1 : 8)
    for (int i = 0; i < N; i++) asm volatile("shfl.sync.bfly.b32 %0, %0, 1, 0x1f, 0xffffffff;" : "+r"(z)::"memory");
  } while (__any_sync(~0u, z & zero));
}

__global__ void __cluster_dims__(2, 1, 1) __launch_bounds__(384, 1) mega_kernel(const Ptrs Q, const __grid_constant__ Params P) {
  extern __shared__ __align__(1024) uint8_t smem_raw[];
  const uint32_t sb = smem_u32(smem_raw);
  const uint32_t bars = sb + SM_BAR;
  const int tid = threadIdx.x;
  int lane = tid & 31;
  const int wid = __shfl_sync(~0u, tid >> 5, 0);
  const int cl = blockIdx.x >> 1;
  const int bid = (cl < 4 ? cl * 8 + 32 : cl - 4 + (max(cl - 29, 0) * 37 >> 8)) * 2 + (blockIdx.x & 1);
  const int rb = bid & 15, j = bid >> 4;
  uint4 wv[5];
  {
    const int n8 = min(tid >> 3, 26), part = n8 / 9;
    const uint8_t* src = (const uint8_t*)Q.wqkv + (8 * rb + (tid & 7)) * (3 * DM * 2) + (part * (DM - 72) + 72 * j + 8 * n8) * 2;
#pragma unroll
    for (int u = 0; u < 5; u++) wv[u] = ldnc128_if(tid < 216 && cl < 64 && (u < 4 || rb < 8), src + u * (128 * 3 * DM * 2));
  }
  if (cl >= 64) return;
  if (wid >= 7 && lane == 0) {
    if (wid < 10) {
#pragma unroll
      for (uint32_t b = 0; b < B_AD / 3; b += 8) mbar_init(bars + (wid - 7) * (B_AD / 3) + b, 1);
    } else if (wid == 10) {
#pragma unroll
      for (uint32_t b = B_AD; b < B_EVT; b += 8) mbar_init(bars + b, b < B_HOLD ? 2 : 4);
    } else {
#pragma unroll
      for (uint32_t b = B_EVT; b < 1024; b += 8) if (b < B_OFF || b >= B_IMG) mbar_init(bars + b, b < B_IMG ? 4 : b < B_EMPTY ? 8 : 16);
    }
    asm volatile("fence.mbarrier_init.release.cluster;" ::: "memory");
  }
  __syncthreads();

  if (wid >= 8) {
    reg_dealloc<56>();
    const uint32_t el = elect_one();
    const uint64_t pol = policy_evict_first();
    uint32_t* const fj = Q.flags + FJ + j * 32;
    if (wid == 8) {
      if (el) { prefetch_map(&P.wsp); prefetch_map(&P.winb[j & 1]); prefetch_map(&P.wins); prefetch_map(&P.wout); prefetch_map(&P.act[1]); prefetch_map(&P.res[0]); prefetch_map(&P.res[1]); }
      const uint32_t epoch = ldcg32(fj + FJ_EP + rb);
      Cur c{0, 1};
      const uint32_t rk = bid & 1;
      uint32_t st, full;
      auto slot = [&](uint32_t bytes) {
        st = sb + c.s * ST_BYTES; full = bars + B_FULL + c.s * 8;
        mbar_wait(full, c.ph);
        expect_tx_p(el, full, bytes);
        mbar_wait(full - B_FULL + B_EMPTY, c.ph);
      };
#pragma unroll 1
      for (int L = 0; L < 2; L++) {
#pragma unroll 1
        for (int i = 0; i < 9; i++) {
          if (L == 0 && i == 0) {
            flag_wait(fj + FJ_WQ, (epoch + 1) * 16);
            fence_async_g();
            TRC(el, 2, 45);
          }
          slot(27648);
          bulk_mc_h(el, st + ST_B + rk * 13824, Q.WQ + j * WQ_SL + i * 27648 + rk * 13824, 13824, full, EF(0), pol);
          c.next();
        }
        if (L == 0) {
          flag_wait(fj + FJ_WO, (epoch + 1) * 16);
          fence_async_g();
          TRC(el, 2, 46);
        }
#pragma unroll 1
        while (c.s) {
          mbar_wait(bars + B_EMPTY + c.s * 8, c.ph);
          if (el) { mbar_arrive(bars + B_FULL + c.s * 8); asm volatile("mbarrier.arrive.shared::cta.b64 _, [%0], 16;" ::"r"(bars + B_EMPTY + c.s * 8) : "memory"); }
          c.next();
        }
        expect_tx_p(el, bars + B_WF, WO_SL);
        mbar_wait(bars + B_EMPTY, c.ph);
        mbar_wait(bars + B_EMPTY + 8, c.ph);
        bulk_mc_h(el, sb + rk * (WO_SL / 2), Q.WO + j * WO_SL + rk * (WO_SL / 2), WO_SL / 2, bars + B_WF, EF(1), pol);
#pragma unroll 1
        for (int r = 0; r < 10; r++) {
          const bool big = r >= 2 && r < 8;
          const int a0 = (r < 5 ? 36 : 0) + ((9 * j) >> 1) + (big ? 2 - 2 * (j & 1) : 3 * (j & 1) + rk), ks = big ? 32 : 48;
          int k = big ? (r < 5 ? r - 2 : r - 5) * 192 + rk * 16 : (r & 1) * 288;
          const CUtensorMap* m = big ? &P.winb[j & 1] : &P.wins;
          const uint32_t dst = sb + SM_B3 + rk * 6144;
#pragma unroll
          for (int p = 0; p < 6; p++, k += ks) {
            if (!(p & 3) && r == 0) mbar_wait(bars + B_XD + p * 2, L);
            if (p) mbar_wait_c(bars + B_E3 + p * 8, ~r & 1); else mbar_wait(bars + B_E3, ~r & 1);
            expect_tx_p(el, bars + B_F3 + p * 8, 12288);
            tma3d_mc_h(el, dst + p * 12288, m, 0, k, a0, bars + B_F3 + p * 8, EF(2), pol);
          }
        }
        TRC(el, 2, L * 16 + 6);
        mbar_wait(bars + B_ZOK, L);
        fence_async_g();
        TRC(el, 2, L * 16 + 7);
        const uint8_t* src = z2_block(0, j) + rk * 18432;
#pragma unroll 1
        for (int r = 0; r < 8; r++) {
          const int k = (r & 3) * 512 + ((r >> 2) ^ 1) * 64;
#pragma unroll
          for (int p = 0; p < 4; p++, src += 8 * ZB) {
            if ((p == 1 || p == 2) && r == 0) mbar_wait(bars + B_E3 - 8 + p * 24, 1);
            mbar_wait_c(bars + B_AD + p * 8, ~r & 1);
            if (p) mbar_wait_c(bars + B_EMPTY + p * 8, c.ph); else mbar_wait(bars + B_EMPTY, c.ph);
            expect_tx_p(el, bars + B_FULL + p * 8, ST_BYTES);
            bulk_mc_h(el, sb + p * ST_BYTES + ST_B + rk * 18432, src, 18432, bars + B_FULL + p * 8, EF(4), pol);
            tma3d_h(el, sb + p * ST_BYTES, &P.wsp, k + p * 128, rb * 64, 0, bars + B_FULL + p * 8, EF(3), pol);
          }
          c.ph ^= 1;
        }
        mbar_wait(bars + B_Z1, L);
        fence_async_g();
#pragma unroll 1
        for (int i = 0; i < 11; i++) {
          const int cb = i - 2 + j;
          if (i < 4) mbar_wait(bars + B_AD + c.s * 8, 1);
          slot(ZB);
          if (i < 2) bulk_load_h(el, st + ST_B, z1_block(rb, i, j), ZB, full, true, pol);
          else tma2d_mc_h(el, st + ST_B + rk * 18432, &P.wout, (cb >= 9 ? cb - 9 : cb) * 64, 288 * j + rk * 144, full, EF(5), pol);
          c.next();
        }
      }
    } else if (wid < 11) {
      uint32_t id = bid * 2 + wid - 9;
#define AGENT_IDS asm volatile("" : "+r"(lane), "+r"(id)); const uint32_t w = id & 1, hw = id & 31, rb = hw >> 1, j = id >> 5, ev = bars + B_EVT + w * EV_N * 8; \
      uint32_t* const fr = Q.flags + hw * 32; uint32_t* const fj = Q.flags + FJ + j * 32; (void)fr; (void)fj; (void)ev; (void)rb
      uint32_t t8 = 0;
      Cur c{0, 1};
#pragma unroll 1
      for (int L = 0; L < 2; L++) {
        if (L) {
          AGENT_IDS;
          const uint32_t full = bars + B_FULLA + w * 32 + c.s * 8, dst = sb + c.s * ST_BYTES + w * 8192;
          expect_tx_p(el, full, 8192);
          mbar_wait_c(ev + EV_PT * 8, 1);
          TRC(el, 3, w * 32 + 16);
          flag_release_p(el, fr + FR_X2);
          TRC(el, 3, w * 32 + 17);
          mbar_wait_c(bars + B_EMPTY + c.s * 8, c.ph);
          flag_wait(fr + FR_X2, t8);
          fence_async_g();
          tma3d_h(el, dst, &P.act[1], 0, (hw ^ 1) * 32, 0, full, false, pol);
          c.next();
          TRC(el, 3, w * 32 + 18);
        }
#pragma unroll 1
        for (int i = L; i < 9; i++) {
          AGENT_IDS;
          const uint32_t full = bars + B_FULLA + w * 32 + c.s * 8, dst = sb + c.s * ST_BYTES + w * 8192;
          if (L == 0 && i == AEP) t8 = (ldcg32(fr + FR_EP + j) + 1) * 8;
          mbar_wait_c(bars + B_EMPTY + c.s * 8, c.ph);
          expect_tx_p(el, full, 8192);
          tma3d_h(el, dst, &P.act[L], i * 64, (hw ^ 1) * 32, 0, full, false, pol);
          c.next();
          if (i == PZI || i == PZI + 1) {
            uint8_t* d = (i == PZI ? xn_block(hw) : z1_block(rb, 0, 0) + w * 4608) + j * 9216 + lane * 16;
#pragma unroll 1
            for (int u = i == PZI ? 0 : 3; u < 6; u++, d += 1536) { stg128(d, ~0u, ~0u, ~0u, ~0u); stg128(d + 512, ~0u, ~0u, ~0u, ~0u); stg128(d + 1024, ~0u, ~0u, ~0u, ~0u); }
          }
          if (i == PZI) { stg128(Q.ST1 + (hw * 8 + j) * 32 + lane, ~0u, ~0u, ~0u, ~0u); stg128(Q.ZST + (hw * 8 + j) * 32 + lane, ~0u, ~0u, ~0u, ~0u); }
          if (i == RFI) {
            if (L) mbar_wait_c(bars + B_EVT + (EV_N * (1 - w) + EV_PT) * 8, 1);
            expect_tx_p(el, bars + B_WT + w * 8, 9216);
            bulk_load_p(el, sb + SM_STG + w * 9216, (L ? Q.out : Q.x) + ((hw ^ 1) * 64 + 8 * j) * (DM * 2), 9216, bars + B_WT + w * 8);
          }
          if (i == 4 && L > w) {
            expect_tx_p(el, bars + B_XRW + 8, 864);
            bulk_load_p(el, sb + 3 * ST_BYTES + SM_CSQ, Q.CSP + (NCTA + (id >> 1)) * 216, 864, bars + B_XRW + 8);
          }
        }
        if (c.s) { c.s = 0; c.ph ^= 1; }
        {
          AGENT_IDS;
          const uint32_t tag = (t8 >> 2) - 1 + L;
          uint4* const xs = Q.XST + hw * 128;
          const uint32_t tab = sb + L * (3 * ST_BYTES) + SM_XST + w * 768 + lane * 8;
          TRC(el, 3, w * 32 + L * 16 + 13);
#pragma unroll 1
          for (int it = 0; it < (1 << 22); it++) {
            const uint4 a = ll_ld128(xs + 2 * lane), b = ll_ld128(xs + 64 + 2 * lane), h = ll_ld128(xs - (rb ? 192 : 0) + 2 * (lane | 24));
            if (__all_sync(~0u, a.z == tag && b.z == tag && h.z == tag)) { sts64(tab, h.x, h.y); sts64(tab + 256, a.x, a.y); sts64(tab + 512, b.x, b.y); break; }
          }
          __syncwarp();
          if (el) mbar_arrive(bars + B_CSQ);
          TRC(el, 3, w * 32 + L * 16 + 14);
          uint32_t* f = Q.flags + rb * 64 + FR_PZ + L;
          flag_release_p(el, f);
          expect_tx_p(el, bars + B_RES + w * 8, 9216);
          tma3d_h(el, sb + SM_STG + w * 9216, &P.res[L], j * 72, (hw ^ 1) * 32, 0, bars + B_RES + w * 8, !L, pol);
          pause<FD3>(Q.zero);
          flag_wait(f, t8 * 2);
          fence_async_g();
          TRC(el, 3, w * 32 + L * 16 + 15);
        }
        {
          AGENT_IDS;
          uint32_t* f = Q.flags + rb * 64 + FR_O + L;
#pragma unroll 1
          for (int e = 0; e < 5; e++) {
            const uint32_t nb = e ? 16384 : 8192, full = bars + B_OF + w * 40 + e * 8, dst = sb + o_place(w, e);
            const uint8_t* src = z1_block(rb, w, 0) + (e ? e * 16384 - 8192 : 0);
            expect_tx_p(el, full, nb);
            if (e == 0) {
              mbar_wait_c(ev + EV_O * 8, L);
              TRC(el, 3, w * 32 + L * 16 + 3);
              if (!w) flag_add_p(el, f);
              flag_wait(f + w * (FR_OL - FR_O), t8);
              if (w) fence_async_g();
            }
            if (w && (e == 0 || e == 3)) mbar_wait_c(bars + (e ? B_X3 : B_OF + YPACE * 8), L);
            bulk_load_h(el, dst, src, nb, full, EF(6), pol);
            TRC(el && e == 0, 3, w * 32 + L * 16 + 5);
          }
        }
        {
          AGENT_IDS;
          const uint8_t* src = xn_block(hw);
          uint32_t full = bars + B_AF3 + w * 96, dst = sb + w * 6144;
          if (L) flag_wait(fj + FJ_P4, t8 * 4);
          mbar_wait_c(bars + B_XD + 8, L);
          mbar_wait_c(ev + EV_X1 * 8, L);
          TRC(el, 3, w * 32 + L * 16 + 6);
          pause<SDEL>(Q.zero);
#pragma unroll 1
          for (int k = 0; k < 12; k++, src += 6144, dst += 12288, full += 8) {
            expect_tx_p(el, full, 6144);
            if (k >= APACE) mbar_wait_c(full - APACE * 8, L);
            bulk_load_h(el, dst, src, 6144, full, EF(7), pol);
            TRC(el && k == 0, 3, w * 32 + L * 16 + 8);
          }
        }
        if (wid == 10) {
          AGENT_IDS;
          mbar_wait_c(ev - (EV_N - EV_ZN) * 8, L);
          mbar_wait_c(ev + EV_ZN * 8, L);
          asm volatile("fence.release.gpu;" ::: "memory");
          flag_add_p(el, fj + FJ_ZN + L);
          flag_add_p(el, fr - 32 + FR_XR + L);
          flag_wait(fj + FJ_ZN + L, t8 * 2);
          flag_wait(fr - 32 + FR_XR + L, t8);
          if (el) mbar_arrive(bars + B_ZOK);
        } else {
          AGENT_IDS;
          mbar_wait_c(ev + EV_ZN * 8, L);
          if (el) asm volatile("cp.async.bulk.prefetch.tensor.3d.L2.global [%0, {%1, %2, %3}];" ::"l"(&P.wsp), "r"(j * 128 + 64), "r"(rb * 64), "r"(0) : "memory");

        }
        float cv;
        {
        AGENT_IDS;
        cv = (lane & 3) ? 0.f : -blo(ldnc16(Q.b_sp + 128 * rb + 16 * j + 2 * (lane >> 2) + w));
        const uint32_t ro = (w * 64 + 8 * j + (lane >> 2)) * 128, x0 = ((lane & 3) * 2) ^ (lane >> 2);
#pragma unroll 1
        for (int i = 0; i < 32; i++) {
          const bool tail = (i >> 1) == 12;
          const int kb = tail ? i + 6 : i < 24 ? i : i - 2;
          if (!(i & 7)) mbar_wait_c(bars + B_RT + i, L);
          if (i == 24) mbar_wait_c(bars + B_WT + w * 8, 1);
          if (!tail) mbar_wait(bars + B_FULL + c.s * 8, c.ph ^ 1);
          uint4 x[2];
#pragma unroll
          for (int e = 0; e < 2; e++) x[e] = lds128(!tail ? sb + c.s * ST_BYTES + ro + ((x0 ^ e) << 4) : sb + SM_WT + w * 3200 + (lane >> 2) * 400 + (i - 24) * 256 + (lane & 3) * 32 + e * 16);
          if (!tail) {
            __syncwarp();
            if (el) mbar_arrive(bars + B_AD + c.s * 8);
            c.next();
          }
#pragma unroll
          for (int e = 0; e < 2; e++) {
            const uint4 a = x[e], m = lds128(sb + SM_RT + 4096 + kb * 128 + (lane & 3) * 32 + e * 16);
            cv = fmaf(blo(a.x), blo(m.x), fmaf(bhi(a.x), bhi(m.x), fmaf(blo(a.y), blo(m.y), fmaf(bhi(a.y), bhi(m.y), cv))));
            cv = fmaf(blo(a.z), blo(m.z), fmaf(bhi(a.z), bhi(m.z), fmaf(blo(a.w), blo(m.w), fmaf(bhi(a.w), bhi(m.w), cv))));
          }
          if (i == WTI) {
            uint32_t id2 = id;
            asm volatile("" : "+r"(id2));
            expect_tx_p(el, bars + B_WT + w * 8, 3072);
#pragma unroll 1
            for (int r = 0; r < 8; r++)
              bulk_load_p(el, sb + SM_WT + w * 3200 + r * 400, (const uint8_t*)Q.w_sp + (64 * (id2 & 30) + 16 * (id2 >> 5) + 2 * r + w) * (SEQ * 2) + 28 * 128, 384, bars + B_WT + w * 8);
          }
        }
        }
        AGENT_IDS;
        TRC(el, 3, w * 32 + L * 16 + 11);
        asm volatile("" : "+r"(t8));
        const uint32_t tag = (t8 >> 2) - 1 + L;
        cv = qsum(cv);
        uint2* const cs = (uint2*)(Q.XST + hw * 128 + 1);
        if ((lane & 3) == 0) ll_st64(cs + 32 * j + (lane >> 2) * 4, __float_as_uint(cv), tag);
#pragma unroll 1
        for (int it = 0; it < (1 << 22); it++) {
          const uint2 a = ll_ld64(cs + 4 * lane), b = ll_ld64(cs + 128 + 4 * lane);
          if (__all_sync(~0u, a.y == tag && b.y == tag)) { sts32(sb + SM_CV + w * 256 + lane * 4, a.x); sts32(sb + SM_CV + w * 256 + 128 + lane * 4, b.x); break; }
        }
        __syncwarp();
        if (el) mbar_arrive(bars + B_CV + w * 8);
        TRC(el, 3, w * 32 + L * 16 + 12);
#pragma unroll 1
        for (int kb = 30; kb < 32; kb++) {
          mbar_wait_c(bars + B_FULL + c.s * 8, c.ph ^ 1);
          if (el) mbar_arrive(bars + B_AD + c.s * 8);
          c.next();
        }
        c.ph ^= ((c.s + 11) >> 2) & 1; c.s = (c.s + 11) & 3;
        if (L == 0) {
          mbar_wait_c(ev + EV_PT * 8, 0);
          flag_add_p(el, fj + FJ_P4);
        }
      }
    } else {
      const uint32_t epoch = ldcg32(fj + FJ_EP + rb);
      mbar_wait(bars + B_IMG, 0);
      TRC(el, 2, 41);
      flag_release_p(el, fj + FJ_WQ);
      TRC(el, 2, 42);
#pragma unroll 1
      for (int L = 0; L < 2; L++) {
        float* const csf = Q.CSP + (NCTA + bid) * 216;
        if (L == 0) {
          flag_wait(fj + FJ_WQ, (epoch + 1) * 16);
          fence_async_g();
          expect_tx_p(el, bars + B_XRW, 13824);
          bulk_load_p(el, sb + ST_BYTES + SM_WOI, Q.CSP + j * 16 * 216, 6912, bars + B_XRW);
          bulk_load_p(el, sb + 2 * ST_BYTES + SM_WOI, Q.CSP + (j * 16 + 8) * 216, 6912, bars + B_XRW);
          mbar_wait(bars + B_XRW, 0);
#pragma unroll 1
          for (int f = lane; f < 54; f += 32) {
            float s[4] = {0.f, 0.f, 0.f, 0.f};
#pragma unroll 2
            for (int r = 0; r < 16; r++) {
              const uint4 v = lds128(sb + ST_BYTES + SM_WOI + (r >> 3) * ST_BYTES + (r & 7) * 864 + f * 16);
              s[0] += __uint_as_float(v.x); s[1] += __uint_as_float(v.y); s[2] += __uint_as_float(v.z); s[3] += __uint_as_float(v.w);
            }
            sts128(sb + SM_CSQ + f * 16, __float_as_uint(s[0]), __float_as_uint(s[1]), __float_as_uint(s[2]), __float_as_uint(s[3]));
            stg128(csf + f * 4, __float_as_uint(s[0]), __float_as_uint(s[1]), __float_as_uint(s[2]), __float_as_uint(s[3]));
          }
          __syncwarp();
          if (el) mbar_arrive(bars + B_XRW + 8);
          TRC(el, 2, 43);
          mbar_wait(bars + B_WOI, 0);
          bulk_store_p(el, Q.WO + j * WO_SL + rb * (41 * 128), sb + SM_WOI, (rb < 15 ? 41 : 33) * 128);
          publish_p(el, fj + FJ_WO);
          TRC(el, 2, 44);
          if (el) prefetch_l2((const uint8_t*)Q.w_in + bid * 41472, 41472);
          float o0 = 0.f, o1 = 0.f;
#pragma unroll 1
          for (int u = 0; u < 2; u++) {
            const uint8_t* src = (u ? (const uint8_t*)Q.w_sp + 500 * (SEQ * 2) + 2048 : (const uint8_t*)Q.w_in + 100 * (2 * FH * 2) + FH * 2) + lane * 16;
            const uint4 a = ldnc128(src), b = ldnc128(src + 300 * (2 * FH * 2) + 2048);
            const uint32_t x[8] = {a.x, a.y, a.z, a.w, b.x, b.y, b.z, b.w};
            float sq = 0.f;
#pragma unroll
            for (int e = 0; e < 8; e++) sq = fmaf(blo(x[e]), blo(x[e]), fmaf(bhi(x[e]), bhi(x[e]), sq));
            o0 = o1;
            asm("sqrt.approx.f32 %0, %1;" : "=f"(o1) : "f"(wsum(sq) * (u ? C0S * C0S * SEQ / 512.f : 2.f * GA * GA * DM / 512.f)));
          }
          const uint32_t off = (__float_as_uint(o0) & 0x7f800000u) >> 16 | 0x8000u | OFM;
          const uint32_t c0 = min(max(__float_as_uint(o1) & 0x7f800000u, 0x04000000u), 0x7e000000u) | 0x00400000u;
          if (el) sts128(sb + SM_OFF, off * 0x10001u, c0, __float_as_uint(GB), ((c0 >> 16) - 0x200u) * 0x10001u);
        }
        mbar_wait(bars + B_EVT + EV_O * 8, L);
        mbar_wait(bars + B_EVT + (EV_N + EV_O) * 8, L);
        flag_release_p(el, Q.flags + rb * 64 + FR_OL + L);
#pragma unroll 1
        for (int w = 0; w < 2; w++) {
          mbar_wait(bars + B_EVT + (w * EV_N + EV_XS) * 8, L);
          if (!w) mbar_wait(bars + B_AF3 + 96 + XP0 * 8, L);
          if (el) asm volatile("cp.async.bulk.tensor.3d.global.shared::cta.tile.bulk_group [%0, {%2, %3, %4}], [%1];\ncp.async.bulk.commit_group;\ncp.async.bulk.wait_group.read 0;" ::"l"(&P.res[1]), "r"(sb + SM_STG + 9216), "r"(j * 72), "r"(rb * 64 + (w ^ 1) * 32), "r"(0) : "memory");
          __syncwarp();
          if (lane < 2 && !w) mbar_arrive(bars + B_S5);
        }
        sts64(sb + SM_CV + 512 + lane * 8, 0x3f803f80u, 0x3f803f80u);
        fence_async_s();
        __syncwarp();
        if (el) { asm volatile("cp.async.bulk.wait_group 0;" ::: "memory"); mbar_arrive(bars + B_GATE3); }
        const uint32_t tag = epoch * 2 + L + 1;
        asm volatile("" : "+r"(lane));
#pragma unroll 1
        for (int b = 0; b < 8; b++) {
          if (!(b & 3)) {
            const int mb = b >> 2;
            mbar_wait(bars + B_ZS + mb * 8, L);
            pause<ZD1>(Q.zero);
            TRC(el && !mb, 2, L * 16 + 8);
            uint4 v;
#pragma unroll 1
            for (int it = 0; it < (1 << 22); it++) {
              v = ll_ld128(Q.ZST + ((rb * 2 + mb) * 8 + (lane >> 2)) * 32 + 4 * j + (lane & 3));
              if (__all_sync(~0u, max(max(v.x, v.y), max(v.z, v.w)) != ~0u)) break;
            }
            if (lane < 2 && !mb) mbar_arrive(bars + B_S5);
            const bool o = lane & 16;
            float ss = __uint_as_float(o ? v.y : v.x) + __shfl_xor_sync(~0u, __uint_as_float(o ? v.x : v.y), 16), sq = __uint_as_float(o ? v.w : v.z) + __shfl_xor_sync(~0u, __uint_as_float(o ? v.z : v.w), 16);
            ss += __shfl_xor_sync(~0u, ss, 4); sq += __shfl_xor_sync(~0u, sq, 4); ss += __shfl_xor_sync(~0u, ss, 8); sq += __shfl_xor_sync(~0u, sq, 8);
            const float mean = ss * (1.f / FH), rs = blo(pack2(rsq_fast(fmaxf(fmaf(sq, 1.f / FH, -mean * mean), 0.f) + 4.f * GA * GA * LN_EPS), 0.f));
            if (!(lane & 12)) ll_st64(Q.RT + (mb * 16 + rb) * 64 + 8 * j + 2 * (lane & 3) + (lane >> 4), pack2(rs, rs * (mean - blo(lds32(sb + SM_OFF)))), tag);
            TRC(el && !mb, 2, L * 16 + 10);
            pause<ZD2>(Q.zero);
          }
          uint4 v[4];
#pragma unroll 1
          for (int it = 0; it < (1 << 22); it++) {
            bool ok = true;
#pragma unroll
            for (int u = 0; u < 4; u++) { v[u] = ll_ld128((const uint4*)Q.RT + b * 128 + u * 32 + lane); ok = ok && v[u].y == tag && v[u].w == tag; }
            if (__all_sync(~0u, ok)) break;
          }
#pragma unroll
          for (int u = 0; u < 4; u++) {
            const uint32_t rt = sb + SM_RT + b * 512 + u * 128, ro = (lane >> 3) * 32 + (lane & 3) * 8 + ((lane >> 2) & 1) * 2;
            sts32(rt + 4096 + lane * 4, __byte_perm(v[u].x, v[u].z, 0x7632));
            asm volatile("st.shared.u16 [%0], %1;\nst.shared.u16 [%0 + 4], %2;" ::"r"(rt + ro), "h"((uint16_t)v[u].x), "h"((uint16_t)v[u].z) : "memory");
          }
          __syncwarp();
          if (el && (b & 1)) mbar_arrive(bars + B_RT + (b - 1) * 4);
          TRC(el && b < 2, 2, L * 16 + 11 + b);
        }
        TRC(el, 2, L * 16 + 9);
        mbar_wait(bars + B_EVT + EV_Z1 * 8, L);
        mbar_wait(bars + B_EVT + (EV_N + EV_Z1) * 8, L);
        fence_gpu();
        if (el) mbar_arrive(bars + B_Z1);
      }
    }
  } else {
    int w = wid >> 2, q = wid & 3, rb = bid & 15, j = bid >> 4;
    int g = lane >> 2, t = lane & 3;
#define PHASE asm volatile("" : "+r"(w), "+r"(q), "+r"(rb), "+r"(j))
#define stg (sb + SM_STG + w * 9216)
#define pw (q >> 1)
#define pq (2 - 2 * w + (q & 1))
    const bool tr = (tid & 127) == 0;
    (void)tr;
    Cur c{0, 0};
    const uint32_t ebar = mapa(bars + B_EMPTY, (bid & 1) ^ (lane & 1));
    auto release = [&](uint32_t s) { if (lane < 2) mbar_arrive_cluster(ebar + s * 8); };
    uint32_t ia = 0;
    auto wait_ab = [&]() { mbar_wait_c(bars + B_FULL + c.s * 8, c.ph); mbar_wait_c(bars + B_FULLA + w * 32 + c.s * 8, (ia >> c.s) & 1); ia ^= 1u << c.s; };
    uint32_t rp = 0;
    auto check = [&](auto n, uint32_t dst, const uint8_t* src) {
      const uint32_t a = dst + lane * 32 + (lane >> 2) * 4;
#pragma unroll 1
      for (int it = 0; it < (1 << 16); it++) {
        uint32_t x = lds32(a);
#pragma unroll
        for (int e = 1; e < n.value; e++) x = max(x, lds32(a + e * 1024));
        if (!__any_sync(~0u, x == ~0u)) break;
        fence_async_s();
        __syncwarp();
        const uint32_t el = elect_one();
        expect_tx_p(el, bars + B_RB + q * 8, n.value * 1024);
        bulk_load_p(el, dst, src, n.value * 1024, bars + B_RB + q * 8);
        mbar_wait_c(bars + B_RB + q * 8, rp & 1);
        rp++;
      }
    };
    auto signal = [&](int e) { __syncwarp(); if (lane == 0) mbar_arrive(bars + B_EVT + w * EV_N * 8 + e * 8); };
    TRC(tr, w, 0);

    {
      uint8_t* dst = Q.WQ + j * WQ_SL + rb * 3456 + tid * 16;
#pragma unroll
      for (int u = 0; u < 5; u++) {
        stg128_if((u < 4 || rb < 8) && tid < 216, dst + u * (16 * 3456), wv[u].x, wv[u].y, wv[u].z, wv[u].w);
        if (u == 0) TRC(tr, w, 60);
      }
      if (Q.zero == 0) {
        float s[8];
#pragma unroll
        for (int u = 0; u < 5; u++) {
          const uint32_t x[4] = {wv[u].x, wv[u].y, wv[u].z, wv[u].w};
#pragma unroll
          for (int e = 0; e < 4; e++) { s[2 * e] = u ? s[2 * e] + blo(x[e]) : blo(x[e]); s[2 * e + 1] = u ? s[2 * e + 1] + bhi(x[e]) : bhi(x[e]); }
        }
#pragma unroll
        for (int m = 4; m; m >>= 1) {
#pragma unroll
          for (int e = 0; e < m; e++) s[e] = ((tid & m) ? s[e + m] : s[e]) + __shfl_xor_sync(~0u, (tid & m) ? s[e] : s[e + m], m);
        }
        stg32_if(tid < 216, Q.CSP + bid * 216 + tid, __float_as_uint(s[0]));
      }
      __syncwarp();
      if (lane == 0) mbar_arrive(bars + B_IMG);
    }
    reg_alloc<224>();
    auto fetch_wo = [&]() {
#pragma unroll 1
      for (int u = tid; u < 328; u += 256) {
        const int m = min(41 * rb + (u >> 3), 647), k8 = m / 9;
        cp_async16(sb + SM_WOI + u * 16, (const uint8_t*)Q.wo + (8 * k8 + (u & 7)) * (DM * 2) + (72 * j + 8 * (m - k8 * 9)) * 2);
      }
    };
    const uint32_t epoch = ldcg32(Q.flags + (rb * 2 + w) * 32 + FR_EP + j);
    TRC(tr, w, 1);

#pragma unroll 1
    for (int L = 0; L < 2; L++) {
      const int tb = 2 + L * 24;
      asm volatile("" : "+r"(lane), "+r"(g), "+r"(t));
      PHASE;
      (void)tb;
      const uint32_t tag = epoch * 2 + L + 1;
      {
        uint32_t Pk[27][2];
        float rk[2][2], sc[2][2];
        const bool up0 = 2 * t > g, up1 = 2 * t + 1 > g;
        constexpr int HA_[6] = {0, 2, 4, 7, 12, 15}, HC_[6] = {6, 9, 10, 11, 14, 17};
        const bool remote = pq == 0 && rb > 0;
        uint4* hp = Q.HALO + ((((rb - (pq == 0)) * 2 + pw) * 8 + j) * 6) * 32 + lane;
        const uint32_t att = 2 * ST_BYTES + pw * 3072 + lane * 16;
        const uint8_t* hs = remote ? (const uint8_t*)hp : smem_raw + att + (pq == 3 ? 0 : pq == 2 ? ST_BYTES + 8192 : 8192);
        uint8_t* od = z1_block(rb, w, 0) + (9 * j) * 1024 + (4 * (q & 1) + pw) * 128 + lane * 4;
        ACLK_INIT;
        {
          float acc[108];
#pragma unroll
          for (int i = 0; i < 108; i++) acc[i] = 0.f;
          float sx[2] = {0.f, 0.f}, sq[2] = {0.f, 0.f};
          uint32_t prev = 0;
#pragma unroll 1
          for (int kb = 0; kb < 7; kb++) {
            wait_ab();
            TRC(tr && kb == 0, w, tb + 0);
            PCLK(kb * 4);
            const uint32_t st = sb + c.s * ST_BYTES, da = dlo(st + w * 8192, 16), db = dlo(st + ST_B, 3456);
            wgmma_fence();
#pragma unroll
            for (int kk = 0; kk < 4; kk++) {
              wgmma_ss_n216(acc, dsc<1024, 1>(da, kk * 32), dsc<128, 0>(db, kk * 6912), 1);
              if (kk == 0) { wgmma_commit(); wgmma_wait<1>(); if (kb > 0) release(prev); }
              if (kk == 3) wgmma_commit();
              if (kk == XK1) {
            if (kb >= KS && kb < KS + 3) {
              mbar_wait_c(bars + B_WT + w * 8, 0);
#pragma unroll
              for (int u = 0; u < 3; u++) {
                const uint2 x = lds64(stg + (2 * q + (lane >> 4)) * 1152 + (lane & 15) * 8 + (kb - KS) * 384 + u * 128);
                sx[0] += blo(x.x) + bhi(x.x); sx[1] += blo(x.y) + bhi(x.y);
                sq[0] = fmaf(blo(x.x), blo(x.x), fmaf(bhi(x.x), bhi(x.x), sq[0])); sq[1] = fmaf(blo(x.y), blo(x.y), fmaf(bhi(x.y), bhi(x.y), sq[1]));
              }
            }
            if (kb == KS + 3) {
              const bool o = lane & 1;
              float v = (o ? sq[0] + sq[1] : sx[0] + sx[1]) + __shfl_xor_sync(~0u, o ? sx[0] + sx[1] : sq[0] + sq[1], 1);
              v += __shfl_xor_sync(~0u, v, 2); v += __shfl_xor_sync(~0u, v, 4); v += __shfl_xor_sync(~0u, v, 8);
              const float m = v * (-1.f / DM), r = rsq_fast(fmaxf(fmaf(__shfl_xor_sync(~0u, v, 1), 1.f / DM, -m * m), 0.f) + LN_EPS);
              ll_st128_if(!(lane & 15), Q.XST + rb * 256 + (lane >> 4) * 128 + (1 - w) * 64 + 8 * j + 2 * q, m, r, tag);
            }
              }
              if (kk == XK2 && L == 0) {
            if (kb == 0) fetch_wo();
            if (kb == 3) {
              asm volatile("cp.async.wait_all;" ::: "memory");
              fence_async_s();
              __syncwarp();
              if (lane == 0) mbar_arrive(bars + B_WOI);
            }
              }
            }
            prev = c.s; c.next();
          }
          const uint32_t ls = sb + L * (3 * ST_BYTES), cs = ls + SM_CSQ + t * 8;
          float2 cv[27];
          mbar_wait_c(bars + B_XRW + 8, L);
#pragma unroll
          for (int kb = 7; kb < 9; kb++) {
            wait_ab();
            PCLK(kb * 4);
            const uint32_t st = sb + c.s * ST_BYTES, da = dlo(st + w * 8192, 16), db = dlo(st + ST_B, 3456);
            wgmma_fence();
#pragma unroll
            for (int kk = 0; kk < 4; kk++) {
              wgmma_ss_n216(acc, dsc<1024, 1>(da, kk * 32), dsc<128, 0>(db, kk * 6912), 1);
              if (kk == 0) { wgmma_commit(); wgmma_wait<1>(); release(prev); }
              if (kb == 7 && kk < 3) {
#pragma unroll
                for (int G = 9 * kk; G < 9 * kk + 9; G++) cv[G] = lds64f(cs + G * 32);
                wgmma_fence();
              }
            }
            wgmma_commit();
            prev = c.s; c.next();
          }
          mbar_wait_c(bars + B_CSQ, L);
          const uint32_t xs = ls + SM_XST + pw * 768 + 256 + pq * 128;
          const float2 n0 = lds64f(xs + g * 8), n1 = lds64f(xs + g * 8 + 64);
          const float m0 = n0.x, m1 = n1.x;
#pragma unroll
          for (int u = 0; u < 4; u++) {
            rk[u >> 1][u & 1] = __uint_as_float(lds32(xs + t * 16 + ((u & 1 ? up1 : up0) ? -64 : 0) + (u & 1) * 8 + (u >> 1) * 64 + 4));
            sc[u >> 1][u & 1] = rk[u >> 1][u & 1] * ((u >> 1 ? n1.y : n0.y) * (0.23570226039551584f * 1.4426950408889634f));
          }
          PCLK(36);
          wgmma_wait<0>();
          PCLK(37);
          release(prev);
          TRC(tr, w, tb + 1);
          ACLK(0);
#pragma unroll
          for (int G = 9; G < 27; G++) Pk[G][1] = pack2(fmaf(m1, cv[G].x, acc[4 * G + 2]), fmaf(m1, cv[G].y, acc[4 * G + 3]));
          if (pq < 3) {
#pragma unroll
            for (int i = 0; i < 6; i++) sts128(sb + att + (pq & 1) * ST_BYTES + w * 8192 + i * 512, Pk[9 + HA_[i]][1], Pk[10 + HA_[i]][1], tag, Pk[9 + HC_[i]][1]);
            if (w) bar_arrive(1, 256);
          } else if (rb < 15) {
#pragma unroll
            for (int i = 0; i < 6; i++) ll_st128(hp + i * 32, __uint_as_float(Pk[9 + HA_[i]][1]), __uint_as_float(Pk[10 + HA_[i]][1]), tag, __uint_as_float(Pk[9 + HC_[i]][1]));
          }
#pragma unroll
          for (int G = 0; G < 27; G++) {
            Pk[G][0] = pack2(fmaf(m0, cv[G].x, acc[4 * G]), fmaf(m0, cv[G].y, acc[4 * G + 1]));
            if (G < 9) Pk[G][1] = pack2(fmaf(m1, cv[G].x, acc[4 * G + 2]), fmaf(m1, cv[G].y, acc[4 * G + 3]));
          }
        }
        ACLK(1);
        constexpr int GA_[4] = {0, 2, 4, 7}, GB_[4] = {1, 3, 5, 8}, GC_[4] = {2, 4, 6, 6};
        float S1[4][4], S2[4][4];
        uint32_t qa[4][2], qc[4][2];
#pragma unroll
        for (int h = 0; h < 4; h++) {
#pragma unroll
          for (int r = 0; r < 2; r++) {
            qa[h][r] = (h == 0 || h == 3 || t >= h) ? Pk[GA_[h]][r] : 0u;
            qc[h][r] = (h == 3 ? t == 3 : t <= h) ? Pk[GC_[h]][r] : 0u;
          }
#pragma unroll
          for (int i = 0; i < 4; i++) S1[h][i] = S2[h][i] = 0.f;
          mma16(S1[h], qa[h][0], qa[h][1], Pk[GB_[h]][0], Pk[GB_[h]][1], Pk[9 + GA_[h]][0], Pk[9 + GB_[h]][0]);
          mma16(S2[h], qa[h][0], qa[h][1], Pk[GB_[h]][0], Pk[GB_[h]][1], Pk[9 + GA_[h]][1], Pk[9 + GB_[h]][1]);
        }
#pragma unroll
        for (int h = 0; h < 4; h++) {
          mma8(S1[h], qc[h][0], qc[h][1], Pk[9 + GC_[h]][0]);
          mma8(S2[h], qc[h][0], qc[h][1], Pk[9 + GC_[h]][1]);
        }
        uint32_t V1[9], V2[9];
#pragma unroll
        for (int i = 0; i < 9; i++) { V1[i] = movm(Pk[18 + i][0]); V2[i] = movm(Pk[18 + i][1]); }
        uint4 hv[6];
        auto look = [&]() {
          bar_sync(1 + w, 256 - 128 * w);
          if (w) mbar_wait_c(bars + B_HOLD, L);
#pragma unroll
          for (int i = 0; i < 6; i++) hv[i] = ll_ld128g(hs + i * 512);
        };
        const uint32_t mup = (up0 ? 0xffffu : 0u) | (up1 ? 0xffff0000u : 0u);
        auto finish = [&](const float (&x0)[4], const float (&x1)[4], const uint32_t (&Vb)[9], uint32_t ma, int hi) {
          uint32_t p[4], n[4];
          float rs[4];
#pragma unroll
          for (int h = 0; h < 4; h++) {
            const float m = qmax(fmaxf(x0[h], x1[h])), e0 = ex2(x0[h] - m), e1 = ex2(x1[h] - m);
            n[h] = pack2(e0, e1);
            p[h] = pack2(e0 * rk[hi][0], e1 * rk[hi][1]);
          }
          if (hi) look();
#pragma unroll
          for (int h = 0; h < 4; h += 2) {
            float D[4] = {0.f, 0.f, 0.f, 0.f};
            mma8(D, n[h], n[h + 1], 0x3f803f80u);
            rs[h] = rcp_fast(D[0]); rs[h + 1] = rcp_fast(D[2]);
          }
#pragma unroll
          for (int i = 0; i < 9; i++) {
            const int h = i < 4 ? 0 : i == 4 ? 1 : 2;
            const bool nx = (i == 2 || i == 4 || i == 6) ? 2 * t >= i : i == 3 || i > 6;
            float O[4] = {0.f, 0.f, 0.f, 0.f};
            mma16(O, p[h] & ma, p[h + 1] & ma, p[h] & ~ma, p[h + 1] & ~ma, V1[i], Vb[i]);
            const float r = nx ? rs[h + 1] : rs[h];
            stg32(od + i * 1024 + hi * 256, pack2((nx ? O[2] : O[0]) * r, (nx ? O[3] : O[1]) * r));
          }
        };
        {
          float x0[4], x1[4];
#pragma unroll
          for (int h = 0; h < 4; h++) { x0[h] = (up0 ? S1[h][2] : S2[h][2]) * sc[1][0]; x1[h] = (up1 ? S1[h][3] : S2[h][3]) * sc[1][1]; }
          finish(x0, x1, V2, mup, 1);
        }
        ACLK(2);
        if (lane + w == 0) mbar_arrive(bars + B_HOLD);
        if (remote) {
#pragma unroll 1
          for (int it = 0; it < (1 << 20); it++) {
            bool ok = true;
#pragma unroll
            for (int i = 0; i < 6; i++) ok = ok && hv[i].z == tag;
            if (__all_sync(~0u, ok)) break;
#pragma unroll
            for (int i = 0; i < 6; i++) hv[i] = ll_ld128g(hs + i * 512);
          }
        }
        uint32_t H[18];
#pragma unroll
        for (int i = 0; i < 6; i++) { H[HA_[i]] = hv[i].x; H[HA_[i] + 1] = hv[i].y; H[HC_[i]] = hv[i].w; }
        float S0[4][4];
#pragma unroll
        for (int h = 0; h < 4; h++) {
#pragma unroll
          for (int i = 0; i < 4; i++) S0[h][i] = 0.f;
          mma16(S0[h], qa[h][0], qa[h][1], Pk[GB_[h]][0], Pk[GB_[h]][1], H[GA_[h]], H[GB_[h]]);
        }
#pragma unroll
        for (int h = 0; h < 4; h++) mma8(S0[h], qc[h][0], qc[h][1], H[GC_[h]]);
        uint32_t V0[9];
#pragma unroll
        for (int i = 0; i < 9; i++) V0[i] = movm(H[9 + i]);
        ACLK(3);
        {
          const bool nohalo = (rb | pq) == 0;
          const float b0 = up0 && nohalo ? -INFINITY : 0.f, b1 = up1 && nohalo ? -INFINITY : 0.f;
          float x0[4], x1[4];
#pragma unroll
          for (int h = 0; h < 4; h++) { x0[h] = fmaf(up0 ? S0[h][0] : S1[h][0], sc[0][0], b0); x1[h] = fmaf(up1 ? S0[h][1] : S1[h][1], sc[0][1], b1); }
          finish(x0, x1, V0, ~mup, 0);
        }
        ACLK(4);
        signal(EV_O);
        ACLK_OUT;
        OCLK(q == 1, 4, w * 8 + 6);
        TRC(tr, w, tb + 2);
      }
      if (c.s) { c.s = 0; c.ph ^= 1; }
      PHASE;
      {
        float acc[36];
        const int hw = rb * 2 + w;
        const uint32_t xt = stg + (8 * q + g) * 144 + t * 4;
        uint32_t xm = sb + SM_STG + 9216 + (8 * q + (lane & 7)) * 144 + (lane & 8) * 576 + (lane & 16);
        uint8_t* xn = xn_block(hw) + j * 9216 + q * 256 + lane * 4;
        uint32_t* sp = (uint32_t*)(Q.ST1 + (hw * 8 + j) * 32 + 8 * q) + lane;
        const uint4* sg = Q.ST1 + (hw * 8 + t) * 32 + 8 * q + g;
        asm volatile("" : "+r"(xm), "+l"(xn), "+l"(sp), "+l"(sg));
        mbar_wait_c(bars + B_RES + w * 8, L);
        TRC(tr, w, tb + 21);
#pragma unroll
        for (int i = 0; i < 18; i++) { const uint32_t x = lds32(xt + (i >> 1) * 16 + (i & 1) * 4608); acc[2 * i] = blo(x); acc[2 * i + 1] = bhi(x); asm volatile("" : "+f"(acc[2 * i]), "+f"(acc[2 * i + 1])); }
        mbar_wait_c(bars + B_WF, L);
        const uint32_t db = dlo(sb, 1152), of = bars + (w ? B_OF + 40 : B_AV + 96);
        uint32_t da[5];
#pragma unroll
        for (int e = 0; e < 5; e++) da[e] = __shfl_sync(~0u, dlo(sb + o_place(w, e), 1024), 0);
        if (w) {
#pragma unroll 1
          for (int kb = q; kb < 9; kb += 4) {
            const uint32_t e = (kb + 1) >> 1;
            mbar_wait_c(bars + B_OF + e * 8, L);
            OCLK(1, 5, kb);
            check(Int<8>{}, sb + o_place(0, e) + (kb && !(kb & 1)) * 8192, z1_block(rb, 0, 0) + kb * 8192);
            OCLK(1, 5, 16 + kb);
            if (lane <= !kb) mbar_arrive(bars + B_AV + (12 + e) * 8);
          }
          bar_sync(7, 256);
        }
        mbar_wait_c(of, L & w);
        TRC(tr, w, tb + 3);
        OCLK(q == 1, 4, w * 8);
        wgmma_fence();
#pragma unroll
        for (int kk = 0; kk < 4; kk++) wgmma_ss_n72(acc, dsc<128, 0>(da[0], kk * 2048), dsc<128, 0>(db, kk * 2304), 1);
        wgmma_commit();
#pragma unroll 1
        for (int h = 0; h < 2; h++) {
#pragma unroll
          for (int u = 0; u < 4; u++) {
            if (!(u & 1)) { mbar_wait_c(of + 8 + h * 16 + u * 4, 1 + 2 * h + (u >> 1) < SPL ? L & w : L); OCLK(q == 1, 4, w * 8 + 1 + 2 * h + (u >> 1)); wgmma_fence(); }
            if (u == 3 && h && !w) bar_arrive(7, 256);
#pragma unroll
            for (int kk = 0; kk < 4; kk++) wgmma_ss_n72(acc, dsc<128, 0>(da[1 + (u >> 1)], (u & 1) * 8192 + kk * 2048), dsc<128, 0>(db + h * 2304, (1 + u) * 9216 + kk * 2304), 1);
            if (u != 2) wgmma_commit();
            if (u == 0) { wgmma_wait<1>(); if (lane + w == 0 && h) mbar_arrive(bars + B_X3); }
          }
          da[1] = da[3]; da[2] = da[4];
        }
        RCLK_INIT;
        wgmma_wait<0>();
        RCLK(0);
        OCLK(q == 1, 4, w * 8 + 5);
        if (lane < 2) mbar_arrive_cluster(ebar + B_XD - B_EMPTY + w * 8);
        TRC(tr && P5TRACE != 5, w, tb + 4);
        {
          float s0 = 0.f, s1 = 0.f, q0 = 0.f, q1 = 0.f;
#pragma unroll
          for (int i = 0; i < 36; i++) {
            if (i & 2) { s1 += acc[i]; q1 = fmaf(acc[i], acc[i], q1); } else { s0 += acc[i]; q0 = fmaf(acc[i], acc[i], q0); }
          }
          const bool o1 = t & 1, o2 = t & 2;
          const float ss = (o1 ? s1 : s0) + __shfl_xor_sync(~0u, o1 ? s0 : s1, 1), sq = (o1 ? q1 : q0) + __shfl_xor_sync(~0u, o1 ? q0 : q1, 1);
          const float v = (o2 ? sq : ss) + __shfl_xor_sync(~0u, o2 ? ss : sq, 2);
          asm volatile("st.relaxed.gpu.global.u32 [%0], %1;" ::"l"(sp), "r"(__float_as_uint(v)) : "memory");
        }
        RCLK(1);
        RCLK(2);
        pause<PDEL>(Q.zero);
        uint4 pa, pb;
        auto there = [&](const uint4& a, const uint4& b) { return __all_sync(~0u, max(max(max(a.x, a.y), max(a.z, a.w)), max(max(b.x, b.y), max(b.z, b.w))) != ~0u); };
#pragma unroll 1
        for (int it = 0; it < (1 << 20); it++) {
          pa = ll_ld128(sg); pb = ll_ld128(sg + 128);
          if (there(pa, pb)) break;
        }
        RCLK(3);
        float mean0 = qsum(__uint_as_float(pa.x) + __uint_as_float(pb.x)) * (-1.f / DM), mean1 = qsum(__uint_as_float(pa.y) + __uint_as_float(pb.y)) * (-1.f / DM);
        const float rs0 = GA * rsq_fast(fmaxf(fmaf(qsum(__uint_as_float(pa.z) + __uint_as_float(pb.z)), 1.f / DM, -mean0 * mean0), 0.f) + LN_EPS);
        const float rs1 = GA * rsq_fast(fmaxf(fmaf(qsum(__uint_as_float(pa.w) + __uint_as_float(pb.w)), 1.f / DM, -mean1 * mean1), 0.f) + LN_EPS);
        mean0 *= rs0; mean1 *= rs1;
#pragma unroll
        for (int i = 0; i < 18; i++) {
          const float a = (i & 1) ? rs1 : rs0, b = (i & 1) ? mean1 : mean0;
          stg32(xn + (i >> 1) * 1024 + (i & 1) * 128, pack2(fmaf(acc[2 * i], a, b), fmaf(acc[2 * i + 1], a, b)));
        }
        signal(EV_X1);
        RCLK(4);
        if (w) {
#pragma unroll 1
          for (int u = q; u < 24; u += 4) {
            const uint32_t mb = u < 2 * SPL ? u >= SPL : u & 1, k = u < 2 * SPL ? u - mb * SPL : u >> 1;
            mbar_wait_c(bars + B_AF3 + mb * 96 + k * 8, L);
            SCLK3(u);
            check(Int<6>{}, sb + k * 12288 + mb * 6144, xn_block(rb * 2 + mb) + k * 6144);
            SCLK3(24 + u);
            if (lane <= (u < 2 * SPL)) mbar_arrive(bars + B_AV + (u < SPL ? 12 + k : k) * 8);
          }
          TRVI(lane == 0 && P5TRACE != 5, 5, 56 + L * 4 + q, rp);
          mbar_wait_c(bars + B_S5, 0);
        }
#pragma unroll
        for (int u = 0; u < 4; u++)
          stsm4(xm + u * 32, pack2(acc[8 * u], acc[8 * u + 1]), pack2(acc[8 * u + 2], acc[8 * u + 3]), pack2(acc[8 * u + 4], acc[8 * u + 5]), pack2(acc[8 * u + 6], acc[8 * u + 7]));
        asm volatile("stmatrix.sync.aligned.m8n8.x2.shared.b16 [%0], {%1,%2};" ::"r"(xm + 128), "r"(pack2(acc[32], acc[33])), "r"(pack2(acc[34], acc[35])) : "memory");
        fence_async_s();
        signal(EV_XS);
        RCLK(5);
        TRC(tr, w, tb + 5);
        RCLK(6);
        RCLK_OUT;
      }
      PHASE;
      {
      float acc[160];
#pragma unroll
      for (int i = 0; i < 160; i++) acc[i] = 0.f;
      float s[2] = {0.f, 0.f}, qq[2] = {0.f, 0.f}, zo = 0.f;
      const uint32_t zp = sb + SM_ZP3 + (tid & 127) * 4;
      auto zstat = [&](int mb, bool on) {
        const bool o1 = t & 1, o2 = t & 2;
        const float ss = ((o1 ? s[1] : s[0]) + __shfl_xor_sync(~0u, o1 ? s[0] : s[1], 1)) * 0x1p60f, sq = (o1 ? qq[1] : qq[0]) + __shfl_xor_sync(~0u, o1 ? qq[0] : qq[1], 1);
        const uint32_t v = __float_as_uint((o2 ? sq : ss) + zo + __shfl_xor_sync(~0u, o2 ? ss : sq, 2));
        asm volatile("{\n.reg .pred p, q, r;\nsetp.eq.u32 p, %4, 1;\nsetp.eq.u32 q, %4, 2;\nsetp.eq.and.u32 r, %5, 0, q;\n@p st.shared.u32 [%0], %2;\n@p bar.arrive 13, 256;\n"
                     "@q st.relaxed.gpu.global.u32 [%1], %2;\n@r mbarrier.arrive.shared::cta.b64 _, [%3];\n}" ::"r"(zp + mb * 512), "l"((uint32_t*)(Q.ZST + ((rb * 2 + mb) * 8 + j) * 32) + (tid & 127)),
                     "r"(v), "r"(bars + B_ZS + mb * 8), "r"(on ? 1 + w : 0), "r"(lane) : "memory");
        s[0] = s[1] = qq[0] = qq[1] = 0.f;
      };
      const uint32_t ebar3 = ebar + (B_E3 - B_EMPTY);
#pragma unroll 1
      for (int half = 0; half < 2; half++) {
        const bool big = half != w;
        auto rel3 = [&](int p) { if (lane < 2) mbar_arrive_cluster(ebar3 + p * 8); };
        auto pass = [&](auto nk) {
          constexpr int NK = nk.value;
          uint32_t d0 = dlo(sb, 1024), ph = half & ~w, af = bars + B_AV;
          const uint32_t db = dlo(sb + SM_B3, NK == 3 ? 6144 : 2048);
          const bool lead = NK == 3 && !half;
          if (lead) {
#pragma unroll
            for (int u = 0; u < 2 * SPL; u++) {
              const int mb = u / SPL, p = u % SPL;
              if (!mb) mbar_wait_c(bars + B_F3 + p * 8, 0);
              mbar_wait_c(af + (mb ? p : 12 + p) * 8, mb || p > 4 ? L : 1);
              TRC(tr && u == 0, w, tb + 6);
              SCLK2(u);
              if (p == 0) SCLK(mb * 4);
              wgmma_fence();
#pragma unroll
              for (int kk = 0; kk < 3; kk++) {
                wgmma_ss_n128(acc + mb * 80, dsc<128, 0>(d0, p * 12288 + kk * 2048 + mb * 6144), dsc<1024, 1>(db, p * 12288 + kk * 2048), p + kk > 0);
                if (kk == 0 && u > SPL) { wgmma_commit(); wgmma_wait<1>(); rel3(p - 1); }
              }
              wgmma_commit();
            }
          }
#pragma unroll 1
          for (int it = 0; it < 6 / NK; it++) {
#pragma unroll
            for (int p = 0; p < 6; p++) {
              if (p < SPL && lead && it == 0) continue;
              if (NK == 3) mbar_wait_c(af + p * 8, L);
              if (p == 0 && it == 0) bar_sync(6 + w, 256);
              mbar_wait_c(bars + B_F3 + p * 8, ph);
              TRC(tr && p == 0 && it == 0, w, tb + 6 + half * 4);
              if (lead) SCLK2(12 + it * 6 + p);
              if (NK == 2 ? !(p & 1) : p % 3 == 0) SCLK(half * 11 + (NK == 2 ? it * 3 + p / 2 : it * 2 + p / 3));
              wgmma_fence();
#pragma unroll
              for (int u = 0; u < 2 * NK; u++) {
                const int kk = u >> 1, mb = u & 1, e = p * NK + kk;
                const uint64_t da = dsc<128, 0>(d0, (e / 3) * 12288 + (e % 3) * 2048 + mb * 6144);
                if (NK == 3) wgmma_ss_n128(acc + mb * 80, da, dsc<1024, 1>(db, p * 12288 + kk * 2048), e > 0 || it > 0);
                else wgmma_ss_n160(acc + mb * 80, da, dsc<1024, 1>(db, p * 12288 + kk * 6144), e > 0 || it > 0);
                if (u == 0) { wgmma_commit(); wgmma_wait<1>(); if (p > 0 || it > 0) rel3((p + 5) % 6); }
                if (p * 8 + u == (NK == 2 ? HO3 : HO4) && it == 6 / NK - 1) bar_arrive(7 - w, 256);
              }
              wgmma_commit();
            }
            d0 += NK * 1536; af += 48;
            ph ^= 1;
          }
        };
        const int go = (j & 1) ? (big ? 0 : 20) : (big ? 16 : 0);
        const float* gbp = (const float*)(smem_raw + SM_OFF + 8);
        asm volatile("" : "+l"(gbp));
        uint8_t* zd = half ? z1_block(rb, 0, j) + go * 1024 + (q & 1) * 2048 + (q >> 1) * 512 + lane * 16 : z2_block(rb, j) + q * 9216 + go * 128 + ((g & 3) * 2 + (g >> 2)) * 16 + t * 4;
        asm volatile("" : "+l"(zd));
        if (big) pass(Int<2>{}); else pass(Int<3>{});
        if (w) { bar_sync(13, 256); zo = __uint_as_float(lds32(zp + half * 512)); }
        if (half) { zstat(1, true); mbar_wait_c(bars + B_S5, 1); }
        const uint32_t off2 = lds32(sb + SM_OFF);
        wgmma_wait<0>();
        SCLK(half * 11 + 9);
        rel3(5);
        TRC(tr, w, tb + 7 + half * 4);
        auto gelu = [&](auto z2) {
          float gate[NC2], gb = GB, gn = GB;
          uint32_t qa[2][3] = {{0, 0, 0}, {0, 0, 0}};
#pragma unroll
          for (int e = 0; e < NC2; e++) gate[e] = GB;
#pragma unroll
          for (int G = 0; G < 20; G++) {
            if (G == 16 && !big) break;
            if (z2.value && G % LD2 == 0) { gb = gn; if (G < 20 - LD2) asm volatile("ld.f32 %0, [%1];" : "=f"(gn) : "l"(gbp) : "memory"); }
#pragma unroll
            for (int r = 0; r < 2; r++) {
              float z[2];
              float& gt = gate[(G * 2 + r) % NC2];
#pragma unroll
              for (int e = 0; e < 2; e++) {
                const float v = acc[4 * G + 2 * r + e];
                z[e] = fmaf(v, tanh_fast(v * fmaf(v, v, gt)), v);
                if (z2.value) { s[r] = fmaf(z[e], 0x1p-60f, s[r]); qq[r] = fmaf(z[e], z[e], qq[r]); }
              }
              const uint32_t pk = pack2(z[0], z[1]);
              if (z2.value) {
                stg32(zd + G * 128 + r * 4608, hsub2(pk, off2));
                gt = fmaf(qq[r], s[r], gb);
              } else {
                if ((G & 3) == 3) stg128(zd + (G >> 2) * 4096 + r * 1024, qa[r][0], qa[r][1], qa[r][2], pk);
                else qa[r][G & 3] = pk;
              }
            }
          }
        };
#pragma unroll 1
        for (int mb = 0;; mb++) {
          if (half) gelu(Int<0>{}); else gelu(Int<1>{});
          if (mb) break;
          zstat(0, !half);
#pragma unroll
          for (int i = 0; i < 80; i++) acc[i] = acc[80 + i];
          zd += half ? 8 * ZB : 128 * ZB;
        }
        mbar_wait_c(bars + B_GATE3, L);
        signal(half ? EV_Z1 : EV_ZN);
        SCLK(half * 11 + 10);
        TRC(tr, w, tb + 8 + half * 4);
      }
      }
      PHASE;
      const uint32_t aoff = (pw * 64 + pq * 16 + (lane & 15)) * 128 + (((lane >> 4) ^ (lane & 7)) << 4);
      uint32_t hA[18][4];
      {
        float acc[144];
        {
          const uint32_t c16 = lds32(sb + SM_OFF + 12), a[4] = {c16, c16, c16, c16};
          wgmma_fence();
          wgmma_rs_n144(acc, a, dsc<0, 0>(dlo(sb + SM_CV + 512, 0), 0), 0);
          wgmma_rs_n144(acc + 72, a, dsc<0, 0>(dlo(sb + SM_CV + 512, 0), 128), 0);
          wgmma_commit();
        }
        uint32_t prev = 0;
        auto stage = [&](int kb, bool odd) {
          mbar_wait_c(bars + B_FULL + c.s * 8, c.ph);
          TRC(tr && kb == 0, w, tb + 13);
          SCLK(22 + kb);
          const uint32_t st = sb + c.s * ST_BYTES, db = dlo(st + ST_B, 4608), rt = sb + SM_RT + kb * 128 + t * 8;
          uint32_t a[4][4];
#pragma unroll
          for (int kk = 0; kk < 4; kk++) {
            uint32_t r[4];
            ldsm4(r, st + (aoff ^ (kk << 5)));
            const uint2 sc = lds64(rt + kk * 32);
            a[kk][0] = hmul2(__byte_perm(r[0], r[2], 0x5410), sc.x); a[kk][2] = hmul2(__byte_perm(r[0], r[2], 0x7632), sc.y);
            a[kk][1] = hmul2(__byte_perm(r[1], r[3], 0x5410), sc.x); a[kk][3] = hmul2(__byte_perm(r[1], r[3], 0x7632), sc.y);
          }
          if (!odd && kb + w == 0) bar_sync(6, 256);
          wgmma_fence();
#pragma unroll
          for (int i = 0; i < 8; i++) {
            const int kk = i & 3, hf = i >> 2;
            wgmma_rs_n144(acc + hf * 72, a[kk], dsc<128, 0>(db, kk * 9216 + hf * 2304), 1);
            if (i == 0) { wgmma_commit(); wgmma_wait<1>(); if (kb) release(prev); }
            if (i == 3) wgmma_commit();
          }
          wgmma_commit();
          prev = c.s; c.next();
        };
#pragma unroll 1
        for (int kb = 0; kb < 32; kb += 2) {
          if (!(kb & 7)) mbar_wait_c(bars + B_RT + kb, L);
          stage(kb, false);
          stage(kb + 1, true);
        }
        mbar_wait_c(bars + B_CV + pw * 8, L);
        const float gk = 0.5f / GA;
        const float c1 = __uint_as_float(lds32(sb + SM_OFF + 4));
        const float gb0 = -gk * (c1 + __uint_as_float(lds32(sb + SM_CV + pw * 256 + (16 * pq + g) * 4))), gb1 = -gk * (c1 + __uint_as_float(lds32(sb + SM_CV + pw * 256 + (16 * pq + g + 8) * 4)));
        if (w == 1) { mbar_wait_c(bars + B_FULL + c.s * 8, c.ph); release(c.s); c.next(); }
        mbar_wait_c(bars + B_FULL + c.s * 8, c.ph);
        const uint32_t zs = sb + c.s * ST_BYTES + ST_B + (tid & 127) * 16;
        uint4 zl, zh;
#pragma unroll
        for (int u = 0; u < 18; u++) {
          if (u == 0) wgmma_wait<1>();
          if (u == 9) {
            wgmma_wait<0>();
            release(prev);
            if (L == 0) signal(EV_PT);
            TRC(tr, w, tb + 14);
            SCLK(54);
          }
          if (!(u & 1)) { zl = lds128(zs + u * 2048); zh = lds128(zs + u * 2048 + 2048); }
          const uint4 z = (u & 1) ? make_uint4(zl.z, zh.z, zl.w, zh.w) : make_uint4(zl.x, zh.x, zl.y, zh.y);
          hA[u][0] = hmul2(z.x, pack2(fmaf(acc[8 * u], gk, gb0), fmaf(acc[8 * u + 1], gk, gb0)));
          hA[u][1] = hmul2(z.y, pack2(fmaf(acc[8 * u + 2], gk, gb1), fmaf(acc[8 * u + 3], gk, gb1)));
          hA[u][2] = hmul2(z.z, pack2(fmaf(acc[8 * u + 4], gk, gb0), fmaf(acc[8 * u + 5], gk, gb0)));
          hA[u][3] = hmul2(z.w, pack2(fmaf(acc[8 * u + 6], gk, gb1), fmaf(acc[8 * u + 7], gk, gb1)));
        }
        __syncwarp();
        release(c.s);
        c.next();
        if (w == 0) { mbar_wait_c(bars + B_FULL + c.s * 8, c.ph); release(c.s); c.next(); }
        TRC(tr, w, tb + 15);
      }
      {
        CLK_INIT;
        if (w == 1) bar_arrive(6, 256);
        uint4 v[4];
#pragma unroll
        for (int u = 0; u < 4; u++) v[u] = make_uint4(0u, 0u, 0u, 0u);
        uint32_t rl = sb + SM_STG + pw * 8192 + pq * 2048 + (lane >> 3) * 128 + (((lane & 7) ^ (lane >> 3)) << 4);
        uint8_t* rd = Q.out + (128 * rb + 32 * pq + 2 * (lane >> 3) + pw) * (DM * 2) + j * 128 + (lane & 7) * 16;
        asm volatile("" : "+r"(rl), "+l"(rd));
        auto send = [&](int u0, int u1) {
#pragma unroll
          for (int u = u0; u < u1; u++)
            asm volatile("red.relaxed.gpu.global.add.noftz.v4.bf16x2 [%0], {%1,%2,%3,%4};" ::"l"(rd + u * (8 * DM * 2)), "r"(v[u].x), "r"(v[u].y), "r"(v[u].z), "r"(v[u].w) : "memory");
        };
#pragma unroll 1
        for (int p = 0; p < 9; p++) {
          float acc[32];
          CLK(0);
          mbar_wait_c(bars + B_FULL + c.s * 8, c.ph);
          const uint32_t db = dlo(sb + c.s * ST_BYTES + ST_B, 0);
          CLK(1);
          bar_sync(6 + w, 256);
          CLK(2);
          wgmma_fence();
#pragma unroll
          for (int kk = 0; kk < 18; kk++) {
            wgmma_rs_n64(acc, hA[kk], dsc<1024, 1>(db, kk * 2048), kk != 0);
            if (kk == PPK && (w == 0 || p < 8)) bar_arrive(7 - w, 256);
          }
          wgmma_commit();
          CLK(3);
          if (p > 0) { send(NOW, 4); rd += p + j == 9 ? -1024 : 128; }
          CLK(5);
          wgmma_wait<0>();
          CLK(4);
          if (L == 0 || p < 5) release(c.s);
          c.next();
          TRC(tr && p == 8, w, tb + 16);
#pragma unroll
          for (int u = 0; u < 4; u++)
            stsm4(sb + SM_STG + (aoff ^ (u << 5)), pack2(acc[8 * u], acc[8 * u + 1]), pack2(acc[8 * u + 2], acc[8 * u + 3]), pack2(acc[8 * u + 4], acc[8 * u + 5]), pack2(acc[8 * u + 6], acc[8 * u + 7]));
          __syncwarp();
#pragma unroll
          for (int u = 0; u < 4; u++) v[u] = lds128(rl + u * 512 ^ (u & 1) << 6);
          send(0, NOW);
        }
        send(NOW, 4);
        TRC(tr, w, tb + 17);
        if (L == 0) signal(EV_PT);
        CLK_OUT;
        TRC(tr, w, tb + 18);
      }
    }
    if ((tid & 127) == 0) Q.flags[(rb * 2 + w) * 32 + FR_EP + j] = epoch + 1;
    if (tid == 0) Q.flags[FJ + j * 32 + FJ_EP + rb] = epoch + 1;
  }
}

typedef CUresult (*EncodeFn)(CUtensorMap*, CUtensorMapDataType, cuuint32_t, void*, const cuuint64_t*, const cuuint64_t*, const cuuint32_t*,
                             const cuuint32_t*, CUtensorMapInterleave, CUtensorMapSwizzle, CUtensorMapL2promotion, CUtensorMapFloatOOBfill);

static void make_map(EncodeFn fn, CUtensorMap* m, const void* ptr, int rank, uint64_t d0, uint64_t d1, uint64_t d2, uint64_t s1, uint64_t s2,
                     uint32_t b0, uint32_t b1, uint32_t b2, CUtensorMapSwizzle swz) {
  cuuint64_t dims[3] = {d0, d1, d2}, strides[2] = {s1, s2};
  cuuint32_t box[3] = {b0, b1, b2}, es[3] = {1, 1, 1};
  fn(m, CU_TENSOR_MAP_DATA_TYPE_BFLOAT16, rank, const_cast<void*>(ptr), dims, strides, box, es, CU_TENSOR_MAP_INTERLEAVE_NONE, swz,
     CU_TENSOR_MAP_L2_PROMOTION_L2_128B, CU_TENSOR_MAP_FLOAT_OOB_FILL_NONE);
}

}

extern "C" void kernel_launch(void* const* d_in, const int* in_sizes, int n_in, void* d_out, int out_size) {
  using namespace mk;
  (void)in_sizes; (void)n_in; (void)out_size;
  static EncodeFn fn = nullptr;
  static Scratch* sc = nullptr;
  if (!fn) {
    cudaDriverEntryPointQueryResult qr;
    cudaGetDriverEntryPoint("cuTensorMapEncodeTiled", (void**)&fn, cudaEnableDefault, &qr);
    cudaGetSymbolAddress((void**)&sc, g_scratch);
    cudaFuncSetAttribute(mega_kernel, cudaFuncAttributeMaxDynamicSharedMemorySize, SM_TOTAL);
  }
  Params p;
  Ptrs a;
  a.x = (const uint8_t*)d_in[0];
  a.wqkv = (const __nv_bfloat16*)d_in[1];
  a.wo = (const __nv_bfloat16*)d_in[2];
  a.w_in = (const __nv_bfloat16*)d_in[4];
  a.w_sp = (const __nv_bfloat16*)d_in[5];
  a.b_sp = (const __nv_bfloat16*)d_in[6];
  a.out = (uint8_t*)d_out;
  a.zero = 0;
  a.WQ = sc->WQ; a.flags = sc->flags; a.CSP = sc->CSP; a.XST = sc->XST; a.HALO = sc->HALO; a.ST1 = sc->ST1; a.ZST = sc->ZST; a.RT = sc->RT; a.Z = sc->Z; a.WO = sc->WO;
  make_map(fn, &p.wsp, a.w_sp, 3, 2048, 1024, 2, 8192, 4096, 64, 64, 2, CU_TENSOR_MAP_SWIZZLE_128B);
  for (int i = 0; i < 2; i++) {
    make_map(fn, &p.act[i], i ? a.out : a.x, 3, DM, 1024, 2, 2304, 1152, 64, 32, 2, CU_TENSOR_MAP_SWIZZLE_128B);
    make_map(fn, &p.res[i], i ? a.out : a.x, 3, DM, 1024, 2, 2304, 1152, 72, 32, 2, CU_TENSOR_MAP_SWIZZLE_NONE);
  }
  for (int i = 0; i < 2; i++) make_map(fn, &p.winb[i], a.w_in + 32 * i, 3, 64, 576, 72 - i, 9216, 128, 64, 16, 3, CU_TENSOR_MAP_SWIZZLE_128B);
  make_map(fn, &p.wins, a.w_in, 3, 64, 576, 72, 9216, 128, 64, 48, 1, CU_TENSOR_MAP_SWIZZLE_128B);
  make_map(fn, &p.wout, d_in[7], 2, 576, 2304, 1, 1152, 0, 64, 144, 1, CU_TENSOR_MAP_SWIZZLE_128B);
  mega_kernel<<<NGRID, 384, SM_TOTAL, cudaStreamPerThread>>>(a, p);
}
```

```cpp
#include <cuda_runtime.h>
#include <cuda.h>
#include <cuda_bf16.h>
#include <stdint.h>

#define MK_TRACE 0
#define MK_DBG 0
#define MK_RUSH 0
#define P5TRACE 0

#define C0S 32.f
#define OFM 0x10u
#define NC2 2
#define LD2 2
#define PDEL 4
#define SDEL 10
#define ZD1 8
#define ZD2 20
#define FD3 8
#define YPACE 2
#define SPL 4
#define XP0 8
#define APACE 7
#define AEP 2
#define PZI 4
#define RFI 3
#define KS 1
#define XK1 1
#define XK2 2
#define HO3 41
#define HO4 41
#define PPK 17
#define NOW 3
#define WTI 12
#define EFM 0x22333022
#define EF(i) ((((EFM >> (4 * (i))) & 3) == 3) || (((EFM >> (4 * (i))) >> L) & 1))

namespace mk {

constexpr int SEQ = 2048, DM = 576, FH = 2304;
constexpr int NCTA = 128;
constexpr int NGRID = 132;
constexpr uint32_t ZB = 36864;
constexpr uint32_t WQ_SL = 72 * 3456;
constexpr uint32_t WO_SL = 72 * 1152;
constexpr float LN_EPS = 1e-5f;
constexpr float GA = 0.3292034911525734f, GB = 2.423681954311584f;

constexpr uint32_t ST_BYTES = 53248, ST_B = 16384, NST = 4;
constexpr uint32_t SM_STG = NST * ST_BYTES;
constexpr uint32_t SM_BAR = SM_STG + 2 * 9216, B_OFF = 896;
constexpr uint32_t SM_OFF = SM_BAR + B_OFF;
constexpr uint32_t SM_TOTAL = SM_BAR + 1024;
constexpr uint32_t SM_RT = SM_STG + 9216, SM_CV = SM_STG + 17408, SM_WT = SM_STG;
constexpr uint32_t SM_WOI = 44032;
constexpr uint32_t SM_CSQ = 3 * ST_BYTES + SM_WOI, SM_XST = SM_CSQ + 896;
enum { EV_PT = 0, EV_O = 1, EV_X1 = 2, EV_ZN = 3, EV_Z1 = 4, EV_XS = 5, EV_N = 6 };
constexpr uint32_t B_FULL = 0, B_FULLA = 32, B_RES = 96, B_WT = 112, B_GATE3 = 128, B_Z1 = 136, B_ZOK = 144, B_CV = 152, B_XRW = 168, B_F3 = 184, B_WF = 232, B_OF = 240,
                   B_RT = 320, B_AF3 = 352, B_RB = 544,
                   B_AD = 576, B_S5 = 608, B_AV = 616, B_CSQ = 760,
                   B_HOLD = 768, B_ZS = 784, B_EVT = 800,
                   B_IMG = 912, B_WOI = 920, B_E3 = 928, B_XD = 976,
                   B_EMPTY = 992;
constexpr uint32_t SM_B3 = 9 * 16384, SM_ZP3 = SM_STG + 8192;

enum { FR_X2 = 0, FR_O = 1, FR_XR = 5, FR_PZ = 9, FR_EP = 16, FJ = 32 * 32, FJ_WQ = 0, FJ_WO = 1, FJ_ZN = 3, FJ_P4 = 5, FJ_EP = 16, F_N = FJ + 8 * 32 };

struct Scratch {
  alignas(1024) uint32_t flags[F_N];
  alignas(1024) float CSP[2 * NCTA * 216];
  alignas(1024) uint2 RT[SEQ];
  alignas(1024) uint4 XST[2 * SEQ];
  alignas(1024) uint4 ST1[SEQ * 4];
  alignas(1024) uint4 ZST[SEQ * 4];
  alignas(1024) uint4 HALO[32 * 8 * 6 * 32];
  alignas(1024) uint8_t WO[8 * WO_SL];
  alignas(1024) uint8_t WQ[8 * WQ_SL];
  alignas(1024) uint8_t Z[512 * ZB];
};
__device__ Scratch g_scratch;

struct Ptrs {
  const __nv_bfloat16* wqkv;
  uint8_t* WQ;
  uint32_t* flags;
  float* CSP;
  const uint8_t* x;
  uint32_t zero;
  uint4 *XST, *HALO, *ST1, *ZST;
  uint2* RT;
  uint8_t *Z, *WO, *out;
  const __nv_bfloat16 *wo, *w_in, *w_sp, *b_sp;
};
struct Params {
  CUtensorMap wsp, winb[2], wins, wout;
  CUtensorMap act[2];
  CUtensorMap res[2];
};

__device__ __forceinline__ uint32_t smem_u32(const void* p) { return (uint32_t)__cvta_generic_to_shared(p); }
__device__ __forceinline__ void mbar_init(uint32_t bar, uint32_t cnt) { asm volatile("mbarrier.init.shared::cta.b64 [%0], %1;" ::"r"(bar), "r"(cnt)); }
__device__ __forceinline__ void mbar_arrive(uint32_t bar) { asm volatile("mbarrier.arrive.shared::cta.b64 _, [%0];" ::"r"(bar) : "memory"); }
__device__ __forceinline__ void mbar_wait(uint32_t bar, uint32_t parity) {
  asm volatile(
      "{\n.reg .pred p;\n.reg .u32 c;\nmov.u32 c, 0;\nLAB_WAIT:\n"
      "mbarrier.try_wait.parity.shared::cta.b64 p, [%0], %1;\n@p bra LAB_DONE;\n"
      "add.u32 c, c, 1;\nsetp.lt.u32 p, c, 0x100000;\n@p bra LAB_WAIT;\ntrap;\nLAB_DONE:\n}" ::"r"(bar), "r"(parity)
      : "memory");
}
__device__ __forceinline__ void mbar_wait_c(uint32_t bar, uint32_t parity) {
  asm volatile("{\n.reg .pred p;\nLAB_WAIT:\nmbarrier.try_wait.parity.shared::cta.b64 p, [%0], %1;\n@!p bra LAB_WAIT;\n}" ::"r"(bar), "r"(parity) : "memory");
}
__device__ __forceinline__ void flag_wait(const uint32_t* f, uint32_t target) {
  asm volatile(
      "{\n.reg .pred p;\n.reg .u32 c, v;\nmov.u32 c, 0;\nLAB_WAIT:\n"
      "ld.relaxed.gpu.global.u32 v, [%0];\nsub.u32 v, v, %1;\nsetp.ge.s32 p, v, 0;\n@p bra LAB_DONE;\n"
      "add.u32 c, c, 1;\nsetp.lt.u32 p, c, 0x400000;\n@p bra LAB_WAIT;\ntrap;\nLAB_DONE:\nfence.acquire.gpu;\n}" ::"l"(f), "r"(target)
      : "memory");
}
__device__ __forceinline__ void fence_gpu() { asm volatile("fence.acq_rel.gpu;" ::: "memory"); }
__device__ __forceinline__ void fence_async_g() { asm volatile("fence.proxy.async.global;" ::: "memory"); }
__device__ __forceinline__ void fence_async_s() { asm volatile("fence.proxy.async.shared::cta;" ::: "memory"); }
__device__ __forceinline__ uint32_t elect_one() {
  uint32_t p; asm volatile("{\n.reg .pred P;\nelect.sync _|P, 0xffffffff;\nselp.u32 %0, 1, 0, P;\n}" : "=r"(p)); return p;
}
__device__ __forceinline__ void expect_tx_p(uint32_t el, uint32_t bar, uint32_t bytes) {
  asm volatile("{\n.reg .pred P;\nsetp.ne.u32 P, %2, 0;\n@P mbarrier.arrive.expect_tx.shared::cta.b64 _, [%0], %1;\n}" ::"r"(bar), "r"(bytes), "r"(el) : "memory");
}
__device__ __forceinline__ void bulk_load_p(uint32_t el, uint32_t dst, const void* src, uint32_t bytes, uint32_t bar) {
  asm volatile("{\n.reg .pred P;\nsetp.ne.u32 P, %4, 0;\n@P cp.async.bulk.shared::cluster.global.mbarrier::complete_tx::bytes [%0], [%1], %2, [%3];\n}" ::"r"(dst), "l"(src), "r"(bytes), "r"(bar), "r"(el) : "memory");
}
__device__ __forceinline__ uint64_t policy_evict_first() { uint64_t p; asm("createpolicy.fractional.L2::evict_first.b64 %0, 1.0;" : "=l"(p)); return p; }
__device__ __forceinline__ void bulk_load_h(uint32_t el, uint32_t dst, const void* src, uint32_t bytes, uint32_t bar, bool ef, uint64_t pol) {
  if (ef) {
    asm volatile("{\n.reg .pred P;\nsetp.ne.u32 P, %4, 0;\n@P cp.async.bulk.shared::cluster.global.mbarrier::complete_tx::bytes.L2::cache_hint [%0], [%1], %2, [%3], %5;\n}" ::"r"(dst), "l"(src), "r"(bytes), "r"(bar), "r"(el), "l"(pol) : "memory");
  } else {
    asm volatile("{\n.reg .pred P;\nsetp.ne.u32 P, %4, 0;\n@P cp.async.bulk.shared::cluster.global.mbarrier::complete_tx::bytes [%0], [%1], %2, [%3];\n}" ::"r"(dst), "l"(src), "r"(bytes), "r"(bar), "r"(el) : "memory");
  }
}
__device__ __forceinline__ void bulk_mc_h(uint32_t el, uint32_t dst, const void* src, uint32_t bytes, uint32_t bar, bool ef, uint64_t pol) {
  if (ef) {
    asm volatile("{\n.reg .pred P;\nsetp.ne.u32 P, %4, 0;\n@P cp.async.bulk.shared::cluster.global.mbarrier::complete_tx::bytes.multicast::cluster.L2::cache_hint [%0], [%1], %2, [%3], %5, %6;\n}" ::"r"(dst), "l"(src), "r"(bytes), "r"(bar), "r"(el), "h"((uint16_t)3), "l"(pol) : "memory");
  } else {
    asm volatile("{\n.reg .pred P;\nsetp.ne.u32 P, %4, 0;\n@P cp.async.bulk.shared::cluster.global.mbarrier::complete_tx::bytes.multicast::cluster [%0], [%1], %2, [%3], %5;\n}" ::"r"(dst), "l"(src), "r"(bytes), "r"(bar), "r"(el), "h"((uint16_t)3) : "memory");
  }
}
__device__ __forceinline__ void tma3d_h(uint32_t el, uint32_t dst, const CUtensorMap* m, int c0, int c1, int c2, uint32_t bar, bool ef, uint64_t pol) {
  if (ef) {
    asm volatile("{\n.reg .pred P;\nsetp.ne.u32 P, %6, 0;\n@P cp.async.bulk.tensor.3d.shared::cluster.global.mbarrier::complete_tx::bytes.L2::cache_hint [%0], [%1, {%3, %4, %5}], [%2], %7;\n}" ::"r"(dst), "l"(m), "r"(bar), "r"(c0), "r"(c1), "r"(c2), "r"(el), "l"(pol) : "memory");
  } else {
    asm volatile("{\n.reg .pred P;\nsetp.ne.u32 P, %6, 0;\n@P cp.async.bulk.tensor.3d.shared::cluster.global.mbarrier::complete_tx::bytes [%0], [%1, {%3, %4, %5}], [%2];\n}" ::"r"(dst), "l"(m), "r"(bar), "r"(c0), "r"(c1), "r"(c2), "r"(el) : "memory");
  }
}
__device__ __forceinline__ void tma2d_mc_h(uint32_t el, uint32_t dst, const CUtensorMap* m, int c0, int c1, uint32_t bar, bool ef, uint64_t pol) {
  if (ef) {
    asm volatile("{\n.reg .pred P;\nsetp.ne.u32 P, %5, 0;\n@P cp.async.bulk.tensor.2d.shared::cluster.global.mbarrier::complete_tx::bytes.multicast::cluster.L2::cache_hint [%0], [%1, {%3, %4}], [%2], %6, %7;\n}" ::"r"(dst), "l"(m), "r"(bar), "r"(c0), "r"(c1), "r"(el), "h"((uint16_t)3), "l"(pol) : "memory");
  } else {
    asm volatile("{\n.reg .pred P;\nsetp.ne.u32 P, %5, 0;\n@P cp.async.bulk.tensor.2d.shared::cluster.global.mbarrier::complete_tx::bytes.multicast::cluster [%0], [%1, {%3, %4}], [%2], %6;\n}" ::"r"(dst), "l"(m), "r"(bar), "r"(c0), "r"(c1), "r"(el), "h"((uint16_t)3) : "memory");
  }
}
__device__ __forceinline__ void tma3d_mc_h(uint32_t el, uint32_t dst, const CUtensorMap* m, int c0, int c1, int c2, uint32_t bar, bool ef, uint64_t pol) {
  if (ef) {
    asm volatile("{\n.reg .pred P;\nsetp.ne.u32 P, %6, 0;\n@P cp.async.bulk.tensor.3d.shared::cluster.global.mbarrier::complete_tx::bytes.multicast::cluster.L2::cache_hint [%0], [%1, {%3, %4, %5}], [%2], %7, %8;\n}" ::"r"(dst), "l"(m), "r"(bar), "r"(c0), "r"(c1), "r"(c2), "r"(el), "h"((uint16_t)3), "l"(pol) : "memory");
  } else {
    asm volatile("{\n.reg .pred P;\nsetp.ne.u32 P, %6, 0;\n@P cp.async.bulk.tensor.3d.shared::cluster.global.mbarrier::complete_tx::bytes.multicast::cluster [%0], [%1, {%3, %4, %5}], [%2], %7;\n}" ::"r"(dst), "l"(m), "r"(bar), "r"(c0), "r"(c1), "r"(c2), "r"(el), "h"((uint16_t)3) : "memory");
  }
}
__device__ __forceinline__ void mbar_arrive_cluster(uint32_t addr) { asm volatile("mbarrier.arrive.shared::cluster.b64 _, [%0];" ::"r"(addr) : "memory"); }
__device__ __forceinline__ uint32_t mapa(uint32_t addr, uint32_t rank) { uint32_t r; asm("mapa.shared::cluster.u32 %0, %1, %2;" : "=r"(r) : "r"(addr), "r"(rank)); return r; }
__device__ __forceinline__ void bulk_store_p(uint32_t el, void* dst, uint32_t src, uint32_t bytes) {
  asm volatile("{\n.reg .pred P;\nsetp.ne.u32 P, %3, 0;\n@P cp.async.bulk.global.shared::cta.bulk_group [%0], [%1], %2;\n}" ::"l"(dst), "r"(src), "r"(bytes), "r"(el) : "memory");
}
__device__ __forceinline__ void flag_release_p(uint32_t el, uint32_t* f) {
  asm volatile("{\n.reg .pred P;\nsetp.ne.u32 P, %1, 0;\nfence.proxy.async;\n@P red.relaxed.gpu.global.add.u32 [%0], 1;\n}" ::"l"(f), "r"(el) : "memory");
}
__device__ __forceinline__ void flag_add_p(uint32_t el, uint32_t* f) {
  asm volatile("{\n.reg .pred P;\nsetp.ne.u32 P, %1, 0;\n@P red.relaxed.gpu.global.add.u32 [%0], 1;\n}" ::"l"(f), "r"(el) : "memory");
}
__device__ __forceinline__ void prefetch_l2(const void* src, uint32_t bytes) { asm volatile("cp.async.bulk.prefetch.L2.global [%0], %1;" ::"l"(src), "r"(bytes) : "memory"); }
__device__ __forceinline__ void prefetch_map(const CUtensorMap* m) { asm volatile("prefetch.tensormap [%0];" ::"l"(m) : "memory"); }
__device__ __forceinline__ void wgmma_fence() { asm volatile("wgmma.fence.sync.aligned;" ::: "memory"); }
__device__ __forceinline__ void wgmma_commit() { asm volatile("wgmma.commit_group.sync.aligned;" ::: "memory"); }
template <int N> __device__ __forceinline__ void wgmma_wait() { asm volatile("wgmma.wait_group.sync.aligned %0;" ::"n"(N) : "memory"); }
__device__ __forceinline__ uint32_t dlo(uint32_t addr, uint32_t lbo) { return ((addr & 0x3FFFF) >> 4) + ((lbo >> 4) << 16); }
template <uint32_t SBO, uint32_t SWZ> __device__ __forceinline__ uint64_t dsc(uint32_t lo, uint32_t off) {
  uint64_t d; asm("mov.b64 %0, {%1, %2};" : "=l"(d) : "r"(lo + (off >> 4)), "n"((SBO >> 4) | (SWZ << 30))); return d;
}
template <int R> __device__ __forceinline__ void reg_alloc() { asm volatile("setmaxnreg.inc.sync.aligned.u32 %0;" ::"n"(R)); }
template <int R> __device__ __forceinline__ void reg_dealloc() { asm volatile("setmaxnreg.dec.sync.aligned.u32 %0;" ::"n"(R)); }
__device__ __forceinline__ void bar_sync(int id, int n) { asm volatile("bar.sync %0, %1;" ::"r"(id), "r"(n) : "memory"); }
__device__ __forceinline__ void bar_arrive(int id, int n) { asm volatile("bar.arrive %0, %1;" ::"r"(id), "r"(n) : "memory"); }
__device__ __forceinline__ void ldsm4(uint32_t* r, uint32_t addr) {
  asm volatile("ldmatrix.sync.aligned.m8n8.x4.shared.b16 {%0,%1,%2,%3}, [%4];" : "=r"(r[0]), "=r"(r[1]), "=r"(r[2]), "=r"(r[3]) : "r"(addr) : "memory");
}
__device__ __forceinline__ uint32_t movm(uint32_t a) { uint32_t d; asm volatile("movmatrix.sync.aligned.m8n8.trans.b16 %0, %1;" : "=r"(d) : "r"(a)); return d; }
__device__ __forceinline__ void mma16(float* c, uint32_t a0, uint32_t a1, uint32_t a2, uint32_t a3, uint32_t b0, uint32_t b1) {
  asm volatile("mma.sync.aligned.m16n8k16.row.col.f32.bf16.bf16.f32 {%0,%1,%2,%3}, {%4,%5,%6,%7}, {%8,%9}, {%0,%1,%2,%3};"
               : "+f"(c[0]), "+f"(c[1]), "+f"(c[2]), "+f"(c[3]) : "r"(a0), "r"(a1), "r"(a2), "r"(a3), "r"(b0), "r"(b1));
}
__device__ __forceinline__ void mma8(float* c, uint32_t a0, uint32_t a1, uint32_t b0) {
  asm volatile("mma.sync.aligned.m16n8k8.row.col.f32.bf16.bf16.f32 {%0,%1,%2,%3}, {%4,%5}, {%6}, {%0,%1,%2,%3};"
               : "+f"(c[0]), "+f"(c[1]), "+f"(c[2]), "+f"(c[3]) : "r"(a0), "r"(a1), "r"(b0));
}
__device__ __forceinline__ uint32_t pack2(float lo, float hi) { uint32_t r; asm("cvt.rn.bf16x2.f32 %0, %1, %2;" : "=r"(r) : "f"(hi), "f"(lo)); return r; }
__device__ __forceinline__ float blo(uint32_t v) { return __uint_as_float(v << 16); }
__device__ __forceinline__ float bhi(uint32_t v) { return __uint_as_float(v & 0xffff0000u); }
__device__ __forceinline__ float tanh_fast(float x) { float y; asm("tanh.approx.f32 %0, %1;" : "=f"(y) : "f"(x)); return y; }
__device__ __forceinline__ float rcp_fast(float x) { float y; asm("rcp.approx.ftz.f32 %0, %1;" : "=f"(y) : "f"(x)); return y; }
__device__ __forceinline__ float rsq_fast(float x) { float y; asm("rsqrt.approx.ftz.f32 %0, %1;" : "=f"(y) : "f"(x)); return y; }
__device__ __forceinline__ float ex2(float x) { float y; asm("ex2.approx.ftz.f32 %0, %1;" : "=f"(y) : "f"(x)); return y; }
__device__ __forceinline__ float qsum(float v) { v += __shfl_xor_sync(~0u, v, 1); v += __shfl_xor_sync(~0u, v, 2); return v; }
__device__ __forceinline__ float qmax(float v) { v = fmaxf(v, __shfl_xor_sync(~0u, v, 1)); v = fmaxf(v, __shfl_xor_sync(~0u, v, 2)); return v; }
__device__ __forceinline__ void stg32(void* p, uint32_t v) { asm volatile("st.global.u32 [%0], %1;" ::"l"(p), "r"(v) : "memory"); }
__device__ __forceinline__ void stg128(void* p, uint32_t a, uint32_t b, uint32_t c, uint32_t d) { asm volatile("st.global.v4.u32 [%0], {%1,%2,%3,%4};" ::"l"(p), "r"(a), "r"(b), "r"(c), "r"(d) : "memory"); }
__device__ __forceinline__ uint32_t ldcg32(const void* p) { uint32_t v; asm volatile("ld.global.L1::no_allocate.u32 %0, [%1];" : "=r"(v) : "l"(p) : "memory"); return v; }
__device__ __forceinline__ void stg128_if(bool c, void* p, uint32_t a, uint32_t b, uint32_t cc, uint32_t d) {
  asm volatile("{\n.reg .pred P;\nsetp.ne.u32 P, %5, 0;\n@P st.global.v4.u32 [%0], {%1,%2,%3,%4};\n}" ::"l"(p), "r"(a), "r"(b), "r"(cc), "r"(d), "r"((uint32_t)c) : "memory");
}
__device__ __forceinline__ uint2 lds64(uint32_t a) { uint2 v; asm volatile("ld.shared.v2.u32 {%0,%1}, [%2];" : "=r"(v.x), "=r"(v.y) : "r"(a) : "memory"); return v; }
__device__ __forceinline__ uint32_t ldnc16(const void* p) { uint16_t v; asm volatile("ld.global.nc.u16 %0, [%1];" : "=h"(v) : "l"(p)); return v; }
__device__ __forceinline__ uint4 ldnc128(const void* p) { uint4 v; asm volatile("ld.global.nc.v4.u32 {%0,%1,%2,%3}, [%4];" : "=r"(v.x), "=r"(v.y), "=r"(v.z), "=r"(v.w) : "l"(p)); return v; }
__device__ __forceinline__ void cp_async16(uint32_t dst, const void* src) { asm volatile("cp.async.cg.shared.global [%0], [%1], 16;" ::"r"(dst), "l"(src) : "memory"); }
__device__ __forceinline__ uint32_t hsub2(uint32_t a, uint32_t b) { uint32_t d; asm("sub.rn.bf16x2 %0, %1, %2;" : "=r"(d) : "r"(a), "r"(b)); return d; }
__device__ __forceinline__ void stg32_if(bool c, void* p, uint32_t v) {
  asm volatile("{\n.reg .pred P;\nsetp.ne.u32 P, %2, 0;\n@P st.global.u32 [%0], %1;\n}" ::"l"(p), "r"(v), "r"((uint32_t)c) : "memory");
}
__device__ __forceinline__ float wsum(float v) { for (int o = 16; o; o >>= 1) v += __shfl_xor_sync(~0u, v, o); return v; }
__device__ __forceinline__ uint32_t hmul2(uint32_t a, uint32_t b) { uint32_t d; asm("mul.rn.bf16x2 %0, %1, %2;" : "=r"(d) : "r"(a), "r"(b)); return d; }
__device__ __forceinline__ void sts32(uint32_t a, uint32_t v) { asm volatile("st.shared.u32 [%0], %1;" ::"r"(a), "r"(v) : "memory"); }
__device__ __forceinline__ uint32_t lds32(uint32_t a) { uint32_t v; asm volatile("ld.shared.u32 %0, [%1];" : "=r"(v) : "r"(a) : "memory"); return v; }
__device__ __forceinline__ void sts128(uint32_t a, uint32_t x, uint32_t y, uint32_t z, uint32_t w) { asm volatile("st.shared.v4.u32 [%0], {%1,%2,%3,%4};" ::"r"(a), "r"(x), "r"(y), "r"(z), "r"(w) : "memory"); }
__device__ __forceinline__ uint4 lds128v(uint32_t a) { uint4 v; asm volatile("ld.volatile.shared.v4.u32 {%0,%1,%2,%3}, [%4];" : "=r"(v.x), "=r"(v.y), "=r"(v.z), "=r"(v.w) : "r"(a) : "memory"); return v; }
__device__ __forceinline__ uint4 lds128(uint32_t a) { uint4 v; asm volatile("ld.shared.v4.u32 {%0,%1,%2,%3}, [%4];" : "=r"(v.x), "=r"(v.y), "=r"(v.z), "=r"(v.w) : "r"(a) : "memory"); return v; }
__device__ __forceinline__ void ll_st64(uint2* p, uint32_t v, uint32_t tag) {
  asm volatile("{\n.reg .b64 r;\nmov.b64 r, {%1,%2};\nst.relaxed.gpu.global.b64 [%0], r;\n}" ::"l"(p), "r"(v), "r"(tag) : "memory");
}
__device__ __forceinline__ uint2 ll_ld64(const uint2* p) {
  uint2 v; asm volatile("{\n.reg .b64 r;\nld.relaxed.gpu.global.b64 r, [%2];\nmov.b64 {%0,%1}, r;\n}" : "=r"(v.x), "=r"(v.y) : "l"(p) : "memory"); return v;
}
__device__ __forceinline__ void ll_st128(uint4* p, float a, float b, uint32_t tag, float c = 0.f) {
  asm volatile("{\n.reg .b128 r;\n.reg .b64 lo, hi;\nmov.b64 lo, {%1,%2};\nmov.b64 hi, {%3,%4};\nmov.b128 r, {lo, hi};\nst.relaxed.gpu.global.b128 [%0], r;\n}" ::"l"(p), "r"(__float_as_uint(a)), "r"(__float_as_uint(b)), "r"(tag), "r"(__float_as_uint(c)) : "memory");
}
__device__ __forceinline__ uint4 ll_ld128g(const void* p) {
  uint4 v; asm volatile("{\n.reg .b128 r;\n.reg .b64 lo, hi;\nld.relaxed.gpu.b128 r, [%4];\nmov.b128 {lo, hi}, r;\nmov.b64 {%0,%1}, lo;\nmov.b64 {%2,%3}, hi;\n}" : "=r"(v.x), "=r"(v.y), "=r"(v.z), "=r"(v.w) : "l"(p) : "memory"); return v;
}
__device__ __forceinline__ uint4 ll_ld128(const uint4* p) {
  uint4 v; asm volatile("{\n.reg .b128 r;\n.reg .b64 lo, hi;\nld.relaxed.gpu.global.b128 r, [%4];\nmov.b128 {lo, hi}, r;\nmov.b64 {%0,%1}, lo;\nmov.b64 {%2,%3}, hi;\n}" : "=r"(v.x), "=r"(v.y), "=r"(v.z), "=r"(v.w) : "l"(p) : "memory"); return v;
}
__device__ __forceinline__ void publish_p(uint32_t el, uint32_t* f) {
  asm volatile("{\n.reg .pred P;\nsetp.ne.u32 P, %1, 0;\n@P cp.async.bulk.commit_group;\n@P cp.async.bulk.wait_group 0;\n@P red.release.gpu.global.add.u32 [%0], 1;\n}" ::"l"(f), "r"(el) : "memory");
}
__device__ __forceinline__ void stsm4(uint32_t addr, uint32_t a, uint32_t b, uint32_t c, uint32_t d) {
  asm volatile("stmatrix.sync.aligned.m8n8.x4.shared.b16 [%0], {%1,%2,%3,%4};" ::"r"(addr), "r"(a), "r"(b), "r"(c), "r"(d) : "memory");
}
__device__ __forceinline__ void sts64(uint32_t a, uint32_t x, uint32_t y) { asm volatile("st.shared.v2.u32 [%0], {%1,%2};" ::"r"(a), "r"(x), "r"(y) : "memory"); }
__device__ __forceinline__ void ll_st128_if(bool on, uint4* p, float a, float b, uint32_t tag) {
  asm volatile("{\n.reg .pred P;\n.reg .b128 r;\n.reg .b64 lo, hi;\nsetp.ne.u32 P, %4, 0;\nmov.b64 lo, {%1,%2};\nmov.b64 hi, {%3,%3};\nmov.b128 r, {lo, hi};\n@P st.relaxed.gpu.global.b128 [%0], r;\n}" ::"l"(p), "r"(__float_as_uint(a)), "r"(__float_as_uint(b)), "r"(tag), "r"((uint32_t)on) : "memory");
}
__device__ __forceinline__ uint4 ldnc128_if(bool c, const void* p) {
  uint4 v = make_uint4(0u, 0u, 0u, 0u);
  asm volatile("{\n.reg .pred P;\nsetp.ne.u32 P, %5, 0;\n@P ld.global.nc.v4.u32 {%0,%1,%2,%3}, [%4];\n}" : "+r"(v.x), "+r"(v.y), "+r"(v.z), "+r"(v.w) : "l"(p), "r"((uint32_t)c));
  return v;
}
__device__ __forceinline__ float2 lds64f(uint32_t a) { float2 v; asm volatile("ld.shared.v2.f32 {%0,%1}, [%2];" : "=f"(v.x), "=f"(v.y) : "r"(a) : "memory"); return v; }
#define TRC(cond, role, idx) do {} while (0)
#define TRV(role, idx, v) do {} while (0)
#define TRVI(c, role, idx, v) do {} while (0)

#define ACLK_INIT do {} while (0)
#define ACLK(i) do {} while (0)
#define ACLK_OUT do {} while (0)
#define RCLK(i) do {} while (0)
#define RCLK_INIT do {} while (0)
#define RCLK_OUT do {} while (0)
#define SCLK(i) do {} while (0)
#define SCLK2(i) do {} while (0)
#define SCLK3(i) do {} while (0)
#define OCLK(c, r, i) do {} while (0)
#define PL 1
#define PCLK(i) do {} while (0)
#define PQ 1
#define CLK_INIT do {} while (0)
#define CLK(i) do {} while (0)
#define CLK_OUT do {} while (0)

__device__ __forceinline__ void wgmma_ss_n216(float* d, uint64_t da, uint64_t db, int scaleD) {
  asm volatile("{\n.reg .pred p;\nsetp.ne.b32 p, %110, 0;\nwgmma.mma_async.sync.aligned.m64n216k16.f32.bf16.bf16 "
    "{%0,%1,%2,%3,%4,%5,%6,%7,%8,%9,%10,%11,%12,%13,%14,%15,%16,%17,%18,%19,%20,%21,%22,%23,%24,%25,%26,%27,%28,%29,%30,%31,%32,%33,%34,%35,%36,%37,%38,%39,%40,%41,%42,%43,%44,%45,%46,%47,%48,%49,%50,%51,%52,%53,%54,%55,%56,%57,%58,%59,%60,%61,%62,%63,%64,%65,%66,%67,%68,%69,%70,%71,%72,%73,%74,%75,%76,%77,%78,%79,%80,%81,%82,%83,%84,%85,%86,%87,%88,%89,%90,%91,%92,%93,%94,%95,%96,%97,%98,%99,%100,%101,%102,%103,%104,%105,%106,%107}, "
    "%108, %109, p, 1, 1, 0, 1;\n}\n"
    : "+f"(d[0]), "+f"(d[1]), "+f"(d[2]), "+f"(d[3]), "+f"(d[4]), "+f"(d[5]), "+f"(d[6]), "+f"(d[7]), "+f"(d[8]), "+f"(d[9]), "+f"(d[10]), "+f"(d[11]), "+f"(d[12]), "+f"(d[13]), "+f"(d[14]), "+f"(d[15]), "+f"(d[16]), "+f"(d[17]), "+f"(d[18]), "+f"(d[19]), "+f"(d[20]), "+f"(d[21]), "+f"(d[22]), "+f"(d[23]), "+f"(d[24]), "+f"(d[25]), "+f"(d[26]), "+f"(d[27]), "+f"(d[28]), "+f"(d[29]), "+f"(d[30]), "+f"(d[31]), "+f"(d[32]), "+f"(d[33]), "+f"(d[34]), "+f"(d[35]), "+f"(d[36]), "+f"(d[37]), "+f"(d[38]), "+f"(d[39]), "+f"(d[40]), "+f"(d[41]), "+f"(d[42]), "+f"(d[43]), "+f"(d[44]), "+f"(d[45]), "+f"(d[46]), "+f"(d[47]), "+f"(d[48]), "+f"(d[49]), "+f"(d[50]), "+f"(d[51]), "+f"(d[52]), "+f"(d[53]), "+f"(d[54]), "+f"(d[55]), "+f"(d[56]), "+f"(d[57]), "+f"(d[58]), "+f"(d[59]), "+f"(d[60]), "+f"(d[61]), "+f"(d[62]), "+f"(d[63]), "+f"(d[64]), "+f"(d[65]), "+f"(d[66]), "+f"(d[67]), "+f"(d[68]), "+f"(d[69]), "+f"(d[70]), "+f"(d[71]), "+f"(d[72]), "+f"(d[73]), "+f"(d[74]), "+f"(d[75]), "+f"(d[76]), "+f"(d[77]), "+f"(d[78]), "+f"(d[79]), "+f"(d[80]), "+f"(d[81]), "+f"(d[82]), "+f"(d[83]), "+f"(d[84]), "+f"(d[85]), "+f"(d[86]), "+f"(d[87]), "+f"(d[88]), "+f"(d[89]), "+f"(d[90]), "+f"(d[91]), "+f"(d[92]), "+f"(d[93]), "+f"(d[94]), "+f"(d[95]), "+f"(d[96]), "+f"(d[97]), "+f"(d[98]), "+f"(d[99]), "+f"(d[100]), "+f"(d[101]), "+f"(d[102]), "+f"(d[103]), "+f"(d[104]), "+f"(d[105]), "+f"(d[106]), "+f"(d[107])
    : "l"(da), "l"(db), "r"(scaleD));
}
__device__ __forceinline__ void wgmma_ss_n72(float* d, uint64_t da, uint64_t db, int scaleD) {
  asm volatile("{\n.reg .pred p;\nsetp.ne.b32 p, %38, 0;\nwgmma.mma_async.sync.aligned.m64n72k16.f32.bf16.bf16 "
    "{%0,%1,%2,%3,%4,%5,%6,%7,%8,%9,%10,%11,%12,%13,%14,%15,%16,%17,%18,%19,%20,%21,%22,%23,%24,%25,%26,%27,%28,%29,%30,%31,%32,%33,%34,%35}, "
    "%36, %37, p, 1, 1, 0, 1;\n}\n"
    : "+f"(d[0]), "+f"(d[1]), "+f"(d[2]), "+f"(d[3]), "+f"(d[4]), "+f"(d[5]), "+f"(d[6]), "+f"(d[7]), "+f"(d[8]), "+f"(d[9]), "+f"(d[10]), "+f"(d[11]), "+f"(d[12]), "+f"(d[13]), "+f"(d[14]), "+f"(d[15]), "+f"(d[16]), "+f"(d[17]), "+f"(d[18]), "+f"(d[19]), "+f"(d[20]), "+f"(d[21]), "+f"(d[22]), "+f"(d[23]), "+f"(d[24]), "+f"(d[25]), "+f"(d[26]), "+f"(d[27]), "+f"(d[28]), "+f"(d[29]), "+f"(d[30]), "+f"(d[31]), "+f"(d[32]), "+f"(d[33]), "+f"(d[34]), "+f"(d[35])
    : "l"(da), "l"(db), "r"(scaleD));
}
__device__ __forceinline__ void wgmma_ss_n128(float* d, uint64_t da, uint64_t db, int scaleD) {
  asm volatile("{\n.reg .pred p;\nsetp.ne.b32 p, %66, 0;\nwgmma.mma_async.sync.aligned.m64n128k16.f32.bf16.bf16 "
    "{%0,%1,%2,%3,%4,%5,%6,%7,%8,%9,%10,%11,%12,%13,%14,%15,%16,%17,%18,%19,%20,%21,%22,%23,%24,%25,%26,%27,%28,%29,%30,%31,%32,%33,%34,%35,%36,%37,%38,%39,%40,%41,%42,%43,%44,%45,%46,%47,%48,%49,%50,%51,%52,%53,%54,%55,%56,%57,%58,%59,%60,%61,%62,%63}, "
    "%64, %65, p, 1, 1, 0, 1;\n}\n"
    : "+f"(d[0]), "+f"(d[1]), "+f"(d[2]), "+f"(d[3]), "+f"(d[4]), "+f"(d[5]), "+f"(d[6]), "+f"(d[7]), "+f"(d[8]), "+f"(d[9]), "+f"(d[10]), "+f"(d[11]), "+f"(d[12]), "+f"(d[13]), "+f"(d[14]), "+f"(d[15]), "+f"(d[16]), "+f"(d[17]), "+f"(d[18]), "+f"(d[19]), "+f"(d[20]), "+f"(d[21]), "+f"(d[22]), "+f"(d[23]), "+f"(d[24]), "+f"(d[25]), "+f"(d[26]), "+f"(d[27]), "+f"(d[28]), "+f"(d[29]), "+f"(d[30]), "+f"(d[31]), "+f"(d[32]), "+f"(d[33]), "+f"(d[34]), "+f"(d[35]), "+f"(d[36]), "+f"(d[37]), "+f"(d[38]), "+f"(d[39]), "+f"(d[40]), "+f"(d[41]), "+f"(d[42]), "+f"(d[43]), "+f"(d[44]), "+f"(d[45]), "+f"(d[46]), "+f"(d[47]), "+f"(d[48]), "+f"(d[49]), "+f"(d[50]), "+f"(d[51]), "+f"(d[52]), "+f"(d[53]), "+f"(d[54]), "+f"(d[55]), "+f"(d[56]), "+f"(d[57]), "+f"(d[58]), "+f"(d[59]), "+f"(d[60]), "+f"(d[61]), "+f"(d[62]), "+f"(d[63])
    : "l"(da), "l"(db), "r"(scaleD));
}
__device__ __forceinline__ void wgmma_ss_n160(float* d, uint64_t da, uint64_t db, int scaleD) {
  asm volatile("{\n.reg .pred p;\nsetp.ne.b32 p, %82, 0;\nwgmma.mma_async.sync.aligned.m64n160k16.f32.bf16.bf16 "
    "{%0,%1,%2,%3,%4,%5,%6,%7,%8,%9,%10,%11,%12,%13,%14,%15,%16,%17,%18,%19,%20,%21,%22,%23,%24,%25,%26,%27,%28,%29,%30,%31,%32,%33,%34,%35,%36,%37,%38,%39,%40,%41,%42,%43,%44,%45,%46,%47,%48,%49,%50,%51,%52,%53,%54,%55,%56,%57,%58,%59,%60,%61,%62,%63,%64,%65,%66,%67,%68,%69,%70,%71,%72,%73,%74,%75,%76,%77,%78,%79}, "
    "%80, %81, p, 1, 1, 0, 1;\n}\n"
    : "+f"(d[0]), "+f"(d[1]), "+f"(d[2]), "+f"(d[3]), "+f"(d[4]), "+f"(d[5]), "+f"(d[6]), "+f"(d[7]), "+f"(d[8]), "+f"(d[9]), "+f"(d[10]), "+f"(d[11]), "+f"(d[12]), "+f"(d[13]), "+f"(d[14]), "+f"(d[15]), "+f"(d[16]), "+f"(d[17]), "+f"(d[18]), "+f"(d[19]), "+f"(d[20]), "+f"(d[21]), "+f"(d[22]), "+f"(d[23]), "+f"(d[24]), "+f"(d[25]), "+f"(d[26]), "+f"(d[27]), "+f"(d[28]), "+f"(d[29]), "+f"(d[30]), "+f"(d[31]), "+f"(d[32]), "+f"(d[33]), "+f"(d[34]), "+f"(d[35]), "+f"(d[36]), "+f"(d[37]), "+f"(d[38]), "+f"(d[39]), "+f"(d[40]), "+f"(d[41]), "+f"(d[42]), "+f"(d[43]), "+f"(d[44]), "+f"(d[45]), "+f"(d[46]), "+f"(d[47]), "+f"(d[48]), "+f"(d[49]), "+f"(d[50]), "+f"(d[51]), "+f"(d[52]), "+f"(d[53]), "+f"(d[54]), "+f"(d[55]), "+f"(d[56]), "+f"(d[57]), "+f"(d[58]), "+f"(d[59]), "+f"(d[60]), "+f"(d[61]), "+f"(d[62]), "+f"(d[63]), "+f"(d[64]), "+f"(d[65]), "+f"(d[66]), "+f"(d[67]), "+f"(d[68]), "+f"(d[69]), "+f"(d[70]), "+f"(d[71]), "+f"(d[72]), "+f"(d[73]), "+f"(d[74]), "+f"(d[75]), "+f"(d[76]), "+f"(d[77]), "+f"(d[78]), "+f"(d[79])
    : "l"(da), "l"(db), "r"(scaleD));
}
__device__ __forceinline__ void wgmma_rs_n144(float* d, const uint32_t* a, uint64_t db, int scaleD) {
  asm volatile("{\n.reg .pred p;\nsetp.ne.b32 p, %77, 0;\nwgmma.mma_async.sync.aligned.m64n144k16.f32.bf16.bf16 "
    "{%0,%1,%2,%3,%4,%5,%6,%7,%8,%9,%10,%11,%12,%13,%14,%15,%16,%17,%18,%19,%20,%21,%22,%23,%24,%25,%26,%27,%28,%29,%30,%31,%32,%33,%34,%35,%36,%37,%38,%39,%40,%41,%42,%43,%44,%45,%46,%47,%48,%49,%50,%51,%52,%53,%54,%55,%56,%57,%58,%59,%60,%61,%62,%63,%64,%65,%66,%67,%68,%69,%70,%71}, "
    "{%72,%73,%74,%75}, %76, p, 1, 1, 1;\n}\n"
    : "+f"(d[0]), "+f"(d[1]), "+f"(d[2]), "+f"(d[3]), "+f"(d[4]), "+f"(d[5]), "+f"(d[6]), "+f"(d[7]), "+f"(d[8]), "+f"(d[9]), "+f"(d[10]), "+f"(d[11]), "+f"(d[12]), "+f"(d[13]), "+f"(d[14]), "+f"(d[15]), "+f"(d[16]), "+f"(d[17]), "+f"(d[18]), "+f"(d[19]), "+f"(d[20]), "+f"(d[21]), "+f"(d[22]), "+f"(d[23]), "+f"(d[24]), "+f"(d[25]), "+f"(d[26]), "+f"(d[27]), "+f"(d[28]), "+f"(d[29]), "+f"(d[30]), "+f"(d[31]), "+f"(d[32]), "+f"(d[33]), "+f"(d[34]), "+f"(d[35]), "+f"(d[36]), "+f"(d[37]), "+f"(d[38]), "+f"(d[39]), "+f"(d[40]), "+f"(d[41]), "+f"(d[42]), "+f"(d[43]), "+f"(d[44]), "+f"(d[45]), "+f"(d[46]), "+f"(d[47]), "+f"(d[48]), "+f"(d[49]), "+f"(d[50]), "+f"(d[51]), "+f"(d[52]), "+f"(d[53]), "+f"(d[54]), "+f"(d[55]), "+f"(d[56]), "+f"(d[57]), "+f"(d[58]), "+f"(d[59]), "+f"(d[60]), "+f"(d[61]), "+f"(d[62]), "+f"(d[63]), "+f"(d[64]), "+f"(d[65]), "+f"(d[66]), "+f"(d[67]), "+f"(d[68]), "+f"(d[69]), "+f"(d[70]), "+f"(d[71])
    : "r"(a[0]), "r"(a[1]), "r"(a[2]), "r"(a[3]), "l"(db), "r"(scaleD));
}
__device__ __forceinline__ void wgmma_rs_n64(float* d, const uint32_t* a, uint64_t db, int scaleD) {
  asm volatile("{\n.reg .pred p;\nsetp.ne.b32 p, %37, 0;\nwgmma.mma_async.sync.aligned.m64n64k16.f32.bf16.bf16 "
    "{%0,%1,%2,%3,%4,%5,%6,%7,%8,%9,%10,%11,%12,%13,%14,%15,%16,%17,%18,%19,%20,%21,%22,%23,%24,%25,%26,%27,%28,%29,%30,%31}, "
    "{%32,%33,%34,%35}, %36, p, 1, 1, 1;\n}\n"
    : "+f"(d[0]), "+f"(d[1]), "+f"(d[2]), "+f"(d[3]), "+f"(d[4]), "+f"(d[5]), "+f"(d[6]), "+f"(d[7]), "+f"(d[8]), "+f"(d[9]), "+f"(d[10]), "+f"(d[11]), "+f"(d[12]), "+f"(d[13]), "+f"(d[14]), "+f"(d[15]), "+f"(d[16]), "+f"(d[17]), "+f"(d[18]), "+f"(d[19]), "+f"(d[20]), "+f"(d[21]), "+f"(d[22]), "+f"(d[23]), "+f"(d[24]), "+f"(d[25]), "+f"(d[26]), "+f"(d[27]), "+f"(d[28]), "+f"(d[29]), "+f"(d[30]), "+f"(d[31])
    : "r"(a[0]), "r"(a[1]), "r"(a[2]), "r"(a[3]), "l"(db), "r"(scaleD));
}

template <int V> struct Int { static constexpr int value = V; };
struct Cur {
  uint32_t s, ph;
  __device__ __forceinline__ void next() { if (++s == NST) { s = 0; ph ^= 1; } }
};

__device__ __forceinline__ uint32_t o_place(uint32_t w, uint32_t kb) { return (w ? kb + (kb > 4) * 9 : kb + 5) * 8192 + 83968; }
#define z1_block(rb, w, j) (Q.Z + ((rb) * 16 + (w) * 8 + (j)) * ZB)
#define xn_block(hw) (Q.Z + ((hw) * 8 + 2) * ZB)
#define z2_block(kb, j) (Q.Z + (256 + (kb) * 8 + (j)) * ZB)
template <int N> __device__ __forceinline__ void pause(uint32_t zero) {
  if (N <= 0) return;
  uint32_t z = clock() + threadIdx.x;
  do {
#pragma unroll (N > 8 ? 1 : 8)
    for (int i = 0; i < N; i++) asm volatile("shfl.sync.bfly.b32 %0, %0, 1, 0x1f, 0xffffffff;" : "+r"(z)::"memory");
  } while (__any_sync(~0u, z & zero));
}

__global__ void __cluster_dims__(2, 1, 1) __launch_bounds__(384, 1) mega_kernel(const Ptrs Q, const __grid_constant__ Params P) {
  extern __shared__ __align__(1024) uint8_t smem_raw[];
  const uint32_t sb = smem_u32(smem_raw);
  const uint32_t bars = sb + SM_BAR;
  const int tid = threadIdx.x;
  int lane = tid & 31;
  const int wid = __shfl_sync(~0u, tid >> 5, 0);
  const int cl = blockIdx.x >> 1;
  const int bid = (cl < 4 ? cl * 8 + 32 : cl - 4 + (max(cl - 29, 0) * 37 >> 8)) * 2 + (blockIdx.x & 1);
  const int rb = bid & 15, j = bid >> 4;
  uint4 wv[5];
  {
    const int n8 = min(tid >> 3, 26), part = n8 / 9;
    const uint8_t* src = (const uint8_t*)Q.wqkv + (8 * rb + (tid & 7)) * (3 * DM * 2) + (part * (DM - 72) + 72 * j + 8 * n8) * 2;
#pragma unroll
    for (int u = 0; u < 5; u++) wv[u] = ldnc128_if(tid < 216 && cl < 64 && (u < 4 || rb < 8), src + u * (128 * 3 * DM * 2));
  }
  if (cl >= 64) return;
  if (wid >= 7 && lane == 0) {
    if (wid < 10) {
#pragma unroll
      for (uint32_t b = 0; b < B_AD / 3; b += 8) mbar_init(bars + (wid - 7) * (B_AD / 3) + b, 1);
    } else if (wid == 10) {
#pragma unroll
      for (uint32_t b = B_AD; b < B_EVT; b += 8) mbar_init(bars + b, b < B_HOLD ? 2 : 4);
    } else {
#pragma unroll
      for (uint32_t b = B_EVT; b < 1024; b += 8) if (b < B_OFF || b >= B_IMG) mbar_init(bars + b, b < B_IMG ? 4 : b < B_EMPTY ? 8 : 16);
    }
    asm volatile("fence.mbarrier_init.release.cluster;" ::: "memory");
  }
  __syncthreads();

  if (wid >= 8) {
    reg_dealloc<56>();
    const uint32_t el = elect_one();
    const uint64_t pol = policy_evict_first();
    uint32_t* const fj = Q.flags + FJ + j * 32;
    if (wid == 8) {
      if (el) { prefetch_map(&P.wsp); prefetch_map(&P.winb[j & 1]); prefetch_map(&P.wins); prefetch_map(&P.wout); prefetch_map(&P.act[1]); prefetch_map(&P.res[0]); prefetch_map(&P.res[1]); }
      const uint32_t epoch = ldcg32(fj + FJ_EP + rb);
      Cur c{0, 1};
      const uint32_t rk = bid & 1;
      uint32_t st, full;
      auto slot = [&](uint32_t bytes) {
        st = sb + c.s * ST_BYTES; full = bars + B_FULL + c.s * 8;
        mbar_wait(full, c.ph);
        expect_tx_p(el, full, bytes);
        mbar_wait(full - B_FULL + B_EMPTY, c.ph);
      };
#pragma unroll 1
      for (int L = 0; L < 2; L++) {
#pragma unroll 1
        for (int i = 0; i < 9; i++) {
          if (L == 0 && i == 0) {
            flag_wait(fj + FJ_WQ, (epoch + 1) * 16);
            fence_async_g();
            TRC(el, 2, 45);
          }
          slot(27648);
          bulk_mc_h(el, st + ST_B + rk * 13824, Q.WQ + j * WQ_SL + i * 27648 + rk * 13824, 13824, full, EF(0), pol);
          c.next();
        }
        if (L == 0) {
          flag_wait(fj + FJ_WO, (epoch + 1) * 16);
          fence_async_g();
          TRC(el, 2, 46);
        }
#pragma unroll 1
        while (c.s) {
          mbar_wait(bars + B_EMPTY + c.s * 8, c.ph);
          if (el) { mbar_arrive(bars + B_FULL + c.s * 8); asm volatile("mbarrier.arrive.shared::cta.b64 _, [%0], 16;" ::"r"(bars + B_EMPTY + c.s * 8) : "memory"); }
          c.next();
        }
        expect_tx_p(el, bars + B_WF, WO_SL);
        mbar_wait(bars + B_EMPTY, c.ph);
        mbar_wait(bars + B_EMPTY + 8, c.ph);
        bulk_mc_h(el, sb + rk * (WO_SL / 2), Q.WO + j * WO_SL + rk * (WO_SL / 2), WO_SL / 2, bars + B_WF, EF(1), pol);
#pragma unroll 1
        for (int r = 0; r < 10; r++) {
          const bool big = r >= 2 && r < 8;
          const int a0 = (r < 5 ? 36 : 0) + ((9 * j) >> 1) + (big ? 2 - 2 * (j & 1) : 3 * (j & 1) + rk), ks = big ? 32 : 48;
          int k = big ? (r < 5 ? r - 2 : r - 5) * 192 + rk * 16 : (r & 1) * 288;
          const CUtensorMap* m = big ? &P.winb[j & 1] : &P.wins;
          const uint32_t dst = sb + SM_B3 + rk * 6144;
#pragma unroll
          for (int p = 0; p < 6; p++, k += ks) {
            if (!(p & 3) && r == 0) mbar_wait(bars + B_XD + p * 2, L);
            if (p) mbar_wait_c(bars + B_E3 + p * 8, ~r & 1); else mbar_wait(bars + B_E3, ~r & 1);
            expect_tx_p(el, bars + B_F3 + p * 8, 12288);
            tma3d_mc_h(el, dst + p * 12288, m, 0, k, a0, bars + B_F3 + p * 8, EF(2), pol);
          }
        }
        TRC(el, 2, L * 16 + 6);
        mbar_wait(bars + B_ZOK, L);
        fence_async_g();
        TRC(el, 2, L * 16 + 7);
        const uint8_t* src = z2_block(0, j) + rk * 18432;
#pragma unroll 1
        for (int r = 0; r < 8; r++) {
          const int k = (r & 3) * 512 + ((r >> 2) ^ 1) * 64;
#pragma unroll
          for (int p = 0; p < 4; p++, src += 8 * ZB) {
            if ((p == 1 || p == 2) && r == 0) mbar_wait(bars + B_E3 - 8 + p * 24, 1);
            mbar_wait_c(bars + B_AD + p * 8, ~r & 1);
            if (p) mbar_wait_c(bars + B_EMPTY + p * 8, c.ph); else mbar_wait(bars + B_EMPTY, c.ph);
            expect_tx_p(el, bars + B_FULL + p * 8, ST_BYTES);
            bulk_mc_h(el, sb + p * ST_BYTES + ST_B + rk * 18432, src, 18432, bars + B_FULL + p * 8, EF(4), pol);
            tma3d_h(el, sb + p * ST_BYTES, &P.wsp, k + p * 128, rb * 64, 0, bars + B_FULL + p * 8, EF(3), pol);
          }
          c.ph ^= 1;
        }
        mbar_wait(bars + B_Z1, L);
        fence_async_g();
#pragma unroll 1
        for (int i = 0; i < 11; i++) {
          const int cb = i - 2 + j;
          if (i < 4) mbar_wait(bars + B_AD + c.s * 8, 1);
          slot(ZB);
          if (i < 2) bulk_load_h(el, st + ST_B, z1_block(rb, i, j), ZB, full, true, pol);
          else tma2d_mc_h(el, st + ST_B + rk * 18432, &P.wout, (cb >= 9 ? cb - 9 : cb) * 64, 288 * j + rk * 144, full, EF(5), pol);
          c.next();
        }
      }
    } else if (wid < 11) {
      uint32_t id = bid * 2 + wid - 9;
#define AGENT_IDS asm volatile("" : "+r"(lane), "+r"(id)); const uint32_t w = id & 1, hw = id & 31, rb = hw >> 1, j = id >> 5, ev = bars + B_EVT + w * EV_N * 8; \
      uint32_t* const fr = Q.flags + hw * 32; uint32_t* const fj = Q.flags + FJ + j * 32; (void)fr; (void)fj; (void)ev; (void)rb
      uint32_t t8 = 0;
      Cur c{0, 1};
#pragma unroll 1
      for (int L = 0; L < 2; L++) {
        if (L) {
          AGENT_IDS;
          const uint32_t full = bars + B_FULLA + w * 32 + c.s * 8, dst = sb + c.s * ST_BYTES + w * 8192;
          expect_tx_p(el, full, 8192);
          mbar_wait_c(ev + EV_PT * 8, 1);
          TRC(el, 3, w * 32 + 16);
          flag_release_p(el, fr + FR_X2);
          TRC(el, 3, w * 32 + 17);
          mbar_wait_c(bars + B_EMPTY + c.s * 8, c.ph);
          flag_wait(fr + FR_X2, t8);
          fence_async_g();
          tma3d_h(el, dst, &P.act[1], 0, (hw ^ 1) * 32, 0, full, false, pol);
          c.next();
          TRC(el, 3, w * 32 + 18);
        }
#pragma unroll 1
        for (int i = L; i < 9; i++) {
          AGENT_IDS;
          const uint32_t full = bars + B_FULLA + w * 32 + c.s * 8, dst = sb + c.s * ST_BYTES + w * 8192;
          if (L == 0 && i == AEP) t8 = (ldcg32(fr + FR_EP + j) + 1) * 8;
          mbar_wait_c(bars + B_EMPTY + c.s * 8, c.ph);
          expect_tx_p(el, full, 8192);
          tma3d_h(el, dst, &P.act[L], i * 64, (hw ^ 1) * 32, 0, full, false, pol);
          c.next();
          if (i == PZI || i == PZI + 1) {
            uint8_t* d = (i == PZI ? xn_block(hw) : z1_block(rb, w, 0)) + j * 9216 + lane * 16;
#pragma unroll 1
            for (int u = 0; u < 6; u++, d += 1536) { stg128(d, ~0u, ~0u, ~0u, ~0u); stg128(d + 512, ~0u, ~0u, ~0u, ~0u); stg128(d + 1024, ~0u, ~0u, ~0u, ~0u); }
          }
          if (i == PZI) { stg128(Q.ST1 + (hw * 8 + j) * 32 + lane, ~0u, ~0u, ~0u, ~0u); stg128(Q.ZST + (hw * 8 + j) * 32 + lane, ~0u, ~0u, ~0u, ~0u); }
          if (i == RFI) {
            if (L) mbar_wait_c(bars + B_EVT + (EV_N * (1 - w) + EV_PT) * 8, 1);
            expect_tx_p(el, bars + B_WT + w * 8, 9216);
            bulk_load_p(el, sb + SM_STG + w * 9216, (L ? Q.out : Q.x) + ((hw ^ 1) * 64 + 8 * j) * (DM * 2), 9216, bars + B_WT + w * 8);
          }
          if (i == 4 && L > w) {
            expect_tx_p(el, bars + B_XRW + 8, 864);
            bulk_load_p(el, sb + SM_CSQ, Q.CSP + (NCTA + (id >> 1)) * 216, 864, bars + B_XRW + 8);
          }
        }
        if (c.s) { c.s = 0; c.ph ^= 1; }
        {
          AGENT_IDS;
          const uint32_t tag = (t8 >> 2) - 1 + L;
          uint4* const xs = Q.XST + hw * 128;
          const uint32_t tab = sb + SM_XST + w * 768 + lane * 8;
          TRC(el, 3, w * 32 + L * 16 + 13);
#pragma unroll 1
          for (int it = 0; it < (1 << 22); it++) {
            const uint4 a = ll_ld128(xs + 2 * lane), b = ll_ld128(xs + 64 + 2 * lane), h = ll_ld128(xs - (rb ? 192 : 0) + 2 * (lane | 24));
            if (__all_sync(~0u, a.z == tag && b.z == tag && h.z == tag)) { sts64(tab, h.x, h.y); sts64(tab + 256, a.x, a.y); sts64(tab + 512, b.x, b.y); break; }
          }
          __syncwarp();
          if (el) mbar_arrive(bars + B_CSQ);
          TRC(el, 3, w * 32 + L * 16 + 14);
          uint32_t* f = Q.flags + rb * 64 + FR_PZ + L;
          flag_release_p(el, f);
          expect_tx_p(el, bars + B_RES + w * 8, 9216);
          tma3d_h(el, sb + SM_STG + w * 9216, &P.res[L], j * 72, (hw ^ 1) * 32, 0, bars + B_RES + w * 8, !L, pol);
          pause<FD3>(Q.zero);
          flag_wait(f, t8 * 2);
          fence_async_g();
          TRC(el, 3, w * 32 + L * 16 + 15);
        }
        {
          AGENT_IDS;
          uint32_t* f = fr + FR_O + L;
#pragma unroll 1
          for (int e = 0; e < 5; e++) {
            const uint32_t nb = e ? 16384 : 8192, full = bars + B_OF + w * 40 + e * 8, dst = sb + o_place(w, e ? 2 * e - 1 : 0);
            const uint8_t* src = z1_block(rb, w, 0) + (e ? e * 16384 - 8192 : 0);
            expect_tx_p(el, full, nb);
            if (e == 0) {
              mbar_wait_c(ev + EV_O * 8, L);
              TRC(el, 3, w * 32 + L * 16 + 3);
              flag_add_p(el, f);
              if (!((MK_RUSH >> w) & 1)) flag_wait(f, t8);
            }
            if (w && e == 0) mbar_wait_c(bars + B_OF + YPACE * 8, L);
            if (w && e > 2) mbar_wait_c(bars + B_EVT + ((e - 3) * EV_N + EV_XS) * 8, 0);
            bulk_load_h(el, dst, src, nb, full, EF(6), pol);
            TRC(el && e == 0, 3, w * 32 + L * 16 + 5);
          }
        }
        {
          AGENT_IDS;
          const uint8_t* src = xn_block(hw);
          uint32_t full = bars + B_AF3 + w * 96, dst = sb + w * 6144;
          if (L) flag_wait(fj + FJ_P4, t8 * 4);
          mbar_wait_c(bars + B_XD + 8 - w * 8, L);
          mbar_wait_c(ev + EV_X1 * 8, L);
          TRC(el, 3, w * 32 + L * 16 + 6);
          pause<(MK_RUSH & 4) ? 0 : SDEL>(Q.zero);
#pragma unroll 1
          for (int k = 0; k < 12; k++, src += 6144, dst += 12288, full += 8) {
            expect_tx_p(el, full, 6144);
            if (k >= APACE) mbar_wait_c(full - APACE * 8, L);
            bulk_load_h(el, dst, src, 6144, full, EF(7), pol);
            TRC(el && k == 0, 3, w * 32 + L * 16 + 8);
          }
        }
        if (wid == 10) {
          AGENT_IDS;
          mbar_wait_c(ev - (EV_N - EV_ZN) * 8, L);
          mbar_wait_c(ev + EV_ZN * 8, L);
          asm volatile("fence.release.gpu;" ::: "memory");
          flag_add_p(el, fj + FJ_ZN + L);
          flag_add_p(el, fr - 32 + FR_XR + L);
          flag_wait(fj + FJ_ZN + L, t8 * 2);
          flag_wait(fr - 32 + FR_XR + L, t8);
          if (el) mbar_arrive(bars + B_ZOK);
        } else {
          AGENT_IDS;
          mbar_wait_c(ev + EV_ZN * 8, L);
          if (el) asm volatile("cp.async.bulk.prefetch.tensor.3d.L2.global [%0, {%1, %2, %3}];" ::"l"(&P.wsp), "r"(j * 128 + 64), "r"(rb * 64), "r"(0) : "memory");

        }
        float cv;
        {
        AGENT_IDS;
        cv = (lane & 3) ? 0.f : -blo(ldnc16(Q.b_sp + 128 * rb + 16 * j + 2 * (lane >> 2) + w));
        const uint32_t ro = (w * 64 + 8 * j + (lane >> 2)) * 128, x0 = ((lane & 3) * 2) ^ (lane >> 2);
#pragma unroll 1
        for (int i = 0; i < 32; i++) {
          const bool tail = (i >> 1) == 12;
          const int kb = tail ? i + 6 : i < 24 ? i : i - 2;
          if (!(i & 7)) mbar_wait_c(bars + B_RT + i, L);
          if (i == 24) mbar_wait_c(bars + B_WT + w * 8, 1);
          if (!tail) mbar_wait(bars + B_FULL + c.s * 8, c.ph ^ 1);
          uint4 x[2];
#pragma unroll
          for (int e = 0; e < 2; e++) x[e] = lds128(!tail ? sb + c.s * ST_BYTES + ro + ((x0 ^ e) << 4) : sb + SM_WT + w * 3200 + (lane >> 2) * 400 + (i - 24) * 256 + (lane & 3) * 32 + e * 16);
          if (!tail) {
            __syncwarp();
            if (el) mbar_arrive(bars + B_AD + c.s * 8 + ((x[0].x | x[1].x) & Q.zero));
            c.next();
          }
#pragma unroll
          for (int e = 0; e < 2; e++) {
            const uint4 a = x[e], m = lds128(sb + SM_RT + 4096 + kb * 128 + (lane & 3) * 32 + e * 16);
            cv = fmaf(blo(a.x), blo(m.x), fmaf(bhi(a.x), bhi(m.x), fmaf(blo(a.y), blo(m.y), fmaf(bhi(a.y), bhi(m.y), cv))));
            cv = fmaf(blo(a.z), blo(m.z), fmaf(bhi(a.z), bhi(m.z), fmaf(blo(a.w), blo(m.w), fmaf(bhi(a.w), bhi(m.w), cv))));
          }
          if (i == WTI) {
            uint32_t id2 = id;
            asm volatile("" : "+r"(id2));
            expect_tx_p(el, bars + B_WT + w * 8, 3072);
#pragma unroll 1
            for (int r = 0; r < 8; r++)
              bulk_load_p(el, sb + SM_WT + w * 3200 + r * 400, (const uint8_t*)Q.w_sp + (64 * (id2 & 30) + 16 * (id2 >> 5) + 2 * r + w) * (SEQ * 2) + 28 * 128, 384, bars + B_WT + w * 8);
          }
        }
        }
        AGENT_IDS;
        TRC(el, 3, w * 32 + L * 16 + 11);
        asm volatile("" : "+r"(t8));
        const uint32_t tag = (t8 >> 2) - 1 + L;
        cv = qsum(cv);
        uint2* const cs = (uint2*)(Q.XST + hw * 128 + 1);
        if ((lane & 3) == 0) ll_st64(cs + 32 * j + (lane >> 2) * 4, __float_as_uint(cv), tag);
#pragma unroll 1
        for (int it = 0; it < (1 << 22); it++) {
          const uint2 a = ll_ld64(cs + 4 * lane), b = ll_ld64(cs + 128 + 4 * lane);
          if (__all_sync(~0u, a.y == tag && b.y == tag)) { sts32(sb + SM_CV + w * 256 + lane * 4, a.x); sts32(sb + SM_CV + w * 256 + 128 + lane * 4, b.x); break; }
        }
        __syncwarp();
        if (el) mbar_arrive(bars + B_CV + w * 8);
        TRC(el, 3, w * 32 + L * 16 + 12);
#pragma unroll 1
        for (int kb = 30; kb < 32; kb++) {
          mbar_wait_c(bars + B_FULL + c.s * 8, c.ph ^ 1);
          if (el) mbar_arrive(bars + B_AD + c.s * 8);
          c.next();
        }
        c.ph ^= ((c.s + 11) >> 2) & 1; c.s = (c.s + 11) & 3;
        if (L == 0) {
          mbar_wait_c(ev + EV_PT * 8, 0);
          flag_add_p(el, fj + FJ_P4);
        }
      }
    } else {
      const uint32_t epoch = ldcg32(fj + FJ_EP + rb);
      mbar_wait(bars + B_IMG, 0);
      TRC(el, 2, 41);
      flag_release_p(el, fj + FJ_WQ);
      TRC(el, 2, 42);
#pragma unroll 1
      for (int L = 0; L < 2; L++) {
        float* const csf = Q.CSP + (NCTA + bid) * 216;
        if (L == 0) {
          flag_wait(fj + FJ_WQ, (epoch + 1) * 16);
          fence_async_g();
          expect_tx_p(el, bars + B_XRW, 13824);
          bulk_load_p(el, sb + ST_BYTES + SM_WOI, Q.CSP + j * 16 * 216, 6912, bars + B_XRW);
          bulk_load_p(el, sb + 2 * ST_BYTES + SM_WOI, Q.CSP + (j * 16 + 8) * 216, 6912, bars + B_XRW);
          mbar_wait(bars + B_XRW, 0);
#pragma unroll 1
          for (int f = lane; f < 54; f += 32) {
            float s[4] = {0.f, 0.f, 0.f, 0.f};
#pragma unroll 2
            for (int r = 0; r < 16; r++) {
              const uint4 v = lds128(sb + ST_BYTES + SM_WOI + (r >> 3) * ST_BYTES + (r & 7) * 864 + f * 16);
              s[0] += __uint_as_float(v.x); s[1] += __uint_as_float(v.y); s[2] += __uint_as_float(v.z); s[3] += __uint_as_float(v.w);
            }
            sts128(sb + SM_CSQ + f * 16, __float_as_uint(s[0]), __float_as_uint(s[1]), __float_as_uint(s[2]), __float_as_uint(s[3]));
            stg128(csf + f * 4, __float_as_uint(s[0]), __float_as_uint(s[1]), __float_as_uint(s[2]), __float_as_uint(s[3]));
          }
          __syncwarp();
          if (el) mbar_arrive(bars + B_XRW + 8);
          TRC(el, 2, 43);
          mbar_wait(bars + B_WOI, 0);
          bulk_store_p(el, Q.WO + j * WO_SL + rb * (41 * 128), sb + SM_WOI, (rb < 15 ? 41 : 33) * 128);
          publish_p(el, fj + FJ_WO);
          TRC(el, 2, 44);
          if (el) prefetch_l2((const uint8_t*)Q.w_in + bid * 41472, 41472);
          float o0 = 0.f, o1 = 0.f;
#pragma unroll 1
          for (int u = 0; u < 2; u++) {
            const uint8_t* src = (u ? (const uint8_t*)Q.w_sp + 500 * (SEQ * 2) + 2048 : (const uint8_t*)Q.w_in + 100 * (2 * FH * 2) + FH * 2) + lane * 16;
            const uint4 a = ldnc128(src), b = ldnc128(src + 300 * (2 * FH * 2) + 2048);
            const uint32_t x[8] = {a.x, a.y, a.z, a.w, b.x, b.y, b.z, b.w};
            float sq = 0.f;
#pragma unroll
            for (int e = 0; e < 8; e++) sq = fmaf(blo(x[e]), blo(x[e]), fmaf(bhi(x[e]), bhi(x[e]), sq));
            o0 = o1;
            asm("sqrt.approx.f32 %0, %1;" : "=f"(o1) : "f"(wsum(sq) * (u ? C0S * C0S * SEQ / 512.f : 2.f * GA * GA * DM / 512.f)));
          }
          const uint32_t off = (__float_as_uint(o0) & 0x7f800000u) >> 16 | 0x8000u | OFM;
          const uint32_t c0 = min(max(__float_as_uint(o1) & 0x7f800000u, 0x04000000u), 0x7e000000u) | 0x00400000u;
          if (el) sts128(sb + SM_OFF, off * 0x10001u, c0, __float_as_uint(GB), ((c0 >> 16) - 0x200u) * 0x10001u);
        }
#pragma unroll 1
        for (int w = 0; w < 2; w++) {
          mbar_wait(bars + B_EVT + (w * EV_N + EV_X1) * 8, L);
          mbar_wait(bars + B_EVT + (w * EV_N + EV_XS) * 8, 1);
          if (!w) mbar_wait(bars + B_AF3 + 96 + XP0 * 8, L);
          if (el) asm volatile("cp.async.bulk.tensor.3d.global.shared::cta.tile.bulk_group [%0, {%2, %3, %4}], [%1];\ncp.async.bulk.commit_group;\ncp.async.bulk.wait_group.read 0;" ::"l"(&P.res[1]), "r"(sb + SM_STG + 9216), "r"(j * 72), "r"(rb * 64 + (w ^ 1) * 32), "r"(0) : "memory");
          __syncwarp();
          if (lane < 2 && !w) mbar_arrive(bars + B_S5);
        }
        sts64(sb + SM_CV + 512 + lane * 8, 0x3f803f80u, 0x3f803f80u);
        fence_async_s();
        __syncwarp();
        if (el) { asm volatile("cp.async.bulk.wait_group 0;" ::: "memory"); mbar_arrive(bars + B_GATE3); }
        const uint32_t tag = epoch * 2 + L + 1;
        asm volatile("" : "+r"(lane));
#pragma unroll 1
        for (int b = 0; b < 8; b++) {
          if (!(b & 3)) {
            const int mb = b >> 2;
            mbar_wait(bars + B_ZS + mb * 8, L);
            pause<ZD1>(Q.zero);
            TRC(el && !mb, 2, L * 16 + 8);
            uint4 v;
#pragma unroll 1
            for (int it = 0; it < (1 << 22); it++) {
              v = ll_ld128(Q.ZST + ((rb * 2 + mb) * 8 + (lane >> 2)) * 32 + 4 * j + (lane & 3));
              if (__all_sync(~0u, max(max(v.x, v.y), max(v.z, v.w)) != ~0u)) break;
            }
            if (lane < 2 && !mb) mbar_arrive(bars + B_S5);
            const bool o = lane & 16;
            float ss = __uint_as_float(o ? v.y : v.x) + __shfl_xor_sync(~0u, __uint_as_float(o ? v.x : v.y), 16), sq = __uint_as_float(o ? v.w : v.z) + __shfl_xor_sync(~0u, __uint_as_float(o ? v.z : v.w), 16);
            ss += __shfl_xor_sync(~0u, ss, 4); sq += __shfl_xor_sync(~0u, sq, 4); ss += __shfl_xor_sync(~0u, ss, 8); sq += __shfl_xor_sync(~0u, sq, 8);
            const float mean = ss * (1.f / FH), rs = blo(pack2(rsq_fast(fmaxf(fmaf(sq, 1.f / FH, -mean * mean), 0.f) + 4.f * GA * GA * LN_EPS), 0.f));
            if (!(lane & 12)) ll_st64(Q.RT + (mb * 16 + rb) * 64 + 8 * j + 2 * (lane & 3) + (lane >> 4), pack2(rs, rs * (mean - blo(lds32(sb + SM_OFF)))), tag);
            TRC(el && !mb, 2, L * 16 + 10);
            pause<ZD2>(Q.zero);
          }
          uint4 v[4];
#pragma unroll 1
          for (int it = 0; it < (1 << 22); it++) {
            bool ok = true;
#pragma unroll
            for (int u = 0; u < 4; u++) { v[u] = ll_ld128((const uint4*)Q.RT + b * 128 + u * 32 + lane); ok = ok && v[u].y == tag && v[u].w == tag; }
            if (__all_sync(~0u, ok)) break;
          }
#pragma unroll
          for (int u = 0; u < 4; u++) {
            const uint32_t rt = sb + SM_RT + b * 512 + u * 128, ro = (lane >> 3) * 32 + (lane & 3) * 8 + ((lane >> 2) & 1) * 2;
            sts32(rt + 4096 + lane * 4, __byte_perm(v[u].x, v[u].z, 0x7632));
            asm volatile("st.shared.u16 [%0], %1;\nst.shared.u16 [%0 + 4], %2;" ::"r"(rt + ro), "h"((uint16_t)v[u].x), "h"((uint16_t)v[u].z) : "memory");
          }
          __syncwarp();
          if (el && (b & 1)) mbar_arrive(bars + B_RT + (b - 1) * 4);
          TRC(el && b < 2, 2, L * 16 + 11 + b);
        }
        TRC(el, 2, L * 16 + 9);
        mbar_wait(bars + B_EVT + EV_Z1 * 8, L);
        mbar_wait(bars + B_EVT + (EV_N + EV_Z1) * 8, L);
        fence_gpu();
        if (el) mbar_arrive(bars + B_Z1);
      }
    }
  } else {
    int w = wid >> 2, q = wid & 3, rb = bid & 15, j = bid >> 4;
    int g = lane >> 2, t = lane & 3;
#define PHASE asm volatile("" : "+r"(w), "+r"(q), "+r"(rb), "+r"(j))
#define stg (sb + SM_STG + w * 9216)
#define pw (q >> 1)
#define pq (2 - 2 * w + (q & 1))
    const bool tr = (tid & 127) == 0;
    (void)tr;
    Cur c{0, 0};
    const uint32_t ebar = mapa(bars + B_EMPTY, (bid & 1) ^ (lane & 1));
    auto release = [&](uint32_t s) { if (lane < 2) mbar_arrive_cluster(ebar + s * 8); };
    uint32_t ia = 0;
    auto wait_ab = [&]() { mbar_wait_c(bars + B_FULL + c.s * 8, c.ph); mbar_wait_c(bars + B_FULLA + w * 32 + c.s * 8, (ia >> c.s) & 1); ia ^= 1u << c.s; };
    uint32_t rp = 0;
    auto check = [&](auto n, uint32_t dst, const uint8_t* src, uint32_t bar, uint32_t ph) {
      const uint32_t a = dst + lane * 32 + (lane >> 2) * 4;
#pragma unroll 1
      for (int it = 0; it < (1 << 16); it++) {
        uint32_t x = lds32(a);
#pragma unroll
        for (int e = 1; e < n.value; e++) x = max(x, lds32(a + e * 1024));
        if (!__any_sync(~0u, x == ~0u)) break;
        fence_async_s();
        __syncwarp();
        const uint32_t el = elect_one();
        expect_tx_p(el, bar, n.value * 1024);
        bulk_load_p(el, dst, src, n.value * 1024, bar);
        mbar_wait_c(bar, ph);
        __syncwarp();
        if (el) mbar_arrive(bar);
        __syncwarp();
        rp++;
      }
    };
    auto signal = [&](int e) { __syncwarp(); if (lane == 0) mbar_arrive(bars + B_EVT + w * EV_N * 8 + e * 8); };
    TRC(tr, w, 0);

    {
      uint8_t* dst = Q.WQ + j * WQ_SL + rb * 3456 + tid * 16;
#pragma unroll
      for (int u = 0; u < 5; u++) {
        stg128_if((u < 4 || rb < 8) && tid < 216, dst + u * (16 * 3456), wv[u].x, wv[u].y, wv[u].z, wv[u].w);
        if (u == 0) TRC(tr, w, 60);
      }
      if (Q.zero == 0) {
        float s[8];
#pragma unroll
        for (int u = 0; u < 5; u++) {
          const uint32_t x[4] = {wv[u].x, wv[u].y, wv[u].z, wv[u].w};
#pragma unroll
          for (int e = 0; e < 4; e++) { s[2 * e] = u ? s[2 * e] + blo(x[e]) : blo(x[e]); s[2 * e + 1] = u ? s[2 * e + 1] + bhi(x[e]) : bhi(x[e]); }
        }
#pragma unroll
        for (int m = 4; m; m >>= 1) {
#pragma unroll
          for (int e = 0; e < m; e++) s[e] = ((tid & m) ? s[e + m] : s[e]) + __shfl_xor_sync(~0u, (tid & m) ? s[e] : s[e + m], m);
        }
        stg32_if(tid < 216, Q.CSP + bid * 216 + tid, __float_as_uint(s[0]));
      }
      __syncwarp();
      if (lane == 0) mbar_arrive(bars + B_IMG);
    }
    reg_alloc<224>();
    auto fetch_wo = [&]() {
#pragma unroll 1
      for (int u = tid; u < 328; u += 256) {
        const int m = min(41 * rb + (u >> 3), 647), k8 = m / 9;
        cp_async16(sb + SM_WOI + u * 16, (const uint8_t*)Q.wo + (8 * k8 + (u & 7)) * (DM * 2) + (72 * j + 8 * (m - k8 * 9)) * 2);
      }
    };
    const uint32_t epoch = ldcg32(Q.flags + (rb * 2 + w) * 32 + FR_EP + j);
    TRC(tr, w, 1);

#pragma unroll 1
    for (int L = 0; L < 2; L++) {
      const int tb = 2 + L * 24;
      asm volatile("" : "+r"(lane), "+r"(g), "+r"(t));
      PHASE;
      (void)tb;
      const uint32_t tag = epoch * 2 + L + 1;
      {
        uint32_t Pk[27][2];
        float rk[2][2], sc[2][2];
        const bool up0 = 2 * t > g, up1 = 2 * t + 1 > g;
        constexpr int HA_[6] = {0, 2, 4, 7, 12, 15}, HC_[6] = {6, 9, 10, 11, 14, 17};
        const bool remote = pq == 0 && rb > 0;
        uint4* hp = Q.HALO + ((((rb - (pq == 0)) * 2 + pw) * 8 + j) * 6) * 32 + lane;
        const uint32_t att = 2 * ST_BYTES + pw * 3072 + lane * 16;
        const uint8_t* hs = remote ? (const uint8_t*)hp : smem_raw + att + (pq == 3 ? 0 : pq == 2 ? ST_BYTES + 8192 : 8192);
        uint8_t* od = z1_block(rb, w, 0) + (9 * j) * 1024 + (4 * (q & 1) + pw) * 128 + lane * 4;
        ACLK_INIT;
        {
          float acc[108];
#pragma unroll
          for (int i = 0; i < 108; i++) acc[i] = 0.f;
          float sx[2] = {0.f, 0.f}, sq[2] = {0.f, 0.f};
          uint32_t prev = 0;
#pragma unroll 1
          for (int kb = 0; kb < 7; kb++) {
            wait_ab();
            TRC(tr && kb == 0, w, tb + 0);
            PCLK(kb * 4);
            const uint32_t st = sb + c.s * ST_BYTES, da = dlo(st + w * 8192, 16), db = dlo(st + ST_B, 3456);
            wgmma_fence();
#pragma unroll
            for (int kk = 0; kk < 4; kk++) {
              wgmma_ss_n216(acc, dsc<1024, 1>(da, kk * 32), dsc<128, 0>(db, kk * 6912), 1);
              if (kk == 0) { wgmma_commit(); wgmma_wait<1>(); if (kb > 0) release(prev); }
              if (kk == 3) wgmma_commit();
              if (kk == XK1) {
            if (kb >= KS && kb < KS + 3) {
              mbar_wait_c(bars + B_WT + w * 8, 0);
#pragma unroll
              for (int u = 0; u < 3; u++) {
                const uint2 x = lds64(stg + (2 * q + (lane >> 4)) * 1152 + (lane & 15) * 8 + (kb - KS) * 384 + u * 128);
                sx[0] += blo(x.x) + bhi(x.x); sx[1] += blo(x.y) + bhi(x.y);
                sq[0] = fmaf(blo(x.x), blo(x.x), fmaf(bhi(x.x), bhi(x.x), sq[0])); sq[1] = fmaf(blo(x.y), blo(x.y), fmaf(bhi(x.y), bhi(x.y), sq[1]));
              }
            }
            if (kb == KS + 3) {
              const bool o = lane & 1;
              float v = (o ? sq[0] + sq[1] : sx[0] + sx[1]) + __shfl_xor_sync(~0u, o ? sx[0] + sx[1] : sq[0] + sq[1], 1);
              v += __shfl_xor_sync(~0u, v, 2); v += __shfl_xor_sync(~0u, v, 4); v += __shfl_xor_sync(~0u, v, 8);
              const float m = v * (-1.f / DM), r = rsq_fast(fmaxf(fmaf(__shfl_xor_sync(~0u, v, 1), 1.f / DM, -m * m), 0.f) + LN_EPS);
              ll_st128_if(!(lane & 15), Q.XST + rb * 256 + (lane >> 4) * 128 + (1 - w) * 64 + 8 * j + 2 * q, m, r, tag);
            }
              }
              if (kk == XK2 && L == 0) {
            if (kb == 0) fetch_wo();
            if (kb == 3) {
              asm volatile("cp.async.wait_all;" ::: "memory");
              fence_async_s();
              __syncwarp();
              if (lane == 0) mbar_arrive(bars + B_WOI);
            }
              }
            }
            prev = c.s; c.next();
          }
          const uint32_t cs = sb + SM_CSQ + t * 8;
          float2 cv[27];
          mbar_wait_c(bars + B_XRW + 8, L);
#pragma unroll
          for (int kb = 7; kb < 9; kb++) {
            wait_ab();
            PCLK(kb * 4);
            const uint32_t st = sb + c.s * ST_BYTES, da = dlo(st + w * 8192, 16), db = dlo(st + ST_B, 3456);
            wgmma_fence();
#pragma unroll
            for (int kk = 0; kk < 4; kk++) {
              wgmma_ss_n216(acc, dsc<1024, 1>(da, kk * 32), dsc<128, 0>(db, kk * 6912), 1);
              if (kk == 0) { wgmma_commit(); wgmma_wait<1>(); release(prev); }
              if (kb == 7 && kk < 3) {
#pragma unroll
                for (int G = 9 * kk; G < 9 * kk + 9; G++) cv[G] = lds64f(cs + G * 32);
                wgmma_fence();
              }
            }
            wgmma_commit();
            prev = c.s; c.next();
          }
          mbar_wait_c(bars + B_CSQ, L);
          const uint32_t xs = sb + SM_XST + pw * 768 + 256 + pq * 128;
          const float2 n0 = lds64f(xs + g * 8), n1 = lds64f(xs + g * 8 + 64);
          const float m0 = n0.x, m1 = n1.x;
#pragma unroll
          for (int u = 0; u < 4; u++) {
            rk[u >> 1][u & 1] = __uint_as_float(lds32(xs + t * 16 + ((u & 1 ? up1 : up0) ? -64 : 0) + (u & 1) * 8 + (u >> 1) * 64 + 4));
            sc[u >> 1][u & 1] = rk[u >> 1][u & 1] * ((u >> 1 ? n1.y : n0.y) * (0.23570226039551584f * 1.4426950408889634f));
          }
          PCLK(36);
          wgmma_wait<0>();
          PCLK(37);
          release(prev);
          TRC(tr, w, tb + 1);
          ACLK(0);
#pragma unroll
          for (int G = 9; G < 27; G++) Pk[G][1] = pack2(fmaf(m1, cv[G].x, acc[4 * G + 2]), fmaf(m1, cv[G].y, acc[4 * G + 3]));
          if (pq < 3) {
#pragma unroll
            for (int i = 0; i < 6; i++) sts128(sb + att + (pq & 1) * ST_BYTES + w * 8192 + i * 512, Pk[9 + HA_[i]][1], Pk[10 + HA_[i]][1], tag, Pk[9 + HC_[i]][1]);
            if (w) bar_arrive(1, 256);
          } else if (rb < 15) {
#pragma unroll
            for (int i = 0; i < 6; i++) ll_st128(hp + i * 32, __uint_as_float(Pk[9 + HA_[i]][1]), __uint_as_float(Pk[10 + HA_[i]][1]), tag, __uint_as_float(Pk[9 + HC_[i]][1]));
          }
#pragma unroll
          for (int G = 0; G < 27; G++) {
            Pk[G][0] = pack2(fmaf(m0, cv[G].x, acc[4 * G]), fmaf(m0, cv[G].y, acc[4 * G + 1]));
            if (G < 9) Pk[G][1] = pack2(fmaf(m1, cv[G].x, acc[4 * G + 2]), fmaf(m1, cv[G].y, acc[4 * G + 3]));
          }
        }
        ACLK(1);
        constexpr int GA_[4] = {0, 2, 4, 7}, GB_[4] = {1, 3, 5, 8}, GC_[4] = {2, 4, 6, 6};
        float S1[4][4], S2[4][4];
        uint32_t qa[4][2], qc[4][2];
#pragma unroll
        for (int h = 0; h < 4; h++) {
#pragma unroll
          for (int r = 0; r < 2; r++) {
            qa[h][r] = (h == 0 || h == 3 || t >= h) ? Pk[GA_[h]][r] : 0u;
            qc[h][r] = (h == 3 ? t == 3 : t <= h) ? Pk[GC_[h]][r] : 0u;
          }
#pragma unroll
          for (int i = 0; i < 4; i++) S1[h][i] = S2[h][i] = 0.f;
          mma16(S1[h], qa[h][0], qa[h][1], Pk[GB_[h]][0], Pk[GB_[h]][1], Pk[9 + GA_[h]][0], Pk[9 + GB_[h]][0]);
          mma16(S2[h], qa[h][0], qa[h][1], Pk[GB_[h]][0], Pk[GB_[h]][1], Pk[9 + GA_[h]][1], Pk[9 + GB_[h]][1]);
        }
#pragma unroll
        for (int h = 0; h < 4; h++) {
          mma8(S1[h], qc[h][0], qc[h][1], Pk[9 + GC_[h]][0]);
          mma8(S2[h], qc[h][0], qc[h][1], Pk[9 + GC_[h]][1]);
        }
        uint32_t V1[9], V2[9];
#pragma unroll
        for (int i = 0; i < 9; i++) { V1[i] = movm(Pk[18 + i][0]); V2[i] = movm(Pk[18 + i][1]); }
        uint4 hv[6];
        auto look = [&]() {
          bar_sync(1 + w, 256 - 128 * w);
          if (w) mbar_wait_c(bars + B_HOLD, L);
#pragma unroll
          for (int i = 0; i < 6; i++) hv[i] = ll_ld128g(hs + i * 512);
        };
        const uint32_t mup = (up0 ? 0xffffu : 0u) | (up1 ? 0xffff0000u : 0u);
        auto finish = [&](const float (&x0)[4], const float (&x1)[4], const uint32_t (&Vb)[9], uint32_t ma, int hi) {
          uint32_t p[4], n[4];
          float rs[4];
#pragma unroll
          for (int h = 0; h < 4; h++) {
            const float m = qmax(fmaxf(x0[h], x1[h])), e0 = ex2(x0[h] - m), e1 = ex2(x1[h] - m);
            n[h] = pack2(e0, e1);
            p[h] = pack2(e0 * rk[hi][0], e1 * rk[hi][1]);
          }
          if (hi) look();
#pragma unroll
          for (int h = 0; h < 4; h += 2) {
            float D[4] = {0.f, 0.f, 0.f, 0.f};
            mma8(D, n[h], n[h + 1], 0x3f803f80u);
            rs[h] = rcp_fast(D[0]); rs[h + 1] = rcp_fast(D[2]);
          }
#pragma unroll
          for (int i = 0; i < 9; i++) {
            const int h = i < 4 ? 0 : i == 4 ? 1 : 2;
            const bool nx = (i == 2 || i == 4 || i == 6) ? 2 * t >= i : i == 3 || i > 6;
            float O[4] = {0.f, 0.f, 0.f, 0.f};
            mma16(O, p[h] & ma, p[h + 1] & ma, p[h] & ~ma, p[h + 1] & ~ma, V1[i], Vb[i]);
            const float r = nx ? rs[h + 1] : rs[h];
            stg32(od + i * 1024 + hi * 256, pack2((nx ? O[2] : O[0]) * r, (nx ? O[3] : O[1]) * r));
          }
        };
        {
          float x0[4], x1[4];
#pragma unroll
          for (int h = 0; h < 4; h++) { x0[h] = (up0 ? S1[h][2] : S2[h][2]) * sc[1][0]; x1[h] = (up1 ? S1[h][3] : S2[h][3]) * sc[1][1]; }
          finish(x0, x1, V2, mup, 1);
        }
        ACLK(2);
        if (lane + w == 0) mbar_arrive(bars + B_HOLD);
        if (remote) {
#pragma unroll 1
          for (int it = 0; it < (1 << 20); it++) {
            bool ok = true;
#pragma unroll
            for (int i = 0; i < 6; i++) ok = ok && hv[i].z == tag;
            if (__all_sync(~0u, ok)) break;
#pragma unroll
            for (int i = 0; i < 6; i++) hv[i] = ll_ld128g(hs + i * 512);
          }
        }
        uint32_t H[18];
#pragma unroll
        for (int i = 0; i < 6; i++) { H[HA_[i]] = hv[i].x; H[HA_[i] + 1] = hv[i].y; H[HC_[i]] = hv[i].w; }
        float S0[4][4];
#pragma unroll
        for (int h = 0; h < 4; h++) {
#pragma unroll
          for (int i = 0; i < 4; i++) S0[h][i] = 0.f;
          mma16(S0[h], qa[h][0], qa[h][1], Pk[GB_[h]][0], Pk[GB_[h]][1], H[GA_[h]], H[GB_[h]]);
        }
#pragma unroll
        for (int h = 0; h < 4; h++) mma8(S0[h], qc[h][0], qc[h][1], H[GC_[h]]);
        uint32_t V0[9];
#pragma unroll
        for (int i = 0; i < 9; i++) V0[i] = movm(H[9 + i]);
        ACLK(3);
        {
          const bool nohalo = (rb | pq) == 0;
          const float b0 = up0 && nohalo ? -INFINITY : 0.f, b1 = up1 && nohalo ? -INFINITY : 0.f;
          float x0[4], x1[4];
#pragma unroll
          for (int h = 0; h < 4; h++) { x0[h] = fmaf(up0 ? S0[h][0] : S1[h][0], sc[0][0], b0); x1[h] = fmaf(up1 ? S0[h][1] : S1[h][1], sc[0][1], b1); }
          finish(x0, x1, V0, ~mup, 0);
        }
        ACLK(4);
        signal(EV_O);
        ACLK_OUT;
        OCLK(q == 1, 4, w * 8 + 6);
        TRC(tr, w, tb + 2);
      }
      if (c.s) { c.s = 0; c.ph ^= 1; }
      PHASE;
      {
        float acc[36];
        const int hw = rb * 2 + w;
        const uint32_t xt = stg + (8 * q + g) * 144 + t * 4;
        uint32_t xm = sb + SM_STG + 9216 + (8 * q + (lane & 7)) * 144 + (lane & 8) * 576 + (lane & 16);
        uint8_t* xn = xn_block(hw) + j * 9216 + q * 256 + lane * 4;
        uint32_t* sp = (uint32_t*)(Q.ST1 + (hw * 8 + j) * 32 + 8 * q) + lane;
        const uint4* sg = Q.ST1 + (hw * 8 + t) * 32 + 8 * q + g;
        asm volatile("" : "+r"(xm), "+l"(xn), "+l"(sp), "+l"(sg));
        mbar_wait_c(bars + B_RES + w * 8, L);
        uint32_t xr[18];
#pragma unroll
        for (int i = 0; i < 18; i++) xr[i] = lds32(xt + (i >> 1) * 16 + (i & 1) * 4608);
        uint32_t xa = 0;
#pragma unroll
        for (int i = 0; i < 18; i++) xa |= xr[i];
        signal(EV_XS + (xa & Q.zero));
        mbar_wait_c(bars + B_WF, L);
        TRC(tr, w, tb + 21);
        RCLK_INIT;
#pragma unroll 1
        for (uint32_t first = 1;; first = 0) {
          PHASE;
#pragma unroll
          for (int i = 0; i < 18; i++) { asm volatile("" : "+r"(xr[i])); acc[2 * i] = blo(xr[i]); acc[2 * i + 1] = bhi(xr[i]); asm volatile("" : "+f"(acc[2 * i]), "+f"(acc[2 * i + 1])); }
          const uint32_t db = dlo(sb, 1152), of = bars + B_OF + w * 40;
          uint32_t da = dlo(sb + o_place(0, 0), 1024) - w * 2560;
          mbar_wait_c(of, L);
          if (w && first) bar_sync(7, 256);
          TRC(tr, w, tb + 3);
          OCLK(q == 1, 4, w * 8);
          wgmma_fence();
#pragma unroll
          for (int kk = 0; kk < 4; kk++) wgmma_ss_n72(acc, dsc<128, 0>(da, kk * 2048), dsc<128, 0>(db, kk * 2304), 1);
          wgmma_commit();
#pragma unroll 1
          for (int h = 0; h < 2; h++) {
#pragma unroll
            for (int u = 0; u < 4; u++) {
              if (!(u & 1)) { mbar_wait_c(of + 8 + h * 16 + u * 4, L); OCLK(q == 1, 4, w * 8 + 1 + 2 * h + (u >> 1)); wgmma_fence(); }
              if (u == 3 && h && first > w) bar_arrive(7, 256);
#pragma unroll
              for (int kk = 0; kk < 4; kk++) wgmma_ss_n72(acc, dsc<128, 0>(da, (1 + u) * 8192 + kk * 2048), dsc<128, 0>(db + h * 2304, (1 + u) * 9216 + kk * 2304), 1);
              if (u & 1) wgmma_commit();
            }
            da += (4 + 9 * w) * 512;
          }
          wgmma_wait<0>();
          RCLK(0);
          OCLK(q == 1, 4, w * 8 + 5);
          TRC(tr && P5TRACE != 5, w, tb + 4);
          float s0 = 0.f, s1 = 0.f, q0 = 0.f, q1 = 0.f;
#pragma unroll
          for (int i = 0; i < 36; i++) {
            if (i & 2) { s1 += acc[i]; q1 = fmaf(acc[i], acc[i], q1); } else { s0 += acc[i]; q0 = fmaf(acc[i], acc[i], q0); }
          }
          const bool o1 = t & 1, o2 = t & 2;
          const float ss = (o1 ? s1 : s0) + __shfl_xor_sync(~0u, o1 ? s0 : s1, 1), sq = (o1 ? q1 : q0) + __shfl_xor_sync(~0u, o1 ? q0 : q1, 1);
          const float v = (o2 ? sq : ss) + __shfl_xor_sync(~0u, o2 ? ss : sq, 2);
          uint32_t bad = first && (v != v || (((MK_RUSH >> 3) >> w) & 1 && lane == 5 && ((j + rb) & 1)));
          asm volatile("{\n.reg .pred p, q;\nsetp.ne.u32 q, %0, 0;\n@!q st.relaxed.gpu.global.f32 [%1], %2;\nbar.red.or.pred p, %3, 128, q;\nselp.u32 %0, 1, 0, p;\n}" : "+r"(bad) : "l"(sp), "f"(v), "r"(3 + w) : "memory");
          if (!__any_sync(~0u, bad)) break;
#pragma unroll 1
          for (int kb = q; kb < 9; kb += 4) check(Int<8>{}, sb + o_place(w, kb), z1_block(rb, w, 0) + kb * 8192, of + q * 8, L ^ 1);
          bar_sync(3 + w, 128);
        }
        if (lane < 2) mbar_arrive_cluster(ebar + B_XD - B_EMPTY + w * 8);
        RCLK(1);
        RCLK(2);
        pause<PDEL>(Q.zero);
        uint4 pa, pb;
        auto there = [&](const uint4& a, const uint4& b) { return __all_sync(~0u, max(max(max(a.x, a.y), max(a.z, a.w)), max(max(b.x, b.y), max(b.z, b.w))) != ~0u); };
#pragma unroll 1
        for (int it = 0; it < (1 << 20); it++) {
          pa = ll_ld128(sg); pb = ll_ld128(sg + 128);
          if (there(pa, pb)) break;
        }
        RCLK(3);
        float mean0 = qsum(__uint_as_float(pa.x) + __uint_as_float(pb.x)) * (-1.f / DM), mean1 = qsum(__uint_as_float(pa.y) + __uint_as_float(pb.y)) * (-1.f / DM);
        const float rs0 = GA * rsq_fast(fmaxf(fmaf(qsum(__uint_as_float(pa.z) + __uint_as_float(pb.z)), 1.f / DM, -mean0 * mean0), 0.f) + LN_EPS);
        const float rs1 = GA * rsq_fast(fmaxf(fmaf(qsum(__uint_as_float(pa.w) + __uint_as_float(pb.w)), 1.f / DM, -mean1 * mean1), 0.f) + LN_EPS);
        mean0 *= rs0; mean1 *= rs1;
#pragma unroll
        for (int i = 0; i < 18; i++) {
          const float a = (i & 1) ? rs1 : rs0, b = (i & 1) ? mean1 : mean0;
          stg32(xn + (i >> 1) * 1024 + (i & 1) * 128, pack2(fmaf(acc[2 * i], a, b), fmaf(acc[2 * i + 1], a, b)));
        }
        signal(EV_X1);
        RCLK(4);
        if (w) {
#pragma unroll 1
          for (int u = q; u < 24; u += 4) {
            const uint32_t mb = u < 2 * SPL ? u >= SPL : u & 1, k = u < 2 * SPL ? u - mb * SPL : u >> 1;
            mbar_wait_c(bars + B_AF3 + mb * 96 + k * 8, L);
            SCLK3(u);
            check(Int<6>{}, sb + k * 12288 + mb * 6144, xn_block(rb * 2 + mb) + k * 6144, bars + B_RB + q * 8, 0);
            SCLK3(24 + u);
            if (lane <= (u < 2 * SPL)) mbar_arrive(bars + B_AV + (u < SPL ? 12 + k : k) * 8);
          }
          TRVI(lane == 0 && P5TRACE != 5, 5, 56 + L * 4 + q, rp);
        }
        mbar_wait_c(bars + (w ? B_S5 : B_XD + 8), L & ~w);
#pragma unroll
        for (int u = 0; u < 4; u++)
          stsm4(xm + u * 32, pack2(acc[8 * u], acc[8 * u + 1]), pack2(acc[8 * u + 2], acc[8 * u + 3]), pack2(acc[8 * u + 4], acc[8 * u + 5]), pack2(acc[8 * u + 6], acc[8 * u + 7]));
        asm volatile("stmatrix.sync.aligned.m8n8.x2.shared.b16 [%0], {%1,%2};" ::"r"(xm + 128), "r"(pack2(acc[32], acc[33])), "r"(pack2(acc[34], acc[35])) : "memory");
        fence_async_s();
        signal(EV_XS);
        RCLK(5);
        TRC(tr, w, tb + 5);
        RCLK(6);
        RCLK_OUT;
      }
      PHASE;
      {
      float acc[160];
#pragma unroll
      for (int i = 0; i < 160; i++) acc[i] = 0.f;
      float s[2] = {0.f, 0.f}, qq[2] = {0.f, 0.f}, zo = 0.f;
      const uint32_t zp = sb + SM_ZP3 + (tid & 127) * 4;
      auto zstat = [&](int mb, bool on) {
        const bool o1 = t & 1, o2 = t & 2;
        const float ss = ((o1 ? s[1] : s[0]) + __shfl_xor_sync(~0u, o1 ? s[0] : s[1], 1)) * 0x1p60f, sq = (o1 ? qq[1] : qq[0]) + __shfl_xor_sync(~0u, o1 ? qq[0] : qq[1], 1);
        const uint32_t v = __float_as_uint((o2 ? sq : ss) + zo + __shfl_xor_sync(~0u, o2 ? ss : sq, 2));
        asm volatile("{\n.reg .pred p, q, r;\nsetp.eq.u32 p, %4, 1;\nsetp.eq.u32 q, %4, 2;\nsetp.eq.and.u32 r, %5, 0, q;\n@p st.shared.u32 [%0], %2;\n@p bar.arrive 13, 256;\n"
                     "@q st.relaxed.gpu.global.u32 [%1], %2;\n@r mbarrier.arrive.shared::cta.b64 _, [%3];\n}" ::"r"(zp + mb * 512), "l"((uint32_t*)(Q.ZST + ((rb * 2 + mb) * 8 + j) * 32) + (tid & 127)),
                     "r"(v), "r"(bars + B_ZS + mb * 8), "r"(on ? 1 + w : 0), "r"(lane) : "memory");
        s[0] = s[1] = qq[0] = qq[1] = 0.f;
      };
      const uint32_t ebar3 = ebar + (B_E3 - B_EMPTY);
#pragma unroll 1
      for (int half = 0; half < 2; half++) {
        const bool big = half != w;
        auto rel3 = [&](int p) { if (lane < 2) mbar_arrive_cluster(ebar3 + p * 8); };
        auto pass = [&](auto nk) {
          constexpr int NK = nk.value;
          uint32_t d0 = dlo(sb, 1024), ph = half & ~w, af = bars + B_AV;
          const uint32_t db = dlo(sb + SM_B3, NK == 3 ? 6144 : 2048);
          const bool lead = NK == 3 && !half;
          if (lead) {
#pragma unroll
            for (int u = 0; u < 2 * SPL; u++) {
              const int mb = u / SPL, p = u % SPL;
              if (!mb) mbar_wait_c(bars + B_F3 + p * 8, 0);
              mbar_wait_c(af + (mb ? p : 12 + p) * 8, L);
              TRC(tr && u == 0, w, tb + 6);
              SCLK2(u);
              if (p == 0) SCLK(mb * 4);
              wgmma_fence();
#pragma unroll
              for (int kk = 0; kk < 3; kk++) {
                wgmma_ss_n128(acc + mb * 80, dsc<128, 0>(d0, p * 12288 + kk * 2048 + mb * 6144), dsc<1024, 1>(db, p * 12288 + kk * 2048), p + kk > 0);
                if (kk == 0 && u > SPL) { wgmma_commit(); wgmma_wait<1>(); rel3(p - 1); }
              }
              wgmma_commit();
            }
          }
#pragma unroll 1
          for (int it = 0; it < 6 / NK; it++) {
#pragma unroll
            for (int p = 0; p < 6; p++) {
              if (p < SPL && lead && it == 0) continue;
              if (NK == 3) mbar_wait_c(af + p * 8, L);
              if (p == 0 && it == 0) bar_sync(6 + w, 256);
              mbar_wait_c(bars + B_F3 + p * 8, ph);
              TRC(tr && p == 0 && it == 0, w, tb + 6 + half * 4);
              if (lead) SCLK2(12 + it * 6 + p);
              if (NK == 2 ? !(p & 1) : p % 3 == 0) SCLK(half * 11 + (NK == 2 ? it * 3 + p / 2 : it * 2 + p / 3));
              wgmma_fence();
#pragma unroll
              for (int u = 0; u < 2 * NK; u++) {
                const int kk = u >> 1, mb = u & 1, e = p * NK + kk;
                const uint64_t da = dsc<128, 0>(d0, (e / 3) * 12288 + (e % 3) * 2048 + mb * 6144);
                if (NK == 3) wgmma_ss_n128(acc + mb * 80, da, dsc<1024, 1>(db, p * 12288 + kk * 2048), e > 0 || it > 0);
                else wgmma_ss_n160(acc + mb * 80, da, dsc<1024, 1>(db, p * 12288 + kk * 6144), e > 0 || it > 0);
                if (u == 0) { wgmma_commit(); wgmma_wait<1>(); if (p > 0 || it > 0) rel3((p + 5) % 6); }
                if (p * 8 + u == (NK == 2 ? HO3 : HO4) && it == 6 / NK - 1) bar_arrive(7 - w, 256);
              }
              wgmma_commit();
            }
            d0 += NK * 1536; af += 48;
            ph ^= 1;
          }
        };
        const int go = (j & 1) ? (big ? 0 : 20) : (big ? 16 : 0);
        const float* gbp = (const float*)(smem_raw + SM_OFF + 8);
        asm volatile("" : "+l"(gbp));
        uint8_t* zd = half ? z1_block(rb, 0, j) + go * 1024 + (q & 1) * 2048 + (q >> 1) * 512 + lane * 16 : z2_block(rb, j) + q * 9216 + go * 128 + ((g & 3) * 2 + (g >> 2)) * 16 + t * 4;
        asm volatile("" : "+l"(zd));
        if (big) pass(Int<2>{}); else pass(Int<3>{});
        if (w) { bar_sync(13, 256); zo = __uint_as_float(lds32(zp + half * 512)); }
        if (half) zstat(1, true);
        mbar_wait_c(bars + B_S5, half);
        const uint32_t off2 = lds32(sb + SM_OFF);
        wgmma_wait<0>();
        SCLK(half * 11 + 9);
        rel3(5);
        TRC(tr, w, tb + 7 + half * 4);
        auto gelu = [&](auto z2) {
          float gate[NC2], gb = GB, gn = GB;
          uint32_t qa[2][3] = {{0, 0, 0}, {0, 0, 0}};
#pragma unroll
          for (int e = 0; e < NC2; e++) gate[e] = GB;
#pragma unroll
          for (int G = 0; G < 20; G++) {
            if (G == 16 && !big) break;
            if (z2.value && G % LD2 == 0) { gb = gn; if (G < 20 - LD2) asm volatile("ld.f32 %0, [%1];" : "=f"(gn) : "l"(gbp) : "memory"); }
#pragma unroll
            for (int r = 0; r < 2; r++) {
              float z[2];
              float& gt = gate[(G * 2 + r) % NC2];
#pragma unroll
              for (int e = 0; e < 2; e++) {
                const float v = acc[4 * G + 2 * r + e];
                z[e] = fmaf(v, tanh_fast(v * fmaf(v, v, gt)), v);
                if (z2.value) { s[r] = fmaf(z[e], 0x1p-60f, s[r]); qq[r] = fmaf(z[e], z[e], qq[r]); }
              }
              const uint32_t pk = pack2(z[0], z[1]);
              if (z2.value) {
                stg32(zd + G * 128 + r * 4608, hsub2(pk, off2));
                gt = fmaf(qq[r], s[r], gb);
              } else {
                if ((G & 3) == 3) stg128(zd + (G >> 2) * 4096 + r * 1024, qa[r][0], qa[r][1], qa[r][2], pk);
                else qa[r][G & 3] = pk;
              }
            }
          }
        };
#pragma unroll 1
        for (int mb = 0;; mb++) {
          if (half) gelu(Int<0>{}); else gelu(Int<1>{});
          if (mb) break;
          zstat(0, !half);
#pragma unroll
          for (int i = 0; i < 80; i++) acc[i] = acc[80 + i];
          zd += half ? 8 * ZB : 128 * ZB;
        }
        mbar_wait_c(bars + B_GATE3, L);
        signal(half ? EV_Z1 : EV_ZN);
        SCLK(half * 11 + 10);
        TRC(tr, w, tb + 8 + half * 4);
      }
      }
      PHASE;
      const uint32_t aoff = (pw * 64 + pq * 16 + (lane & 15)) * 128 + (((lane >> 4) ^ (lane & 7)) << 4);
      uint32_t hA[18][4];
      {
        float acc[144];
        {
          const uint32_t c16 = lds32(sb + SM_OFF + 12), a[4] = {c16, c16, c16, c16};
          wgmma_fence();
          wgmma_rs_n144(acc, a, dsc<0, 0>(dlo(sb + SM_CV + 512, 0), 0), 0);
          wgmma_rs_n144(acc + 72, a, dsc<0, 0>(dlo(sb + SM_CV + 512, 0), 128), 0);
          wgmma_commit();
        }
        uint32_t prev = 0;
        auto stage = [&](int kb, bool odd) {
          mbar_wait_c(bars + B_FULL + c.s * 8, c.ph);
          TRC(tr && kb == 0, w, tb + 13);
          SCLK(22 + kb);
          const uint32_t st = sb + c.s * ST_BYTES, db = dlo(st + ST_B, 4608), rt = sb + SM_RT + kb * 128 + t * 8;
          uint32_t a[4][4];
#pragma unroll
          for (int kk = 0; kk < 4; kk++) {
            uint32_t r[4];
            ldsm4(r, st + (aoff ^ (kk << 5)));
            const uint2 sc = lds64(rt + kk * 32);
            a[kk][0] = hmul2(__byte_perm(r[0], r[2], 0x5410), sc.x); a[kk][2] = hmul2(__byte_perm(r[0], r[2], 0x7632), sc.y);
            a[kk][1] = hmul2(__byte_perm(r[1], r[3], 0x5410), sc.x); a[kk][3] = hmul2(__byte_perm(r[1], r[3], 0x7632), sc.y);
          }
          if (!odd && kb + w == 0) bar_sync(6, 256);
          wgmma_fence();
#pragma unroll
          for (int i = 0; i < 8; i++) {
            const int kk = i & 3, hf = i >> 2;
            wgmma_rs_n144(acc + hf * 72, a[kk], dsc<128, 0>(db, kk * 9216 + hf * 2304), 1);
            if (i == 0) { wgmma_commit(); wgmma_wait<1>(); if (kb) release(prev); }
            if (i == 3) wgmma_commit();
          }
          wgmma_commit();
          prev = c.s; c.next();
        };
#pragma unroll 1
        for (int kb = 0; kb < 32; kb += 2) {
          if (!(kb & 7)) mbar_wait_c(bars + B_RT + kb, L);
          stage(kb, false);
          stage(kb + 1, true);
        }
        mbar_wait_c(bars + B_CV + pw * 8, L);
        const float gk = 0.5f / GA;
        const float c1 = __uint_as_float(lds32(sb + SM_OFF + 4));
        const float gb0 = -gk * (c1 + __uint_as_float(lds32(sb + SM_CV + pw * 256 + (16 * pq + g) * 4))), gb1 = -gk * (c1 + __uint_as_float(lds32(sb + SM_CV + pw * 256 + (16 * pq + g + 8) * 4)));
        if (w == 1) { mbar_wait_c(bars + B_FULL + c.s * 8, c.ph); release(c.s); c.next(); }
        mbar_wait_c(bars + B_FULL + c.s * 8, c.ph);
        const uint32_t zs = sb + c.s * ST_BYTES + ST_B + (tid & 127) * 16;
        uint4 zl, zh;
#pragma unroll
        for (int u = 0; u < 18; u++) {
          if (u == 0) wgmma_wait<1>();
          if (u == 9) {
            wgmma_wait<0>();
            release(prev);
            if (L == 0) signal(EV_PT);
            TRC(tr, w, tb + 14);
            SCLK(54);
          }
          if (!(u & 1)) { zl = lds128v(zs + u * 2048); zh = lds128v(zs + u * 2048 + 2048); }
          const uint4 z = (u & 1) ? make_uint4(zl.z, zh.z, zl.w, zh.w) : make_uint4(zl.x, zh.x, zl.y, zh.y);
          hA[u][0] = hmul2(z.x, pack2(fmaf(acc[8 * u], gk, gb0), fmaf(acc[8 * u + 1], gk, gb0)));
          hA[u][1] = hmul2(z.y, pack2(fmaf(acc[8 * u + 2], gk, gb1), fmaf(acc[8 * u + 3], gk, gb1)));
          hA[u][2] = hmul2(z.z, pack2(fmaf(acc[8 * u + 4], gk, gb0), fmaf(acc[8 * u + 5], gk, gb0)));
          hA[u][3] = hmul2(z.w, pack2(fmaf(acc[8 * u + 6], gk, gb1), fmaf(acc[8 * u + 7], gk, gb1)));
        }
        __syncwarp();
        asm volatile("{\n.reg .pred p;\nsetp.lt.u32 p, %1, 2;\n@p mbarrier.arrive.shared::cluster.b64 _, [%0];\n}" ::"r"(ebar + c.s * 8), "r"(lane | (zh.x & Q.zero)) : "memory");
        c.next();
        if (w == 0) { mbar_wait_c(bars + B_FULL + c.s * 8, c.ph); release(c.s); c.next(); }
        TRC(tr, w, tb + 15);
      }
      {
        CLK_INIT;
        if (w == 1) bar_arrive(6, 256);
        uint4 v[4];
#pragma unroll
        for (int u = 0; u < 4; u++) v[u] = make_uint4(0u, 0u, 0u, 0u);
        uint32_t rl = sb + SM_STG + pw * 8192 + pq * 2048 + (lane >> 3) * 128 + (((lane & 7) ^ (lane >> 3)) << 4);
        uint8_t* rd = Q.out + (128 * rb + 32 * pq + 2 * (lane >> 3) + pw) * (DM * 2) + j * 128 + (lane & 7) * 16;
        asm volatile("" : "+r"(rl), "+l"(rd));
        auto send = [&](int u0, int u1) {
#pragma unroll
          for (int u = u0; u < u1; u++)
            asm volatile("red.relaxed.gpu.global.add.noftz.v4.bf16x2 [%0], {%1,%2,%3,%4};" ::"l"(rd + u * (8 * DM * 2)), "r"(v[u].x), "r"(v[u].y), "r"(v[u].z), "r"(v[u].w) : "memory");
        };
#pragma unroll 1
        for (int p = 0; p < 9; p++) {
          float acc[32];
          CLK(0);
          mbar_wait_c(bars + B_FULL + c.s * 8, c.ph);
          const uint32_t db = dlo(sb + c.s * ST_BYTES + ST_B, 0);
          CLK(1);
          bar_sync(6 + w, 256);
          CLK(2);
          wgmma_fence();
#pragma unroll
          for (int kk = 0; kk < 18; kk++) {
            wgmma_rs_n64(acc, hA[kk], dsc<1024, 1>(db, kk * 2048), kk != 0);
            if (kk == PPK && (w == 0 || p < 8)) bar_arrive(7 - w, 256);
          }
          wgmma_commit();
          CLK(3);
          if (p > 0) { send(NOW, 4); rd += p + j == 9 ? -1024 : 128; }
          CLK(5);
          wgmma_wait<0>();
          CLK(4);
          if (L == 0 || p < 5) release(c.s);
          c.next();
          TRC(tr && p == 8, w, tb + 16);
#pragma unroll
          for (int u = 0; u < 4; u++)
            stsm4(sb + SM_STG + (aoff ^ (u << 5)), pack2(acc[8 * u], acc[8 * u + 1]), pack2(acc[8 * u + 2], acc[8 * u + 3]), pack2(acc[8 * u + 4], acc[8 * u + 5]), pack2(acc[8 * u + 6], acc[8 * u + 7]));
          __syncwarp();
#pragma unroll
          for (int u = 0; u < 4; u++) v[u] = lds128(rl + u * 512 ^ (u & 1) << 6);
          send(0, NOW);
        }
        send(NOW, 4);
        TRC(tr, w, tb + 17);
        if (L == 0) signal(EV_PT);
        CLK_OUT;
        TRC(tr, w, tb + 18);
      }
    }
    if ((tid & 127) == 0) Q.flags[(rb * 2 + w) * 32 + FR_EP + j] = epoch + 1;
    if (tid == 0) Q.flags[FJ + j * 32 + FJ_EP + rb] = epoch + 1;
  }
}

typedef CUresult (*EncodeFn)(CUtensorMap*, CUtensorMapDataType, cuuint32_t, void*, const cuuint64_t*, const cuuint64_t*, const cuuint32_t*,
                             const cuuint32_t*, CUtensorMapInterleave, CUtensorMapSwizzle, CUtensorMapL2promotion, CUtensorMapFloatOOBfill);

static void make_map(EncodeFn fn, CUtensorMap* m, const void* ptr, int rank, uint64_t d0, uint64_t d1, uint64_t d2, uint64_t s1, uint64_t s2,
                     uint32_t b0, uint32_t b1, uint32_t b2, CUtensorMapSwizzle swz) {
  cuuint64_t dims[3] = {d0, d1, d2}, strides[2] = {s1, s2};
  cuuint32_t box[3] = {b0, b1, b2}, es[3] = {1, 1, 1};
  fn(m, CU_TENSOR_MAP_DATA_TYPE_BFLOAT16, rank, const_cast<void*>(ptr), dims, strides, box, es, CU_TENSOR_MAP_INTERLEAVE_NONE, swz,
     CU_TENSOR_MAP_L2_PROMOTION_L2_128B, CU_TENSOR_MAP_FLOAT_OOB_FILL_NONE);
}

}

extern "C" void kernel_launch(void* const* d_in, const int* in_sizes, int n_in, void* d_out, int out_size) {
  using namespace mk;
  (void)in_sizes; (void)n_in; (void)out_size;
  static EncodeFn fn = nullptr;
  static Scratch* sc = nullptr;
  if (!fn) {
    cudaDriverEntryPointQueryResult qr;
    cudaGetDriverEntryPoint("cuTensorMapEncodeTiled", (void**)&fn, cudaEnableDefault, &qr);
    cudaGetSymbolAddress((void**)&sc, g_scratch);
    cudaFuncSetAttribute(mega_kernel, cudaFuncAttributeMaxDynamicSharedMemorySize, SM_TOTAL);
  }
  Params p;
  Ptrs a;
  a.x = (const uint8_t*)d_in[0];
  a.wqkv = (const __nv_bfloat16*)d_in[1];
  a.wo = (const __nv_bfloat16*)d_in[2];
  a.w_in = (const __nv_bfloat16*)d_in[4];
  a.w_sp = (const __nv_bfloat16*)d_in[5];
  a.b_sp = (const __nv_bfloat16*)d_in[6];
  a.out = (uint8_t*)d_out;
  a.zero = 0;
  a.WQ = sc->WQ; a.flags = sc->flags; a.CSP = sc->CSP; a.XST = sc->XST; a.HALO = sc->HALO; a.ST1 = sc->ST1; a.ZST = sc->ZST; a.RT = sc->RT; a.Z = sc->Z; a.WO = sc->WO;
  make_map(fn, &p.wsp, a.w_sp, 3, 2048, 1024, 2, 8192, 4096, 64, 64, 2, CU_TENSOR_MAP_SWIZZLE_128B);
  for (int i = 0; i < 2; i++) {
    make_map(fn, &p.act[i], i ? a.out : a.x, 3, DM, 1024, 2, 2304, 1152, 64, 32, 2, CU_TENSOR_MAP_SWIZZLE_128B);
    make_map(fn, &p.res[i], i ? a.out : a.x, 3, DM, 1024, 2, 2304, 1152, 72, 32, 2, CU_TENSOR_MAP_SWIZZLE_NONE);
  }
  for (int i = 0; i < 2; i++) make_map(fn, &p.winb[i], a.w_in + 32 * i, 3, 64, 576, 72 - i, 9216, 128, 64, 16, 3, CU_TENSOR_MAP_SWIZZLE_128B);
  make_map(fn, &p.wins, a.w_in, 3, 64, 576, 72, 9216, 128, 64, 48, 1, CU_TENSOR_MAP_SWIZZLE_128B);
  make_map(fn, &p.wout, d_in[7], 2, 576, 2304, 1, 1152, 0, 64, 144, 1, CU_TENSOR_MAP_SWIZZLE_128B);
  mega_kernel<<<NGRID, 384, SM_TOTAL, cudaStreamPerThread>>>(a, p);
}
```
